```python
import torch

def _softmax(x, axis=-1):
    return torch.softmax(x, dim=axis)
def _gelu(x):
    return torch.nn.functional.gelu(x, approximate="tanh")
def _silu(x):
    return torch.nn.functional.silu(x)
def _sigmoid(x):
    return torch.sigmoid(x)
def _layernorm(x, axis=-1, eps=1e-5):
    m = x.mean(dim=axis, keepdim=True)
    v = x.var(dim=axis, keepdim=True, unbiased=False)
    return (x - m) / torch.sqrt(v + eps)
def _scatter_add(tgt, idx, src, axis=0):
    return tgt.clone().index_add_(axis, idx, src)
def _segment_sum(src, seg, n):
    out = torch.zeros((n,) + src.shape[1:], dtype=src.dtype)
    return out.index_add_(0, seg, src)
def _pad(x, pw):
    flat = tuple(v for pair in reversed(pw) for v in pair)
    return torch.nn.functional.pad(x, flat)

kernel_name = 'interleave_layers__ssm_conv_h3__mixer_s_mlp__prompt'

def setup_inputs():

    _w = (lambda a: (lambda t: t.to(torch.bfloat16) if t.is_floating_point() else t)(torch.as_tensor(a)))
    def _A_setup():
        B, S, D = 1, 2048, 1024
        ks = 4
        return {
            "q": _w((lambda *s: torch.randn(*s, dtype=torch.bfloat16) * 0.05)(B, S, D)),
            "k": _w((lambda *s: torch.randn(*s, dtype=torch.bfloat16) * 0.4)(B, S, D)),
            "v": _w((lambda *s: torch.randn(*s, dtype=torch.bfloat16) * 0.4)(B, S, D)),
            "shift_k": _w((lambda *s: torch.randn(*s, dtype=torch.bfloat16) * 0.4)(D, ks) * 0.5),
            "ssm_k": _w((lambda *s: torch.randn(*s, dtype=torch.bfloat16) * 0.4)(D, S) * (1.0 / S ** 0.5)),
            "ssm_D": _w((lambda *s: torch.randn(*s, dtype=torch.bfloat16) * 0.4)(D)),
        }
    _A_in = _A_setup()

    def _B_setup():
        B, S, D, F = 1, 2048, 1024, 3584
        return {
            "x":  _w((lambda *s: torch.randn(*s, dtype=torch.bfloat16) * 0.05)(B, S, D)),
            "w1": _w((lambda *s: torch.randn(*s, dtype=torch.bfloat16) * 1.6)(D, D) * (D ** -0.5)),
            "w2": _w((lambda *s: torch.randn(*s, dtype=torch.bfloat16) * 1.6)(D, D) * (D ** -0.5)),
            "w3": _w((lambda *s: torch.randn(*s, dtype=torch.bfloat16) * 1.6)(D, F) * (D ** -0.5)),
            "w4": _w((lambda *s: torch.randn(*s, dtype=torch.bfloat16) * 1.6)(F, D) * (F ** -0.5)),
        }
    _B_in = _B_setup()

    return {
        "A_q": _A_in["q"],
        "A_k": _A_in["k"],
        "A_v": _A_in["v"],
        "A_shift_k": _A_in["shift_k"],
        "A_ssm_k": _A_in["ssm_k"],
        "A_ssm_D": _A_in["ssm_D"],
        "B_x": _B_in["x"],
        "B_w1": _B_in["w1"],
        "B_w2": _B_in["w2"],
        "B_w3": _B_in["w3"],
        "B_w4": _B_in["w4"],
    }

def reference(A_q, A_k, A_v, A_shift_k, A_ssm_k, A_ssm_D, B_x, B_w1, B_w2, B_w3, B_w4):
    def _A_ref(q, k, v, shift_k, ssm_k, ssm_D):
        B, S, D = q.shape
        ks = shift_k.shape[-1]
        k_pad = _pad(k, ((0, 0), (ks - 1, 0), (0, 0)))
        k_shift = torch.zeros_like(k)
        for t in range(ks):
            k_shift = k_shift + k_pad[:, t:t + S, :] * shift_k[:, ks - 1 - t][None, None, :]
        kv = k_shift * v
        L = 2 * S
        kv_pad = _pad(kv, ((0, 0), (0, S), (0, 0)))
        kf_pad = _pad(ssm_k, ((0, 0), (0, S)))
        kv_f = (lambda x, axes=(-2,-1): torch.fft.rfft2(x.float(), dim=axes))(kv_pad[:, None, :, :], axes=(1, 2))
        kf_f = (lambda x, axes=(-2,-1): torch.fft.rfft2(x.float(), dim=axes))(kf_pad[:, None, :], axes=(1, 2))
        kf_f = (lambda x, *d: x.permute(*d))(kf_f, 1, 2, 0)
        y_f = kv_f * kf_f[None, :, :, :]
        y = (lambda x, s, axes=(-2,-1): torch.fft.irfft2(x, s=s, dim=axes).to(torch.bfloat16))(y_f, (1, L), axes=(1, 2))[:, 0, :S, :]
        y = y + kv * ssm_D[None, None, :]
        return q * y

    def _B_ref(x, w1, w2, w3, w4):
        B, S, D = x.shape
        h = _gelu(_layernorm(x, axis=-1) @ w1)
        c = D // 4
        g0 = _pad(h[:, :, 0*c:1*c], ((0, 0), (1, 0), (0, 0)))[:, :S, :]
        g1 = _pad(h[:, :, 1*c:2*c], ((0, 0), (0, 1), (0, 0)))[:, 1:, :]
        g2 = _pad(h[:, :, 2*c:3*c], ((0, 0), (2, 0), (0, 0)))[:, :S, :]
        g3 = _pad(h[:, :, 3*c:   ], ((0, 0), (0, 2), (0, 0)))[:, 2:, :]
        hs = torch.concatenate([g0, g1, g2, g3], axis=-1) @ w2
        x1 = x + hs
        h2 = _gelu(_layernorm(x1, axis=-1) @ w3) @ w4
        return x1 + h2

    x = A_q
    x = x + _A_ref(_layernorm(x, axis=-1), A_k, A_v, A_shift_k, A_ssm_k, A_ssm_D)
    x = x + _B_ref(_layernorm(x, axis=-1), B_w1, B_w2, B_w3, B_w4)
    x = x + _A_ref(_layernorm(x, axis=-1), A_k, A_v, A_shift_k, A_ssm_k, A_ssm_D)
    x = x + _B_ref(_layernorm(x, axis=-1), B_w1, B_w2, B_w3, B_w4)
    return x
```

```cpp
#include <cuda_runtime.h>
#include <cuda_bf16.h>
#include <cuda.h>
#include <stdint.h>

namespace {

typedef __nv_bfloat16 bf16;
constexpr int SEQ = 2048, DM = 1024, FF = 3584;
constexpr float LN_EPS = 1e-5f;

constexpr int CB_BYTES = SEQ * 16;
__device__ __align__(1024) bf16 g_x3[2][SEQ * DM];
__device__ __align__(1024) bf16 g_h[SEQ * DM];
__device__ __align__(1024) bf16 g_x1[SEQ * DM];
__device__ __align__(1024) bf16 g_hid[SEQ * FF];
__device__ __align__(1024) bf16 g_y[SEQ * DM];
__device__ __align__(128) float2 g_qstat[SEQ];
__device__ __align__(128) float2 g_part[5][8][SEQ];
__device__ __align__(128) float g_cs1[4][DM];
__device__ __align__(128) float g_cs3[FF];
constexpr int FS = 8;
constexpr int FLAG_PROG = 32 * 8 * FS;
constexpr int FLAG_WORDS = FLAG_PROG + 2 * 8;
__device__ __align__(128) uint32_t g_flag[FLAG_WORDS];
__device__ __align__(128) uint32_t g_role[4];
__device__ __align__(128) uint32_t g_qcnt;

__device__ __forceinline__ uint32_t smem_u32(const void* p) { return (uint32_t)__cvta_generic_to_shared(p); }
__device__ __forceinline__ uint32_t opaque(uint32_t x) { uint32_t y; asm volatile("mov.u32 %0, %1;" : "=r"(y) : "r"(x)); return y; }
__device__ __forceinline__ void mbar_init(uint32_t bar, uint32_t cnt) { asm volatile("mbarrier.init.shared::cta.b64 [%0], %1;" :: "r"(bar), "r"(cnt)); }
__device__ __forceinline__ void mbar_expect_tx(uint32_t bar, uint32_t bytes) {
  asm volatile("mbarrier.arrive.expect_tx.shared::cta.b64 _, [%0], %1;" :: "r"(bar), "r"(bytes) : "memory");
}
__device__ __forceinline__ void mbar_arrive(uint32_t bar) { asm volatile("mbarrier.arrive.shared::cta.b64 _, [%0];" :: "r"(bar) : "memory"); }
__device__ __forceinline__ void mbar_arrive_if(uint32_t bar, bool cond) {
  asm volatile("{\n.reg .pred p;\nsetp.ne.b32 p, %1, 0;\n@p mbarrier.arrive.shared::cta.b64 _, [%0];\n}" :: "r"(bar), "r"((uint32_t)cond) : "memory");
}
constexpr int SPIN_LIMIT = 1 << 18;
__device__ __forceinline__ bool mbar_try(uint32_t bar, uint32_t parity) {
  uint32_t done;
  asm volatile("{\n.reg .pred p;\nmbarrier.try_wait.parity.shared::cta.b64 p, [%1], %2;\nselp.b32 %0, 1, 0, p;\n}"
               : "=r"(done) : "r"(bar), "r"(parity) : "memory");
  return done != 0;
}
__device__ __forceinline__ bool spin_give_up(uint32_t abort_addr, int& spins, uint32_t tag_a, uint32_t tag_b) {
  uint32_t dead;
  asm volatile("ld.volatile.shared.u32 %0, [%1];" : "=r"(dead) : "r"(abort_addr) : "memory");
  if (++spins > SPIN_LIMIT) { asm volatile("st.volatile.shared.u32 [%0], %1;" :: "r"(abort_addr), "r"(1) : "memory"); dead = 1; }
  return dead != 0;
}
__device__ __forceinline__ void mbar_wait(uint32_t bar, uint32_t parity, uint32_t abort_addr) {
  if (__builtin_expect(mbar_try(bar, parity), 1)) return;
  int spins = 0;
  while (!mbar_try(bar, parity)) { if (spin_give_up(abort_addr, spins, bar - abort_addr, parity)) break; }
}
__device__ __forceinline__ bool elect_one() {
  uint32_t p;
  asm volatile("{\n.reg .pred P;\nelect.sync _|P, 0xffffffff;\nselp.b32 %0, 1, 0, P;\n}" : "=r"(p));
  return p != 0;
}
__device__ __forceinline__ void fence_async_smem() { asm volatile("fence.proxy.async.shared::cta;" ::: "memory"); }
__device__ __forceinline__ void fence_async_global() { asm volatile("fence.proxy.async.global;" ::: "memory"); }
__device__ __forceinline__ void named_bar(int id, int n) { asm volatile("bar.sync %0, %1;" :: "r"(id), "r"(n) : "memory"); }
__device__ __forceinline__ uint4 ld_nc_u4(const void* p) {
  uint4 v; asm volatile("ld.global.nc.L1::no_allocate.v4.u32 {%0,%1,%2,%3}, [%4];" : "=r"(v.x), "=r"(v.y), "=r"(v.z), "=r"(v.w) : "l"(p)); return v;
}
__device__ __forceinline__ void tma_2d_mc(uint32_t dst, const CUtensorMap* m, uint32_t bar, int c0, int c1, uint16_t mask) {
  asm volatile("cp.async.bulk.tensor.2d.shared::cluster.global.mbarrier::complete_tx::bytes.multicast::cluster [%0], [%1, {%3, %4}], [%2], %5;"
               :: "r"(dst), "l"(m), "r"(bar), "r"(c0), "r"(c1), "h"(mask) : "memory");
}
__device__ __forceinline__ void tma_2d(uint32_t dst, const CUtensorMap* m, uint32_t bar, int c0, int c1) {
  asm volatile("cp.async.bulk.tensor.2d.shared::cluster.global.mbarrier::complete_tx::bytes [%0], [%1, {%3, %4}], [%2];"
               :: "r"(dst), "l"(m), "r"(bar), "r"(c0), "r"(c1) : "memory");
}
__device__ __forceinline__ void bulk_copy_cluster(uint32_t dst, uint32_t src, uint32_t bytes, uint32_t bar) {
  asm volatile("cp.async.bulk.shared::cluster.shared::cta.mbarrier::complete_tx::bytes [%0], [%1], %2, [%3];"
               :: "r"(dst), "r"(src), "r"(bytes), "r"(bar) : "memory");
}
__device__ __forceinline__ uint32_t mapa(uint32_t addr, uint32_t cta) {
  uint32_t r; asm volatile("mapa.shared::cluster.u32 %0, %1, %2;" : "=r"(r) : "r"(addr), "r"(cta)); return r;
}
__device__ __forceinline__ void bulk_store(void* dst, uint32_t src, uint32_t bytes) {
  asm volatile("cp.async.bulk.global.shared::cta.bulk_group [%0], [%1], %2;" :: "l"(dst), "r"(src), "r"(bytes) : "memory");
}
__device__ __forceinline__ void tma_3d(uint32_t dst, const CUtensorMap* m, uint32_t bar, int c0, int c1, int c2) {
  asm volatile("cp.async.bulk.tensor.3d.shared::cluster.global.mbarrier::complete_tx::bytes [%0], [%1, {%3, %4, %5}], [%2];"
               :: "r"(dst), "l"(m), "r"(bar), "r"(c0), "r"(c1), "r"(c2) : "memory");
}
__device__ __forceinline__ void tma_store_2d(const CUtensorMap* m, uint32_t src, int c0, int c1) {
  asm volatile("cp.async.bulk.tensor.2d.global.shared::cta.bulk_group [%0, {%2, %3}], [%1];" :: "l"(m), "r"(src), "r"(c0), "r"(c1) : "memory");
}
__device__ __forceinline__ void bulk_commit() { asm volatile("cp.async.bulk.commit_group;" ::: "memory"); }
__device__ __forceinline__ void bulk_wait_all() { asm volatile("cp.async.bulk.wait_group 0;" ::: "memory"); }
__device__ __forceinline__ void prefetch_l2(const void* p, uint32_t bytes) { asm volatile("cp.async.bulk.prefetch.L2.global [%0], %1;" :: "l"(p), "r"(bytes) : "memory"); }
__device__ __forceinline__ void cluster_exit_barrier() {
  __syncwarp();
  asm volatile("barrier.cluster.arrive.relaxed;\nbarrier.cluster.wait;" ::: "memory");
}
__device__ __forceinline__ void wg_fence() { asm volatile("wgmma.fence.sync.aligned;" ::: "memory"); }
__device__ __forceinline__ void wg_commit() { asm volatile("wgmma.commit_group.sync.aligned;" ::: "memory"); }
template <int N> __device__ __forceinline__ void wg_wait() { asm volatile("wgmma.wait_group.sync.aligned %0;" :: "n"(N) : "memory"); }
template <int R> __device__ __forceinline__ void reg_alloc() { asm volatile("setmaxnreg.inc.sync.aligned.u32 %0;" :: "n"(R)); }
template <int R> __device__ __forceinline__ void reg_dealloc() { asm volatile("setmaxnreg.dec.sync.aligned.u32 %0;" :: "n"(R)); }
__device__ __forceinline__ void ldsm_x4(uint32_t addr, uint32_t& r0, uint32_t& r1, uint32_t& r2, uint32_t& r3) {
  asm volatile("ldmatrix.sync.aligned.m8n8.x4.shared.b16 {%0,%1,%2,%3}, [%4];" : "=r"(r0), "=r"(r1), "=r"(r2), "=r"(r3) : "r"(addr));
}
__device__ __forceinline__ void ldsm_x4_t(uint32_t addr, uint32_t& r0, uint32_t& r1, uint32_t& r2, uint32_t& r3) {
  asm volatile("ldmatrix.sync.aligned.m8n8.x4.trans.shared.b16 {%0,%1,%2,%3}, [%4];" : "=r"(r0), "=r"(r1), "=r"(r2), "=r"(r3) : "r"(addr));
}
__device__ __forceinline__ void stsm_x4(uint32_t addr, uint32_t r0, uint32_t r1, uint32_t r2, uint32_t r3) {
  asm volatile("stmatrix.sync.aligned.m8n8.x4.shared.b16 [%0], {%1,%2,%3,%4};" :: "r"(addr), "r"(r0), "r"(r1), "r"(r2), "r"(r3) : "memory");
}
__device__ __forceinline__ float2 lds_f2(uint32_t addr) { float2 v; asm volatile("ld.shared.v2.f32 {%0,%1}, [%2];" : "=f"(v.x), "=f"(v.y) : "r"(addr)); return v; }
__device__ __forceinline__ void sts16(uint32_t addr, uint16_t v) { asm volatile("st.shared.u16 [%0], %1;" :: "r"(addr), "h"(v) : "memory"); }
__device__ __forceinline__ void sts32(uint32_t addr, uint32_t v) { asm volatile("st.shared.u32 [%0], %1;" :: "r"(addr), "r"(v) : "memory"); }
__device__ __forceinline__ void sts128(uint32_t addr, uint4 v) {
  asm volatile("st.shared.v4.u32 [%0], {%1,%2,%3,%4};" :: "r"(addr), "r"(v.x), "r"(v.y), "r"(v.z), "r"(v.w) : "memory");
}
__device__ __forceinline__ void mma16816(float (&d)[4], uint32_t a0, uint32_t a1, uint32_t a2, uint32_t a3, uint32_t b0, uint32_t b1) {
  asm("mma.sync.aligned.m16n8k16.row.col.f32.bf16.bf16.f32 {%0,%1,%2,%3}, {%4,%5,%6,%7}, {%8,%9}, {%0,%1,%2,%3};"
               : "+f"(d[0]), "+f"(d[1]), "+f"(d[2]), "+f"(d[3]) : "r"(a0), "r"(a1), "r"(a2), "r"(a3), "r"(b0), "r"(b1));
}
__device__ __forceinline__ uint32_t pack_bf16(float lo, float hi) {
  uint32_t r; asm("cvt.rn.bf16x2.f32 %0, %1, %2;" : "=r"(r) : "f"(hi), "f"(lo)); return r;
}
__device__ __forceinline__ float bf_lo(uint32_t v) { return __uint_as_float(v << 16); }
__device__ __forceinline__ float bf_hi(uint32_t v) { return __uint_as_float(v & 0xffff0000u); }
__device__ __forceinline__ uint32_t bmul2(uint32_t a, uint32_t b) { uint32_t r; asm("mul.rn.bf16x2 %0, %1, %2;" : "=r"(r) : "r"(a), "r"(b)); return r; }
__device__ __forceinline__ uint32_t badd2(uint32_t a, uint32_t b) { uint32_t r; asm("add.rn.bf16x2 %0, %1, %2;" : "=r"(r) : "r"(a), "r"(b)); return r; }
#define STAMP(idx) do {} while (0)
#define MSTAMP(idx) do {} while (0)
#define BSTAMP(idx, saddr) do {} while (0)

__device__ __forceinline__ uint32_t pack_f16(float lo, float hi) {
  uint32_t r; asm("cvt.rn.satfinite.f16x2.f32 %0, %1, %2;" : "=r"(r) : "f"(hi), "f"(lo)); return r;
}
__device__ __forceinline__ uint32_t gelu_pair_f16(uint32_t h) {
  const uint32_t c0 = 0x3e623e62u, c1 = 0x34913491u;
  uint32_t u, p, z, t, r, o;
  asm("mul.rn.f16x2 %0, %1, %1;" : "=r"(u) : "r"(h));
  asm("fma.rn.f16x2 %0, %1, %2, %3;" : "=r"(p) : "r"(u), "r"(c1), "r"(c0));
  asm("mul.rn.f16x2 %0, %1, %2;" : "=r"(z) : "r"(h), "r"(p));
  asm("tanh.approx.f16x2 %0, %1;" : "=r"(t) : "r"(z));
  asm("fma.rn.f16x2 %0, %1, %2, %1;" : "=r"(r) : "r"(h), "r"(t));
  float lo, hi;
  asm("{\n.reg .f16 a, b;\nmov.b32 {a, b}, %2;\ncvt.f32.f16 %0, a;\ncvt.f32.f16 %1, b;\n}" : "=f"(lo), "=f"(hi) : "r"(r));
  asm("cvt.rn.bf16x2.f32 %0, %1, %2;" : "=r"(o) : "f"(hi), "f"(lo));
  return o;
}
__device__ __forceinline__ float gelu_from_half(float h) {
  const float c0 = 2.f * 0.7978845608028654f, c1 = 8.f * 0.7978845608028654f * 0.044715f;
  float z = h * fmaf(h * h, c1, c0);
  float t; asm("tanh.approx.f32 %0, %1;" : "=f"(t) : "f"(z));
  return fmaf(h, t, h);
}
__device__ __forceinline__ void wgmma_ss_n128(float (&d)[64], uint32_t a_lo, uint32_t b_lo) {
  asm volatile(
    "{\n.reg .b64 da, db;\nmov.b64 da, {%64, 8};\nmov.b64 db, {%65, 0x40000040};\n"
    "wgmma.mma_async.sync.aligned.m64n128k16.f32.bf16.bf16 "
    "{%0, %1, %2, %3, %4, %5, %6, %7, %8, %9, %10, %11, %12, %13, %14, %15, "
    "%16, %17, %18, %19, %20, %21, %22, %23, %24, %25, %26, %27, %28, %29, %30, %31, "
    "%32, %33, %34, %35, %36, %37, %38, %39, %40, %41, %42, %43, %44, %45, %46, %47, "
    "%48, %49, %50, %51, %52, %53, %54, %55, %56, %57, %58, %59, %60, %61, %62, %63}, "
    "da, db, 1, 1, 1, 0, 1;\n}\n"
    : "+f"(d[0]), "+f"(d[1]), "+f"(d[2]), "+f"(d[3]), "+f"(d[4]), "+f"(d[5]), "+f"(d[6]), "+f"(d[7]),
      "+f"(d[8]), "+f"(d[9]), "+f"(d[10]), "+f"(d[11]), "+f"(d[12]), "+f"(d[13]), "+f"(d[14]), "+f"(d[15]),
      "+f"(d[16]), "+f"(d[17]), "+f"(d[18]), "+f"(d[19]), "+f"(d[20]), "+f"(d[21]), "+f"(d[22]), "+f"(d[23]),
      "+f"(d[24]), "+f"(d[25]), "+f"(d[26]), "+f"(d[27]), "+f"(d[28]), "+f"(d[29]), "+f"(d[30]), "+f"(d[31]),
      "+f"(d[32]), "+f"(d[33]), "+f"(d[34]), "+f"(d[35]), "+f"(d[36]), "+f"(d[37]), "+f"(d[38]), "+f"(d[39]),
      "+f"(d[40]), "+f"(d[41]), "+f"(d[42]), "+f"(d[43]), "+f"(d[44]), "+f"(d[45]), "+f"(d[46]), "+f"(d[47]),
      "+f"(d[48]), "+f"(d[49]), "+f"(d[50]), "+f"(d[51]), "+f"(d[52]), "+f"(d[53]), "+f"(d[54]), "+f"(d[55]),
      "+f"(d[56]), "+f"(d[57]), "+f"(d[58]), "+f"(d[59]), "+f"(d[60]), "+f"(d[61]), "+f"(d[62]), "+f"(d[63])
    : "r"(a_lo), "r"(b_lo));
}
__device__ __forceinline__ void wgmma_ss_n192(float (&d)[96], uint32_t a_lo, uint32_t b_lo) {
  asm volatile(
    "{\n.reg .b64 da, db;\nmov.b64 da, {%96, 8};\nmov.b64 db, {%97, 0x40000040};\n"
    "wgmma.mma_async.sync.aligned.m64n192k16.f32.bf16.bf16 "
    "{%0, %1, %2, %3, %4, %5, %6, %7, %8, %9, %10, %11, %12, %13, %14, %15, "
    "%16, %17, %18, %19, %20, %21, %22, %23, %24, %25, %26, %27, %28, %29, %30, %31, "
    "%32, %33, %34, %35, %36, %37, %38, %39, %40, %41, %42, %43, %44, %45, %46, %47, "
    "%48, %49, %50, %51, %52, %53, %54, %55, %56, %57, %58, %59, %60, %61, %62, %63, "
    "%64, %65, %66, %67, %68, %69, %70, %71, %72, %73, %74, %75, %76, %77, %78, %79, "
    "%80, %81, %82, %83, %84, %85, %86, %87, %88, %89, %90, %91, %92, %93, %94, %95}, "
    "da, db, 1, 1, 1, 0, 1;\n}\n"
    : "+f"(d[0]), "+f"(d[1]), "+f"(d[2]), "+f"(d[3]), "+f"(d[4]), "+f"(d[5]), "+f"(d[6]), "+f"(d[7]),
      "+f"(d[8]), "+f"(d[9]), "+f"(d[10]), "+f"(d[11]), "+f"(d[12]), "+f"(d[13]), "+f"(d[14]), "+f"(d[15]),
      "+f"(d[16]), "+f"(d[17]), "+f"(d[18]), "+f"(d[19]), "+f"(d[20]), "+f"(d[21]), "+f"(d[22]), "+f"(d[23]),
      "+f"(d[24]), "+f"(d[25]), "+f"(d[26]), "+f"(d[27]), "+f"(d[28]), "+f"(d[29]), "+f"(d[30]), "+f"(d[31]),
      "+f"(d[32]), "+f"(d[33]), "+f"(d[34]), "+f"(d[35]), "+f"(d[36]), "+f"(d[37]), "+f"(d[38]), "+f"(d[39]),
      "+f"(d[40]), "+f"(d[41]), "+f"(d[42]), "+f"(d[43]), "+f"(d[44]), "+f"(d[45]), "+f"(d[46]), "+f"(d[47]),
      "+f"(d[48]), "+f"(d[49]), "+f"(d[50]), "+f"(d[51]), "+f"(d[52]), "+f"(d[53]), "+f"(d[54]), "+f"(d[55]),
      "+f"(d[56]), "+f"(d[57]), "+f"(d[58]), "+f"(d[59]), "+f"(d[60]), "+f"(d[61]), "+f"(d[62]), "+f"(d[63]),
      "+f"(d[64]), "+f"(d[65]), "+f"(d[66]), "+f"(d[67]), "+f"(d[68]), "+f"(d[69]), "+f"(d[70]), "+f"(d[71]),
      "+f"(d[72]), "+f"(d[73]), "+f"(d[74]), "+f"(d[75]), "+f"(d[76]), "+f"(d[77]), "+f"(d[78]), "+f"(d[79]),
      "+f"(d[80]), "+f"(d[81]), "+f"(d[82]), "+f"(d[83]), "+f"(d[84]), "+f"(d[85]), "+f"(d[86]), "+f"(d[87]),
      "+f"(d[88]), "+f"(d[89]), "+f"(d[90]), "+f"(d[91]), "+f"(d[92]), "+f"(d[93]), "+f"(d[94]), "+f"(d[95])
    : "r"(a_lo), "r"(b_lo));
}
__device__ __forceinline__ void wgmma_ss_n256(float (&d)[128], uint32_t a_lo, uint32_t b_lo) {
  asm volatile(
    "{\n.reg .b64 da, db;\nmov.b64 da, {%128, 8};\nmov.b64 db, {%129, 0x40000040};\n"
    "wgmma.mma_async.sync.aligned.m64n256k16.f32.bf16.bf16 "
    "{%0, %1, %2, %3, %4, %5, %6, %7, %8, %9, %10, %11, %12, %13, %14, %15, "
    "%16, %17, %18, %19, %20, %21, %22, %23, %24, %25, %26, %27, %28, %29, %30, %31, "
    "%32, %33, %34, %35, %36, %37, %38, %39, %40, %41, %42, %43, %44, %45, %46, %47, "
    "%48, %49, %50, %51, %52, %53, %54, %55, %56, %57, %58, %59, %60, %61, %62, %63, "
    "%64, %65, %66, %67, %68, %69, %70, %71, %72, %73, %74, %75, %76, %77, %78, %79, "
    "%80, %81, %82, %83, %84, %85, %86, %87, %88, %89, %90, %91, %92, %93, %94, %95, "
    "%96, %97, %98, %99, %100, %101, %102, %103, %104, %105, %106, %107, %108, %109, %110, %111, "
    "%112, %113, %114, %115, %116, %117, %118, %119, %120, %121, %122, %123, %124, %125, %126, %127}, "
    "da, db, 1, 1, 1, 0, 1;\n}\n"
    : "+f"(d[0]), "+f"(d[1]), "+f"(d[2]), "+f"(d[3]), "+f"(d[4]), "+f"(d[5]), "+f"(d[6]), "+f"(d[7]),
      "+f"(d[8]), "+f"(d[9]), "+f"(d[10]), "+f"(d[11]), "+f"(d[12]), "+f"(d[13]), "+f"(d[14]), "+f"(d[15]),
      "+f"(d[16]), "+f"(d[17]), "+f"(d[18]), "+f"(d[19]), "+f"(d[20]), "+f"(d[21]), "+f"(d[22]), "+f"(d[23]),
      "+f"(d[24]), "+f"(d[25]), "+f"(d[26]), "+f"(d[27]), "+f"(d[28]), "+f"(d[29]), "+f"(d[30]), "+f"(d[31]),
      "+f"(d[32]), "+f"(d[33]), "+f"(d[34]), "+f"(d[35]), "+f"(d[36]), "+f"(d[37]), "+f"(d[38]), "+f"(d[39]),
      "+f"(d[40]), "+f"(d[41]), "+f"(d[42]), "+f"(d[43]), "+f"(d[44]), "+f"(d[45]), "+f"(d[46]), "+f"(d[47]),
      "+f"(d[48]), "+f"(d[49]), "+f"(d[50]), "+f"(d[51]), "+f"(d[52]), "+f"(d[53]), "+f"(d[54]), "+f"(d[55]),
      "+f"(d[56]), "+f"(d[57]), "+f"(d[58]), "+f"(d[59]), "+f"(d[60]), "+f"(d[61]), "+f"(d[62]), "+f"(d[63]),
      "+f"(d[64]), "+f"(d[65]), "+f"(d[66]), "+f"(d[67]), "+f"(d[68]), "+f"(d[69]), "+f"(d[70]), "+f"(d[71]),
      "+f"(d[72]), "+f"(d[73]), "+f"(d[74]), "+f"(d[75]), "+f"(d[76]), "+f"(d[77]), "+f"(d[78]), "+f"(d[79]),
      "+f"(d[80]), "+f"(d[81]), "+f"(d[82]), "+f"(d[83]), "+f"(d[84]), "+f"(d[85]), "+f"(d[86]), "+f"(d[87]),
      "+f"(d[88]), "+f"(d[89]), "+f"(d[90]), "+f"(d[91]), "+f"(d[92]), "+f"(d[93]), "+f"(d[94]), "+f"(d[95]),
      "+f"(d[96]), "+f"(d[97]), "+f"(d[98]), "+f"(d[99]), "+f"(d[100]), "+f"(d[101]), "+f"(d[102]), "+f"(d[103]),
      "+f"(d[104]), "+f"(d[105]), "+f"(d[106]), "+f"(d[107]), "+f"(d[108]), "+f"(d[109]), "+f"(d[110]), "+f"(d[111]),
      "+f"(d[112]), "+f"(d[113]), "+f"(d[114]), "+f"(d[115]), "+f"(d[116]), "+f"(d[117]), "+f"(d[118]), "+f"(d[119]),
      "+f"(d[120]), "+f"(d[121]), "+f"(d[122]), "+f"(d[123]), "+f"(d[124]), "+f"(d[125]), "+f"(d[126]), "+f"(d[127])
    : "r"(a_lo), "r"(b_lo));
}
__device__ __forceinline__ void wgmma_ss_n128_p(float (&d)[64], uint32_t a_lo, uint32_t b_lo, uint32_t keep) {
  asm volatile(
    "{\n.reg .pred p;\nsetp.ne.b32 p, %66, 0;\n"
    "{\n.reg .b64 da, db;\nmov.b64 da, {%64, 8};\nmov.b64 db, {%65, 0x40000040};\n"
    "wgmma.mma_async.sync.aligned.m64n128k16.f32.bf16.bf16 "
    "{%0, %1, %2, %3, %4, %5, %6, %7, %8, %9, %10, %11, %12, %13, %14, %15, "
    "%16, %17, %18, %19, %20, %21, %22, %23, %24, %25, %26, %27, %28, %29, %30, %31, "
    "%32, %33, %34, %35, %36, %37, %38, %39, %40, %41, %42, %43, %44, %45, %46, %47, "
    "%48, %49, %50, %51, %52, %53, %54, %55, %56, %57, %58, %59, %60, %61, %62, %63}, "
    "da, db, p, 1, 1, 0, 1;\n}\n}\n"
    : "+f"(d[0]), "+f"(d[1]), "+f"(d[2]), "+f"(d[3]), "+f"(d[4]), "+f"(d[5]), "+f"(d[6]), "+f"(d[7]),
      "+f"(d[8]), "+f"(d[9]), "+f"(d[10]), "+f"(d[11]), "+f"(d[12]), "+f"(d[13]), "+f"(d[14]), "+f"(d[15]),
      "+f"(d[16]), "+f"(d[17]), "+f"(d[18]), "+f"(d[19]), "+f"(d[20]), "+f"(d[21]), "+f"(d[22]), "+f"(d[23]),
      "+f"(d[24]), "+f"(d[25]), "+f"(d[26]), "+f"(d[27]), "+f"(d[28]), "+f"(d[29]), "+f"(d[30]), "+f"(d[31]),
      "+f"(d[32]), "+f"(d[33]), "+f"(d[34]), "+f"(d[35]), "+f"(d[36]), "+f"(d[37]), "+f"(d[38]), "+f"(d[39]),
      "+f"(d[40]), "+f"(d[41]), "+f"(d[42]), "+f"(d[43]), "+f"(d[44]), "+f"(d[45]), "+f"(d[46]), "+f"(d[47]),
      "+f"(d[48]), "+f"(d[49]), "+f"(d[50]), "+f"(d[51]), "+f"(d[52]), "+f"(d[53]), "+f"(d[54]), "+f"(d[55]),
      "+f"(d[56]), "+f"(d[57]), "+f"(d[58]), "+f"(d[59]), "+f"(d[60]), "+f"(d[61]), "+f"(d[62]), "+f"(d[63])
    : "r"(a_lo), "r"(b_lo), "r"(keep));
}
__device__ __forceinline__ void wgmma_ss_n256_first(float (&d)[128], uint32_t a_lo, uint32_t b_lo) {
  asm volatile(
    "{\n.reg .b64 da, db;\nmov.b64 da, {%128, 8};\nmov.b64 db, {%129, 0x40000040};\n"
    "mov.b32 %0, 0; mov.b32 %1, 0; mov.b32 %2, 0; mov.b32 %3, 0; mov.b32 %4, 0; mov.b32 %5, 0; mov.b32 %6, 0; mov.b32 %7, 0;\n"
    "mov.b32 %8, 0; mov.b32 %9, 0; mov.b32 %10, 0; mov.b32 %11, 0; mov.b32 %12, 0; mov.b32 %13, 0; mov.b32 %14, 0; mov.b32 %15, 0;\n"
    "mov.b32 %16, 0; mov.b32 %17, 0; mov.b32 %18, 0; mov.b32 %19, 0; mov.b32 %20, 0; mov.b32 %21, 0; mov.b32 %22, 0; mov.b32 %23, 0;\n"
    "mov.b32 %24, 0; mov.b32 %25, 0; mov.b32 %26, 0; mov.b32 %27, 0; mov.b32 %28, 0; mov.b32 %29, 0; mov.b32 %30, 0; mov.b32 %31, 0;\n"
    "mov.b32 %32, 0; mov.b32 %33, 0; mov.b32 %34, 0; mov.b32 %35, 0; mov.b32 %36, 0; mov.b32 %37, 0; mov.b32 %38, 0; mov.b32 %39, 0;\n"
    "mov.b32 %40, 0; mov.b32 %41, 0; mov.b32 %42, 0; mov.b32 %43, 0; mov.b32 %44, 0; mov.b32 %45, 0; mov.b32 %46, 0; mov.b32 %47, 0;\n"
    "mov.b32 %48, 0; mov.b32 %49, 0; mov.b32 %50, 0; mov.b32 %51, 0; mov.b32 %52, 0; mov.b32 %53, 0; mov.b32 %54, 0; mov.b32 %55, 0;\n"
    "mov.b32 %56, 0; mov.b32 %57, 0; mov.b32 %58, 0; mov.b32 %59, 0; mov.b32 %60, 0; mov.b32 %61, 0; mov.b32 %62, 0; mov.b32 %63, 0;\n"
    "mov.b32 %64, 0; mov.b32 %65, 0; mov.b32 %66, 0; mov.b32 %67, 0; mov.b32 %68, 0; mov.b32 %69, 0; mov.b32 %70, 0; mov.b32 %71, 0;\n"
    "mov.b32 %72, 0; mov.b32 %73, 0; mov.b32 %74, 0; mov.b32 %75, 0; mov.b32 %76, 0; mov.b32 %77, 0; mov.b32 %78, 0; mov.b32 %79, 0;\n"
    "mov.b32 %80, 0; mov.b32 %81, 0; mov.b32 %82, 0; mov.b32 %83, 0; mov.b32 %84, 0; mov.b32 %85, 0; mov.b32 %86, 0; mov.b32 %87, 0;\n"
    "mov.b32 %88, 0; mov.b32 %89, 0; mov.b32 %90, 0; mov.b32 %91, 0; mov.b32 %92, 0; mov.b32 %93, 0; mov.b32 %94, 0; mov.b32 %95, 0;\n"
    "mov.b32 %96, 0; mov.b32 %97, 0; mov.b32 %98, 0; mov.b32 %99, 0; mov.b32 %100, 0; mov.b32 %101, 0; mov.b32 %102, 0; mov.b32 %103, 0;\n"
    "mov.b32 %104, 0; mov.b32 %105, 0; mov.b32 %106, 0; mov.b32 %107, 0; mov.b32 %108, 0; mov.b32 %109, 0; mov.b32 %110, 0; mov.b32 %111, 0;\n"
    "mov.b32 %112, 0; mov.b32 %113, 0; mov.b32 %114, 0; mov.b32 %115, 0; mov.b32 %116, 0; mov.b32 %117, 0; mov.b32 %118, 0; mov.b32 %119, 0;\n"
    "mov.b32 %120, 0; mov.b32 %121, 0; mov.b32 %122, 0; mov.b32 %123, 0; mov.b32 %124, 0; mov.b32 %125, 0; mov.b32 %126, 0; mov.b32 %127, 0;\n"
    "wgmma.mma_async.sync.aligned.m64n256k16.f32.bf16.bf16 "
    "{%0, %1, %2, %3, %4, %5, %6, %7, %8, %9, %10, %11, %12, %13, %14, %15, "
    "%16, %17, %18, %19, %20, %21, %22, %23, %24, %25, %26, %27, %28, %29, %30, %31, "
    "%32, %33, %34, %35, %36, %37, %38, %39, %40, %41, %42, %43, %44, %45, %46, %47, "
    "%48, %49, %50, %51, %52, %53, %54, %55, %56, %57, %58, %59, %60, %61, %62, %63, "
    "%64, %65, %66, %67, %68, %69, %70, %71, %72, %73, %74, %75, %76, %77, %78, %79, "
    "%80, %81, %82, %83, %84, %85, %86, %87, %88, %89, %90, %91, %92, %93, %94, %95, "
    "%96, %97, %98, %99, %100, %101, %102, %103, %104, %105, %106, %107, %108, %109, %110, %111, "
    "%112, %113, %114, %115, %116, %117, %118, %119, %120, %121, %122, %123, %124, %125, %126, %127}, "
    "da, db, 1, 1, 1, 0, 1;\n}\n"
    : "=f"(d[0]), "=f"(d[1]), "=f"(d[2]), "=f"(d[3]), "=f"(d[4]), "=f"(d[5]), "=f"(d[6]), "=f"(d[7]),
      "=f"(d[8]), "=f"(d[9]), "=f"(d[10]), "=f"(d[11]), "=f"(d[12]), "=f"(d[13]), "=f"(d[14]), "=f"(d[15]),
      "=f"(d[16]), "=f"(d[17]), "=f"(d[18]), "=f"(d[19]), "=f"(d[20]), "=f"(d[21]), "=f"(d[22]), "=f"(d[23]),
      "=f"(d[24]), "=f"(d[25]), "=f"(d[26]), "=f"(d[27]), "=f"(d[28]), "=f"(d[29]), "=f"(d[30]), "=f"(d[31]),
      "=f"(d[32]), "=f"(d[33]), "=f"(d[34]), "=f"(d[35]), "=f"(d[36]), "=f"(d[37]), "=f"(d[38]), "=f"(d[39]),
      "=f"(d[40]), "=f"(d[41]), "=f"(d[42]), "=f"(d[43]), "=f"(d[44]), "=f"(d[45]), "=f"(d[46]), "=f"(d[47]),
      "=f"(d[48]), "=f"(d[49]), "=f"(d[50]), "=f"(d[51]), "=f"(d[52]), "=f"(d[53]), "=f"(d[54]), "=f"(d[55]),
      "=f"(d[56]), "=f"(d[57]), "=f"(d[58]), "=f"(d[59]), "=f"(d[60]), "=f"(d[61]), "=f"(d[62]), "=f"(d[63]),
      "=f"(d[64]), "=f"(d[65]), "=f"(d[66]), "=f"(d[67]), "=f"(d[68]), "=f"(d[69]), "=f"(d[70]), "=f"(d[71]),
      "=f"(d[72]), "=f"(d[73]), "=f"(d[74]), "=f"(d[75]), "=f"(d[76]), "=f"(d[77]), "=f"(d[78]), "=f"(d[79]),
      "=f"(d[80]), "=f"(d[81]), "=f"(d[82]), "=f"(d[83]), "=f"(d[84]), "=f"(d[85]), "=f"(d[86]), "=f"(d[87]),
      "=f"(d[88]), "=f"(d[89]), "=f"(d[90]), "=f"(d[91]), "=f"(d[92]), "=f"(d[93]), "=f"(d[94]), "=f"(d[95]),
      "=f"(d[96]), "=f"(d[97]), "=f"(d[98]), "=f"(d[99]), "=f"(d[100]), "=f"(d[101]), "=f"(d[102]), "=f"(d[103]),
      "=f"(d[104]), "=f"(d[105]), "=f"(d[106]), "=f"(d[107]), "=f"(d[108]), "=f"(d[109]), "=f"(d[110]), "=f"(d[111]),
      "=f"(d[112]), "=f"(d[113]), "=f"(d[114]), "=f"(d[115]), "=f"(d[116]), "=f"(d[117]), "=f"(d[118]), "=f"(d[119]),
      "=f"(d[120]), "=f"(d[121]), "=f"(d[122]), "=f"(d[123]), "=f"(d[124]), "=f"(d[125]), "=f"(d[126]), "=f"(d[127])
    : "r"(a_lo), "r"(b_lo));
}

template <int N> struct Mma;
template <> struct Mma<128> {
  static __device__ __forceinline__ void ss(float (&d)[64], uint32_t a, uint32_t b) { wgmma_ss_n128(d, a, b); }
  static __device__ __forceinline__ void ss(float (&d)[64], uint32_t a, uint32_t b, uint32_t keep) { wgmma_ss_n128_p(d, a, b, keep); }
};
template <> struct Mma<192> {
  static __device__ __forceinline__ void ss(float (&d)[96], uint32_t a, uint32_t b) { wgmma_ss_n192(d, a, b); }
};
template <> struct Mma<256> {
  static __device__ __forceinline__ void ss(float (&d)[128], uint32_t a, uint32_t b) { wgmma_ss_n256(d, a, b); }
  static __device__ __forceinline__ void ss(float (&d)[128], uint32_t a, uint32_t b, uint32_t) { wgmma_ss_n256_first(d, a, b); }
};
template <int R> __device__ __forceinline__ void pin(float (&d)[R]) {
#pragma unroll
  for (int x = 0; x < R; x++) asm volatile("" : "+f"(d[x]));
}

__device__ __forceinline__ uint32_t ld_relaxed(const uint32_t* p) {
  uint32_t v; asm volatile("ld.relaxed.gpu.global.u32 %0, [%1];" : "=r"(v) : "l"(p) : "memory"); return v;
}
__device__ __forceinline__ void st_release(uint32_t* p, uint32_t v) { asm volatile("st.release.gpu.global.u32 [%0], %1;" :: "l"(p), "r"(v) : "memory"); }
__device__ __forceinline__ void stg32(void* p, uint32_t v) { asm volatile("st.global.u32 [%0], %1;" :: "l"(p), "r"(v) : "memory"); }
__device__ __forceinline__ float rsqrt_fast(float x) { float r; asm("rsqrt.approx.ftz.f32 %0, %1;" : "=f"(r) : "f"(x)); return r; }
__device__ __forceinline__ uint32_t gate_pair(uint32_t x, uint32_t y, float r, float nb) {
  const float a = bf_lo(x), b = bf_hi(x);
  return pack_bf16(fmaf(fmaf(a, r, nb), bf_lo(y), a), fmaf(fmaf(b, r, nb), bf_hi(y), b));
}

constexpr int CV_KT_O = 4144;
constexpr int CV_KT_CH = 8336;
constexpr int CV_KH = 2064;
constexpr int CV_U_PLANE = 2240;
constexpr int CV_U_CH = 4496;
constexpr int CV_U = 8 * CV_KT_CH;
constexpr int CV_K = CV_U + 8 * CV_U_CH;
constexpr int CV_V = CV_K + 128 + 32768;
constexpr int CV_VQ = 8320, CV_Y_CH = 1040;
constexpr int CV_X = (CV_V + 4 * CV_VQ + 1023) / 1024 * 1024;
constexpr int CV_XROW = 2064;
constexpr int CV_ST = CV_X + 16 * CV_XROW;
constexpr int CV_BAR = CV_ST + 16384;
enum { CB_K0, CB_K1, CB_Q0, CB_Q1, CB_Q2, CB_Q3, CB_X0, CB_X1, CB_ST, CB_O1, CB_U1, CB_U2, CB_Y0, CB_Y1, CB_Y2, CB_QC0, CB_QC1, CB_COUNT };
constexpr int CV_SMEM = CV_BAR + 8 * CB_COUNT;

__device__ __forceinline__ uint32_t lds32_nv(uint32_t addr) { uint32_t v; asm("ld.shared.u32 %0, [%1];" : "=r"(v) : "r"(addr)); return v; }
__device__ __forceinline__ void ldsm_x4_nv(uint32_t addr, uint32_t& r0, uint32_t& r1, uint32_t& r2, uint32_t& r3) {
  asm("ldmatrix.sync.aligned.m8n8.x4.shared.b16 {%0,%1,%2,%3}, [%4];" : "=r"(r0), "=r"(r1), "=r"(r2), "=r"(r3) : "r"(addr));
}
__device__ __forceinline__ void stsm_x4_t(uint32_t addr, uint32_t r0, uint32_t r1, uint32_t r2, uint32_t r3) {
  asm volatile("stmatrix.sync.aligned.m8n8.x4.trans.shared.b16 [%0], {%1,%2,%3,%4};" :: "r"(addr), "r"(r0), "r"(r1), "r"(r2), "r"(r3) : "memory");
}
__device__ __forceinline__ void bulk_load(uint32_t dst, const void* src, uint32_t bytes, uint32_t bar) {
  asm volatile("cp.async.bulk.shared::cluster.global.mbarrier::complete_tx::bytes [%0], [%1], %2, [%3];" :: "r"(dst), "l"(src), "r"(bytes), "r"(bar) : "memory");
}
__device__ __forceinline__ void cp_async16(uint32_t dst, const void* src) {
  asm volatile("cp.async.cg.shared.global.L2::256B [%0], [%1], 16;" :: "r"(dst), "l"(src) : "memory");
}
__device__ __forceinline__ void mbar_wait_plain(uint32_t bar, uint32_t parity) {
#pragma unroll 1
  for (int spins = 0; spins < SPIN_LIMIT && !mbar_try(bar, parity); spins++) {}
}

__device__ __forceinline__ void shift_chunk(uint32_t table, int m) {
  const uint32_t src = table + 32 + m * 16;
  uint4 e;
  uint32_t nx;
  asm volatile("ld.shared.v4.u32 {%0,%1,%2,%3}, [%4];" : "=r"(e.x), "=r"(e.y), "=r"(e.z), "=r"(e.w) : "r"(src));
  asm volatile("ld.shared.u32 %0, [%1];" : "=r"(nx) : "r"(src + 16));
  sts128(src + CV_KT_O, make_uint4(__byte_perm(e.x, e.y, 0x5432), __byte_perm(e.y, e.z, 0x5432), __byte_perm(e.z, e.w, 0x5432), __byte_perm(e.w, nx, 0x5432)));
}
__device__ __forceinline__ void kv_block(uint32_t kt, int t0, const uint32_t (&wp)[4], int lane) {
  const int mi = lane >> 3, rev = 7 - (lane & 7);
  uint32_t vv[4], res[4];
  ldsm_x4(kt + CV_V + (t0 >> 9) * (CV_VQ - 8192) + (t0 + 8 * mi + rev) * 16, vv[0], vv[1], vv[2], vv[3]);
#pragma unroll
  for (int i = 0; i < 4; i++) {
    uint32_t k0, k1, k2, k3;
    ldsm_x4(kt + CV_K + (8 + t0 + 8 * i + rev - mi) * 16, k0, k1, k2, k3);
    res[i] = bmul2(badd2(badd2(badd2(bmul2(k3, wp[3]), bmul2(k2, wp[2])), bmul2(k1, wp[1])), bmul2(k0, wp[0])), vv[i]);
  }
  stsm_x4_t(kt + CV_U + (lane & 7) * CV_U_CH + (1 - (mi & 1)) * CV_U_PLANE + (8 + (t0 >> 4) + (mi >> 1)) * 16, res[0], res[1], res[2], res[3]);
}
template <int T0, int NT, int D0, int D1, int J0, int J1>
__device__ __forceinline__ void conv_phase(float (&acc)[16][4], uint32_t abase, uint32_t bbase, uint32_t zero) {
  abase += zero; bbase += zero;
#pragma unroll 1
  for (int dl = 0; dl < 8; dl++) {
    uint32_t bf[NT][2];
#pragma unroll
    for (int j = 0; j < NT; j += 2) ldsm_x4_nv(bbase + (T0 + j) * 128 - dl * 16, bf[j][0], bf[j][1], bf[j + 1][0], bf[j + 1][1]);
    const uint32_t ap = abase + dl * 32, ap2 = ap + zero;
#pragma unroll
    for (int dh = D0; dh < D1; dh++) {
      const uint32_t a0 = lds32_nv(ap + dh * 256), a1 = lds32_nv(ap + dh * 256 - 16), a2 = lds32_nv(ap + dh * 256 + 16), a3 = lds32_nv(ap2 + dh * 256);
#pragma unroll
      for (int j = 0; j < NT; j++)
        if (dh + T0 + j >= J0 && dh + T0 + j < J1) mma16816(acc[dh + T0 + j], a0, a1, a2, a3, bf[j][0], bf[j][1]);
    }
  }
}
__device__ __forceinline__ uint32_t hidden_zero(uint32_t addr) {
  uint32_t z; asm volatile("ld.volatile.shared.u32 %0, [%1];" : "=r"(z) : "r"(addr) : "memory"); return z;
}
template <int J0, int J1>
__device__ __forceinline__ void stage_y(const float (&acc)[16][4], uint32_t ys, uint32_t bar) {
#pragma unroll
  for (int j = J0; j < J1; j += 2)
    stsm_x4_t(ys + (j >> 2) * CV_VQ + (j & 3) * 128, pack_bf16(acc[j][0], acc[j][1]), pack_bf16(acc[j][2], acc[j][3]),
              pack_bf16(acc[j + 1][0], acc[j + 1][1]), pack_bf16(acc[j + 1][2], acc[j + 1][3]));
  __syncwarp();
  mbar_arrive_if(bar, (threadIdx.x & 31) == 0);
}

#define KV_PROMO CU_TENSOR_MAP_L2_PROMOTION_L2_256B
struct alignas(64) ConvMaps { CUtensorMap k, v, w1, w3; };
#define QROW_AT 2
#define CV_JS 8

__global__ void __launch_bounds__(512, 1)
conv_prep_kernel(const __grid_constant__ ConvMaps cm, const bf16* __restrict__ q, const bf16* __restrict__ shift_k, const bf16* __restrict__ ssm_k,
                 const bf16* __restrict__ ssm_d, const bf16* __restrict__ w2) {
  extern __shared__ __align__(1024) char smem[];
  const int tid = threadIdx.x, lane = tid & 31, warp = __shfl_sync(0xffffffffu, tid >> 5, 0);
  const int b = blockIdx.x, d0 = b * 8;
  const uint32_t kt = smem_u32(smem), ub = kt + CV_U, bar = kt + CV_BAR;
  const int g = lane >> 2, qd = lane & 3;
  if (tid == 0) STAMP(48);
  const uint32_t dpair = __ldg(reinterpret_cast<const uint32_t*>(ssm_d + d0 + 2 * qd));
  if (warp == 14) {
    if (elect_one()) {
#pragma unroll
      for (int x = 0; x < CB_COUNT; x++) mbar_init(bar + 8 * x, x >= CB_QC0 ? 32 : x >= CB_Y0 ? 8 : x >= CB_O1 ? 4 : 1);
      asm volatile("fence.mbarrier_init.release.cluster;" ::: "memory");
    }
    __syncwarp();
    asm volatile("bar.arrive 1, 512;" ::: "memory");
    if (elect_one()) {
      const char* krow = reinterpret_cast<const char*>(ssm_k + (size_t)d0 * SEQ);
#pragma unroll 1
      for (int x = 0; x < 4; x++) {
        if (x < 2) {
          const int bytes = x ? 4096 - CV_KH : CV_KH;
          mbar_expect_tx(bar + 8 * (CB_K0 + x), 8 * bytes);
#pragma unroll 1
          for (int ch = 0; ch < 8; ch++) bulk_load(kt + ch * CV_KT_CH + 32 + x * CV_KH, krow + ch * 4096 + x * CV_KH, bytes, bar + 8 * (CB_K0 + x));
        }
        if (x == QROW_AT) {
          mbar_expect_tx(bar + 8 * CB_X0, 32768);
#pragma unroll 1
          for (int r = 0; r < 16; r++) bulk_load(kt + CV_X + r * CV_XROW, q + (size_t)(b * 16 + r) * DM, 2048, bar + 8 * CB_X0);
        }
        const uint32_t bq = bar + 8 * (CB_Q0 + x);
        mbar_expect_tx(bq, 16384);
#pragma unroll
        for (int y = 0; y < 2; y++) {
          tma_2d(kt + CV_K + 128 + x * 8192 + y * 4096, &cm.k, bq, d0, (2 * x + y) * 256);
          tma_2d(kt + CV_V + x * CV_VQ + y * 4096, &cm.v, bq, d0, (2 * x + y) * 256);
        }
      }
      if (b == 0) {
        *reinterpret_cast<uint4*>(g_role) = make_uint4(0, 0, 0, 0);
        __threadfence();
      }
      asm volatile("griddepcontrol.launch_dependents;" ::: "memory");
#pragma unroll 1
      for (int spins = 0; spins < SPIN_LIMIT && ld_relaxed(&g_qcnt) < 128; spins++) __nanosleep(50);
      __threadfence();
      fence_async_global();
      mbar_expect_tx(bar + 8 * CB_ST, 16384);
      bulk_load(kt + CV_ST, g_qstat, 16384, bar + 8 * CB_ST);
      STAMP(63);
    }
    __syncwarp();
  } else {
    const int tw = 32 * min(warp, 14);
    if (tid < 17 && b * 17 + tid < FLAG_WORDS) g_flag[b * 17 + tid] = 0;
    if (tid < 320) reinterpret_cast<uint4*>(&g_part[0][0][0])[b * 320 + tid] = make_uint4(0, 0, 0, 0);
    if (tid < 160) {
      const int x = tid - 128, y = x & 3;
      sts128(tid < 128 ? ub + (tid >> 4) * CV_U_CH + ((tid >> 3) & 1) * CV_U_PLANE + (tid & 7) * 16
                       : y == 3 ? kt + CV_K + (x >> 2) * 16 : kt + (x >> 2) * CV_KT_CH + (y == 2 ? 4128 : y * 16), make_uint4(0, 0, 0, 0));
    }
    uint32_t wp[4];
    {
      const uint4 a = ld_nc_u4(shift_k + (d0 + 2 * qd) * 4);
      wp[0] = __byte_perm(a.x, a.z, 0x5410); wp[1] = __byte_perm(a.x, a.z, 0x7632);
      wp[2] = __byte_perm(a.y, a.w, 0x5410); wp[3] = __byte_perm(a.y, a.w, 0x7632);
    }
    named_bar(1, 512);
#pragma unroll 1
    for (int x = 0; x < 2; x++) {
      mbar_wait_plain(bar + 8 * (CB_K0 + x), 0);
#pragma unroll 1
      for (int idx = x ? tid + 8 * 130 - 256 : tw + lane; idx < (x ? 8 * 258 : 8 * 130); idx += x ? 128 : 480)
        shift_chunk(kt + (idx & 7) * CV_KT_CH, (idx >> 3) - 2);
      __syncwarp();
      mbar_arrive_if(bar + 8 * CB_O1, x && lane == 0);
      if (tid == 0) BSTAMP(54, kt);
#pragma unroll 1
      for (int t0 = x ? tw + 256 : tw; t0 < (x ? SEQ : 32 * warp + 32); t0 += x ? 128 : 32) {
        mbar_wait_plain(bar + 8 * (CB_Q0 + (t0 >> 9)), 0);
        if (tid == 0) BSTAMP(56, kt);
        kv_block(kt, t0, wp, lane);
        __syncwarp();
        mbar_arrive_if(bar + 8 * (CB_U1 + ((t0 >> 9) & 1)), (t0 & 0x580) == 0x580 && lane == 0);
      }
      if (x == 0) named_bar(3, 480);
      if ((warp >> 2) != 2) break;
    }
    if (tid == 256) STAMP(53);
  }

  if (warp < 8) {
    const int o = 2 * qd - g;
    const uint32_t abase = kt + warp * CV_KT_CH + 32 + ((g & 1) ? CV_KT_O + (o - 1) * 2 : o * 2);
    const uint32_t bbase = ub + warp * CV_U_CH + ((lane >> 3) & 1) * CV_U_PLANE + (8 + (lane >> 4) * 8 + (lane & 7)) * 16;
    const uint32_t ys = kt + CV_V + warp * CV_Y_CH + ((lane >> 3) & 1) * 512 + ((lane >> 4) * 8 + (lane & 7)) * 16;
    if (tid == 0) STAMP(49);
    float acc[16][4];
#pragma unroll
    for (int j = 0; j < 16; j++) { acc[j][0] = acc[j][1] = acc[j][2] = acc[j][3] = 0.f; }
    conv_phase<0, 4, 0, 8, 0, 16>(acc, abase, bbase, hidden_zero(ub));
    stage_y<0, 4>(acc, ys, bar + 8 * CB_Y0);
    if (tid == 0) STAMP(57);
    mbar_wait_plain(bar + 8 * CB_K1, 0);
    mbar_wait_plain(bar + 8 * CB_O1, 0);
    conv_phase<0, 4, 8, 16, 0, 16>(acc, abase, bbase, hidden_zero(ub));
    if (tid == 0) STAMP(58);
    if constexpr (CV_JS > 4) {
      mbar_wait_plain(bar + 8 * CB_U1, 0);
      conv_phase<4, CV_JS - 4, 0, CV_JS - 4, 0, CV_JS>(acc, abase, bbase, hidden_zero(ub));
    }
    stage_y<4, CV_JS>(acc, ys, bar + 8 * CB_Y1);
    if (tid == 0) STAMP(59);
    mbar_wait_plain(bar + 8 * CB_U2, 0);
    if (tid == 0) BSTAMP(55, kt);
    conv_phase<4, 12, 0, 12, CV_JS, 16>(acc, abase, bbase, hidden_zero(ub));
    stage_y<CV_JS, 16>(acc, ys, bar + 8 * CB_Y2);
    if (tid == 0) STAMP(50);
  } else if (warp == 15) {
#pragma unroll 1
    for (int x = 0; x < 2; x++) {
      mbar_wait_plain(bar + 8 * (CB_U1 + x), 0);
#pragma unroll 4
      for (int t = 1024 * x + lane; t < 1024 * x + 1024; t += 32) cp_async16(kt + CV_K + 128 + t * 16, q + (size_t)t * DM + d0);
      asm volatile("cp.async.mbarrier.arrive.noinc.shared::cta.b64 [%0];" :: "r"(bar + 8 * (CB_QC0 + x)) : "memory");
    }
  } else if ((warp >> 1) == 6) {
    const int ww = warp - 12, mi = lane >> 3;
    const uint32_t xbuf = kt + CV_X;
    {
      mbar_wait_plain(bar + 8 * CB_X0, 0);
      const uint32_t xa = xbuf + (8 * ww + (lane & 7)) * CV_XROW + (mi & 1) * 1024 + (mi >> 1) * 16;
      float sum[4] = {0.f, 0.f, 0.f, 0.f}, lo[4] = {0.f, 0.f, 0.f, 0.f}, hi[4] = {0.f, 0.f, 0.f, 0.f};
#pragma unroll 4
      for (int x = 0; x < 32; x++) {
        uint32_t a0, a1, a2, a3;
        ldsm_x4(xa + x * 32, a0, a1, a2, a3);
        mma16816(sum, a0, a1, a2, a3, 0x3f803f80u, 0x3f803f80u);
        mma16816(lo, a0, a1, a2, a3, a0, a2);
        mma16816(hi, a0, a1, a2, a3, a1, a3);
      }
      const float mean = (sum[0] + sum[2]) * (1.f / DM), sq = (g & 1) ? lo[1] + hi[3] : lo[0] + hi[2];
      const float rs = rsqrt_fast(fmaxf(fmaf(-mean, mean, sq * (1.f / DM)), 0.f) + LN_EPS);
      if (qd == (g >> 1)) g_qstat[b * 16 + 8 * ww + g] = make_float2(rs, -mean * rs);
      if (tid == 384) STAMP(47);
    }
    const int npieces = b < 112 ? 5 : 1;
    const int xr = (mi >> 1) * 8 + (lane & 7);
    const uint32_t xa = xbuf + xr * 64 + (((ww * 2 + (mi & 1)) ^ ((xr >> 1) & 3)) << 4);
    float cs[4][4] = {};
#pragma unroll 1
    for (int pc = -1; pc < npieces; pc++) {
      named_bar(2, 64);
      if (ww == 0 && pc + 1 < npieces && elect_one()) {
        const uint32_t bx = bar + 8 * (CB_X0 + (pc & 1));
        mbar_expect_tx(bx, 16384);
        tma_2d(xbuf + (pc & 1) * 16384, pc < 0 ? &cm.w1 : &cm.w3, bx, 32 * (pc < 0 ? b >> 2 : b), 256 * (pc < 0 ? b & 3 : pc));
      }
      if (pc < 0) {
        if (tid == 416) asm volatile("red.release.gpu.global.add.u32 [%0], 1;" :: "l"(&g_qcnt) : "memory");
        continue;
      }
      mbar_wait_plain(bar + 8 * (CB_X0 + ((pc + 1) & 1)), ((pc + 1) >> 1) & 1);
#pragma unroll
      for (int r = 0; r < 16; r++) {
        uint32_t a0, a1, a2, a3;
        ldsm_x4_t(xa + ((pc + 1) & 1) * 16384 + r * 1024, a0, a1, a2, a3);
        mma16816(cs[r & 3], a0, a1, a2, a3, 0x3f803f80u, 0x3f803f80u);
      }
      if (pc == 0 || pc == 4) {
        const float lo = (cs[0][0] + cs[1][0]) + (cs[2][0] + cs[3][0]), hi = (cs[0][2] + cs[1][2]) + (cs[2][2] + cs[3][2]);
        if (qd < 2) (pc ? g_cs3 + 32 * b : g_cs1[b & 3] + 32 * (b >> 2))[16 * ww + 8 * qd + g] = qd ? hi : lo;
#pragma unroll
        for (int r = 0; r < 4; r++) cs[r][0] = cs[r][2] = 0.f;
      }
    }
    if (tid == 384) {
      STAMP(52);
      prefetch_l2(reinterpret_cast<const char*>(w2) + (size_t)b * (DM * DM / 64), DM * DM / 64);
    }
  }
  {
    const int mi = lane >> 3, ch = lane & 7;
    const uint32_t ya = kt + CV_V + ch * CV_Y_CH + (mi & 1) * 512 + (mi >> 1) * 16;
    const uint32_t ua = ub + ch * CV_U_CH + (mi & 1) * CV_U_PLANE + (8 + (mi >> 1)) * 16;
    const uint32_t qa = kt + CV_K + 128 + (16 * (mi >> 1) + 15 - 8 * (mi & 1) - ch) * 16;
    const uint32_t sa = kt + CV_ST + (15 - g) * 8;
    char* xo = reinterpret_cast<char*>(g_x3[0]) + (size_t)b * CB_BYTES + (15 - g) * 16 + qd * 4;
    char* yo = reinterpret_cast<char*>(g_y) + (size_t)b * CB_BYTES + ((7 - g) * 4 + qd) * 8;
    mbar_wait_plain(bar + 8 * CB_ST, 0);
    mbar_wait_plain(bar + 8 * CB_QC0, 0);
#pragma unroll 1
    for (int part = warp < 8 ? 2 : warp < 12 ? 0 : 1; part < 3; part++) {
      if (part > (CV_JS <= 8)) mbar_wait_plain(bar + 8 * CB_QC1, 0);
      mbar_wait_plain(bar + 8 * (CB_Y0 + part), 0);
      if (tid == 0) BSTAMP(60, kt);
#pragma unroll 1
      for (int u = part == 0 ? warp - 8 : part == 1 ? warp + 8 : warp + 4 * CV_JS; u < (part == 0 ? 16 : part == 1 ? 4 * CV_JS : 64); u += 4 << part) {
        uint32_t y[4], uu[4], qq[4];
        ldsm_x4_t(ya + (u >> 4) * CV_VQ + (u & 15) * 32, y[0], y[1], y[2], y[3]);
        ldsm_x4_t(ua + u * 32, uu[0], uu[1], uu[2], uu[3]);
        ldsm_x4(qa + u * 512, qq[0], qq[1], qq[2], qq[3]);
#pragma unroll
        for (int i = 0; i < 4; i++) {
          const int off = 16 * (i >> 1) - 8 * (i & 1);
          const float2 s = lds_f2(sa + u * 256 + off * 8);
          y[i] = badd2(y[i], bmul2(uu[i], dpair));
          stg32(xo + u * 512 + off * 16, gate_pair(qq[i], y[i], s.x, s.y));
        }
        asm volatile("st.global.v2.u32 [%0], {%1,%2};" :: "l"(yo + u * 512), "r"(y[1]), "r"(y[0]) : "memory");
        asm volatile("st.global.v2.u32 [%0], {%1,%2};" :: "l"(yo + u * 512 + 256), "r"(y[3]), "r"(y[2]) : "memory");
      }
    }
  }
  if (tid == 0) STAMP(51);
}

enum { M_X3A, M_X3B, M_H, M_X1, M_HID, M_OUT, M_W1, M_W2, M_W3A, M_W3B, M_W4, M_COUNT };
struct alignas(64) Maps { CUtensorMap m[M_COUNT]; };

constexpr int NA = 5;
constexpr int SM_A = 0;
constexpr int SM_B = 2 * NA * 8192;
constexpr int SM_X = SM_B + 114688;
constexpr int SM_CS1 = SM_X + 32768;
constexpr int SM_CS3 = SM_CS1 + 512;
constexpr int SM_ABORT = SM_CS3 + 1792;
constexpr int SM_ROLE = SM_ABORT + 4;
constexpr int SM_BAR = SM_ABORT + 8;
constexpr int BAR_FULLA = 0, BAR_FULLB = 16, BAR_EMPTYA = 24, BAR_EMPTYB = BAR_EMPTYA + 18;
constexpr int BAR_PUB = BAR_EMPTYB + 9;
constexpr int BAR_TURN = BAR_PUB + 26, BAR_CS = BAR_TURN + 1, BAR_OWN = BAR_CS + 1, BAR_ALIGN = BAR_OWN + 2, BAR_END = BAR_ALIGN + 1;
constexpr int MEGA_SMEM = SM_BAR + BAR_END * 8;
static_assert(MEGA_SMEM <= 232448, "shared memory");
#define ALIGN_AT 2
#define LEAD16 7
#define LEAD32 3
#define LEAD24 4
#define TURN_EARLY 1

template <int N> struct BGeo;
template <> struct BGeo<128> { static constexpr int SLOTS = 7, BYTES = 16384, LEAD = LEAD16; };
template <> struct BGeo<256> { static constexpr int SLOTS = 3, BYTES = 32768, LEAD = LEAD32; };
template <> struct BGeo<192> { static constexpr int SLOTS = 4, BYTES = 24576, LEAD = LEAD24; };
__host__ __device__ constexpr int first_slot(int s) { return s == 0 ? 6 : s == 1 ? 1 : s == 2 ? 2 : s == 3 ? 0 : 6; }
__device__ __forceinline__ bool starts_local(int l, int s) { return s == 2 || s == 1 - l; }
__device__ __forceinline__ int token_shift(int j) { return ((j >> 1) & 1 ? 1 : -1) * (1 + (j >> 2)); }

__device__ __forceinline__ void k_order(bool local, int n, int j, int& js, int& p) {
  if (!local) { p = n >> 3; js = ((j & 6) + n) & 7; }
  else if (n < 4) { p = n & 1; js = j ^ (n >> 1); }
  else { const int m = n - 4; p = m >= 6; js = ((j & 6) + 2 + (m >= 6 ? m - 6 : m)) & 7; }
}

struct Ctx {
  uint32_t sm;
  uint32_t bar;
  int i, j, r;
  int bid;
  uint32_t abort;
};

struct Pipe {
  uint32_t ko, kp;
  uint32_t po;
  uint32_t a0, a1, ar;
  uint32_t b;
  uint32_t keep;
  uint32_t turn;
  uint32_t rel;
  bool signals;
  __device__ __forceinline__ void release() const {
    asm volatile("{\n.reg .pred p;\nsetp.ne.b32 p, %1, 0;\n@p mbarrier.arrive.shared::cluster.b64 _, [%0];\n}" :: "r"(rel + po), "r"((uint32_t)signals) : "memory");
  }
  __device__ __forceinline__ void drain() { wg_wait<0>(); release(); po = 64; }
};
__device__ __forceinline__ uint32_t desc_a(const Ctx& c, int off) { return ((c.sm & 0x3FFFFu) >> 4) + 0x400000u + (off >> 4); }
__device__ __forceinline__ uint32_t desc_b(const Ctx& c, int off) { return ((c.sm & 0x3FFFFu) >> 4) + 0x2000000u + ((SM_B + off) >> 4); }

template <int N, bool PRED, class Extra>
__device__ __forceinline__ void gemm_step(float (&acc)[N / 2], const Ctx& c, int wg, Pipe& p, Extra&& extra) {
  using G = BGeo<N>;
  const uint32_t fa = c.bar + 8 * BAR_FULLA + 64 * wg + p.ko, fb = c.bar + 8 * BAR_FULLB + p.ko;
  uint32_t ready;
  asm volatile("{\n.reg .pred p, q;\nmbarrier.try_wait.parity.shared::cta.b64 p, [%1], %3;\nmbarrier.try_wait.parity.shared::cta.b64 q, [%2], %3;\n"
               "and.pred p, p, q;\nselp.b32 %0, 1, 0, p;\n}" : "=r"(ready) : "r"(fa), "r"(fb), "r"(p.kp) : "memory");
  if (__builtin_expect(!ready, 0)) {
    int spins = 0;
    while (!(mbar_try(fa, p.kp) && mbar_try(fb, p.kp))) { if (spin_give_up(c.abort, spins, fa - c.abort, p.kp)) break; }
  }
  wg_fence();
  if constexpr (PRED) { Mma<N>::ss(acc, p.a0, p.b, p.keep); p.keep = 1; } else Mma<N>::ss(acc, p.a0, p.b);
#pragma unroll
  for (int kk = 1; kk < 4; kk++) Mma<N>::ss(acc, p.a0 + kk * 128, p.b + kk * 128);
  wg_commit();
  extra();
  wg_wait<1>();
  p.release();
  p.po = p.ko;
  p.ko = (p.ko + 8) & 63;
  p.kp ^= p.ko == 0;
  p.a0 = p.a1; p.a1 = p.ar;
  p.ar = p.ar == desc_a(c, SM_A + (NA - 1) * 8192) + wg * NA * 512 ? p.ar - (NA - 1) * 512 : p.ar + 512;
  p.b = p.b == desc_b(c, (G::SLOTS - 1) * G::BYTES) ? desc_b(c, 0) : p.b + (G::BYTES >> 4);
}
template <int N>
__device__ __forceinline__ void gemm_begin(const Ctx& c, int wg, Pipe& p, int s, bool local) {
  if (local) {
    fence_async_smem();
    named_bar(2 + wg, 128);
    mbar_arrive_if(c.bar + 8 * BAR_FULLA + 64 * wg + 8 * (threadIdx.x & 1), (threadIdx.x & 126) == 96);
    p.ar = p.a0;
    p.a0 = desc_a(c, SM_X) + wg * 1024;
    p.a1 = p.a0 + 512;
  }
  p.b = desc_b(c, first_slot(s) * BGeo<N>::BYTES);
  p.keep = 0;
}
template <class Hook>
__device__ __forceinline__ void yield_turn(const Ctx& c, int wg, Pipe& p, Hook&& hook) {
  if (wg == 1) p.drain();
  hook();
  if (wg == 1) mbar_wait(c.bar + 8 * BAR_TURN, p.turn, c.abort);
  p.turn ^= 1;
}
__device__ __forceinline__ void pass_turn(const Ctx& c, bool now) { mbar_arrive_if(c.bar + 8 * BAR_TURN, now && threadIdx.x == 96); }
struct Nop { __device__ __forceinline__ void operator()() const {} };
template <int N, bool PRED, int EARLY, class Early, class Hook>
__device__ __forceinline__ void gemm_steps(float (&acc)[N / 2], const Ctx& c, int wg, Pipe& p, int count, Early&& early, Hook&& hook) {
  constexpr int LEAD = BGeo<N>::LEAD, LAST = LEAD > TURN_EARLY ? TURN_EARLY : LEAD - 1;
#pragma unroll 1
  for (int seg = EARLY ? 0 : 1; seg < 2; seg++) {
#pragma unroll 1
    for (int n = seg == 0 ? EARLY : count - EARLY - LEAD; n > 0; n--) gemm_step<N, PRED>(acc, c, wg, p, Nop());
    if (EARLY && seg == 0) early();
  }
  yield_turn(c, wg, p, hook);
#pragma unroll 1
  for (int n = LEAD - 1; n >= 0; n--) {
    gemm_step<N, false>(acc, c, wg, p, Nop());
    pass_turn(c, n == LAST);
  }
  p.drain();
}

struct RowSums {
  float s[4] = {0.f, 0.f, 0.f, 0.f}, q[4] = {0.f, 0.f, 0.f, 0.f};
  __device__ __forceinline__ void add(int x, float v) { s[x & 3] += v; q[x & 3] = fmaf(v, v, q[x & 3]); }
  __device__ __forceinline__ void put(float2* gdst) const {
    const bool odd = threadIdx.x & 1;
    const float s0 = s[0] + s[1], s1 = s[2] + s[3], q0 = q[0] + q[1], q1 = q[2] + q[3];
    float ss = (odd ? s1 : s0) + __shfl_xor_sync(0xffffffffu, odd ? s0 : s1, 1);
    float qq = (odd ? q1 : q0) + __shfl_xor_sync(0xffffffffu, odd ? q0 : q1, 1);
    ss += __shfl_xor_sync(0xffffffffu, ss, 2);
    qq += __shfl_xor_sync(0xffffffffu, qq, 2);
    const float m = ss * (1.f / 128), v = fmaxf(fmaf(-m, ss, qq), 0.f);
    asm volatile("{\n.reg .pred p;\nsetp.eq.b32 p, %3, 0;\n@p st.relaxed.gpu.global.v2.b32 [%0], {%1,%2};\n}"
                 :: "l"(gdst + (odd ? 8 : 0)), "r"(__float_as_uint(m)), "r"(__float_as_uint(v) | 1u), "r"(threadIdx.x & 2) : "memory");
  }
};
__device__ __forceinline__ void put_partial(const float (&v)[64], float2* gdst) {
  RowSums r;
#pragma unroll
  for (int x = 0; x < 64; x++) r.add(x, v[x]);
  r.put(gdst);
}
struct RowStats {
  float2 p[4];
  __device__ __forceinline__ void load(const float2* r0, const float2* r1) {
#pragma unroll
    for (int x = 0; x < 4; x++)
      asm volatile("ld.relaxed.gpu.global.v2.f32 {%0,%1}, [%2];" : "=f"(p[x].x), "=f"(p[x].y) : "l"((x & 2 ? r1 : r0) + (x & 1) * SEQ) : "memory");
  }
  __device__ __forceinline__ void finish(const float2* r0, const float2* r1, uint32_t abort_addr, float2& s0, float2& s1) {
    int spins = 0;
    while (!__all_sync(0xffffffffu, __float_as_uint(p[0].y) & __float_as_uint(p[1].y) & __float_as_uint(p[2].y) & __float_as_uint(p[3].y) & 1)) {
      if (spin_give_up(abort_addr, spins, 200000, 0)) break;
      load(r0, r1);
    }
#pragma unroll
    for (int h = 0; h < 2; h++) {
      const float2 a = p[2 * h], b = p[2 * h + 1];
      float m = a.x + b.x;
      m += __shfl_xor_sync(0xffffffffu, m, 1);
      m += __shfl_xor_sync(0xffffffffu, m, 2);
      m *= 0.125f;
      const float ea = a.x - m, eb = b.x - m;
      float t = fmaf(fmaf(ea, ea, eb * eb), 128.f, a.y + b.y);
      t += __shfl_xor_sync(0xffffffffu, t, 1);
      t += __shfl_xor_sync(0xffffffffu, t, 2);
      (h ? s1 : s0) = make_float2(m, rsqrt_fast(fmaf(t, 1.f / DM, LN_EPS)));
    }
  }
};

__device__ __forceinline__ void emit_panel(const uint32_t* v, char* gp, uint32_t sp, bool stage, uint32_t pub) {
#pragma unroll
  for (int t = 0; t < 8; t++) { stg32(gp + t * CB_BYTES, v[2 * t]); stg32(gp + t * CB_BYTES + 128, v[2 * t + 1]); }
  if (stage) {
#pragma unroll
    for (int t = 0; t < 8; t += 2) stsm_x4(sp + t * 1024, v[2 * t], v[2 * t + 1], v[2 * t + 2], v[2 * t + 3]);
  }
  __syncwarp();
  mbar_arrive_if(pub, (threadIdx.x & 31) == 0);
}

__device__ __forceinline__ float late_zero(uint32_t abort_addr) {
  float z; asm volatile("ld.volatile.shared.f32 %0, [%1];" : "=f"(z) : "r"(abort_addr) : "memory"); return z;
}

template <int NT, bool GELU>
__device__ __forceinline__ void fold_tiles(uint32_t* v, const float* acc, const float2* cs_ptr, float2 st0, float2 st1) {
  const float n0 = -st0.x * st0.y, n1 = -st1.x * st1.y;
#pragma unroll
  for (int tile = 0; tile < NT; tile++) {
    const float2 cs = cs_ptr[tile * 4];
    float a = fmaf(acc[4 * tile + 0], st0.y, n0 * cs.x), b = fmaf(acc[4 * tile + 1], st0.y, n0 * cs.y);
    float cc = fmaf(acc[4 * tile + 2], st1.y, n1 * cs.x), d = fmaf(acc[4 * tile + 3], st1.y, n1 * cs.y);
    if (GELU) { a = gelu_from_half(a); b = gelu_from_half(b); cc = gelu_from_half(cc); d = gelu_from_half(d); }
    v[2 * tile] = GELU ? pack_bf16(a, b) : pack_f16(a, b);
    v[2 * tile + 1] = GELU ? pack_bf16(cc, d) : pack_f16(cc, d);
  }
}

template <int CH, int LO, int HI, int NR>
__device__ __forceinline__ void pick_group(uint32_t (&held)[NR], int idx) {
  if constexpr (HI - LO == 1) {
#pragma unroll
    for (int x = 0; x < CH; x++) asm volatile("mov.b32 %0, %1;" : "=r"(held[x]) : "r"(held[CH * LO + x]));
  } else {
    constexpr int MID = (LO + HI) / 2;
    if (idx < MID) pick_group<CH, LO, MID>(held, idx); else pick_group<CH, MID, HI>(held, idx);
  }
}
template <int CH>
__device__ __forceinline__ void gelu_chunk(const uint32_t* t, char* gp) {
#pragma unroll
  for (int x = 0; x < CH; x++) stg32(gp + (x >> 1) * CB_BYTES + (x & 1) * 128, gelu_pair_f16(t[x]));
}

__device__ __forceinline__ void wait_flags(const uint32_t* lane_flag, uint32_t& seen, uint32_t need, uint32_t mask, uint32_t abort_addr) {
  if ((__ballot_sync(0xffffffffu, seen >= need) & mask) == mask) return;
  int spins = 0;
  while (true) {
    if (lane_flag) seen = ld_relaxed(lane_flag);
    if ((__ballot_sync(0xffffffffu, seen >= need) & mask) == mask) break;
    if (spin_give_up(abort_addr, spins, 100000 + need, mask)) break;
  }
  fence_async_global();
}
__device__ __forceinline__ void mbar_expect_tx_cluster(uint32_t bar, uint32_t bytes) {
  asm volatile("mbarrier.arrive.expect_tx.shared::cluster.b64 _, [%0], %1;" :: "r"(bar), "r"(bytes) : "memory");
}

__device__ __forceinline__ uint32_t pick_role() {
  uint32_t smid;
  asm volatile("mov.u32 %0, %%smid;" : "=r"(smid));
  const uint32_t t = smid >> 1;
  const uint32_t gpc = t < 32 ? t & 7 : t < 60 ? 1 + (t - 32) % 7 : t < 62 ? t - 54 : 0;
  uint32_t p = gpc & 3;
  uint4 cnt;
  asm volatile("ld.relaxed.gpu.global.v4.u32 {%0,%1,%2,%3}, [%4];" : "=r"(cnt.x), "=r"(cnt.y), "=r"(cnt.z), "=r"(cnt.w) : "l"(g_role) : "memory");
  uint32_t tried = 0;
#pragma unroll 1
  for (int k = 0; k < 4; k++) {
    const uint32_t ticket = atomicAdd(&g_role[p], 1u);
    if (ticket < 16) return ticket * 4 + p;
    tried |= 1u << p;
    const uint32_t c4[4] = {cnt.x, cnt.y, cnt.z, cnt.w};
    uint32_t best = 0xffffffffu;
#pragma unroll
    for (uint32_t x = 0; x < 4; x++)
      if (!((tried >> x) & 1) && c4[x] < best) { best = c4[x]; p = x; }
  }
  return 0;
}

#define REG_CONS 224
#define REG_PROD 56
__global__ void __cluster_dims__(2, 1, 1) __launch_bounds__(384, 1)
mega_kernel(const __grid_constant__ Maps maps, const bf16* __restrict__ w4) {
  extern __shared__ __align__(1024) char smem[];
  const int tid = threadIdx.x, lane = tid & 31;
  const int warp = __shfl_sync(0xffffffffu, tid >> 5, 0), wg = warp >> 2;
  if (warp != 5 && elect_one()) {
    const uint32_t sm0 = smem_u32(smem);
    const int w = warp - (warp > 5);
    if (warp == 0) sts32(sm0 + SM_ABORT, (sm0 & 1023) ? 1 : 0);
#pragma unroll
    for (int x = 0; x < 8; x++) {
      const int y = 8 * w + x;
      if (y < BAR_END) mbar_init(sm0 + SM_BAR + 8 * y, (y >= BAR_EMPTYA && y < BAR_PUB) || y == BAR_CS ? 2 : y >= BAR_PUB && y < BAR_TURN ? 4 : 1);
    }
    asm volatile("fence.mbarrier_init.release.cluster;" ::: "memory");
    asm volatile("prefetch.tensormap [%0];" :: "l"(&maps.m[w]) : "memory");
  }
  static_assert(BAR_END <= 88 && M_COUNT == 11, "start-up work of 11 warps");
  if (tid == 160 && (blockIdx.x & 1) == 0) {
    sts32(smem_u32(smem) + SM_ROLE, pick_role());
    asm volatile("fence.release.sync_restrict::shared::cta.cluster;" ::: "memory");
  }
  __syncthreads();
  asm volatile("barrier.cluster.arrive.relaxed.aligned;\nbarrier.cluster.wait.acquire.aligned;" ::: "memory");
  Ctx c;
  c.sm = opaque(smem_u32(smem));
  c.bar = c.sm + SM_BAR;
  c.r = blockIdx.x & 1;
  c.abort = c.sm + SM_ABORT;
  {
    uint32_t role;
    asm volatile("ld.shared::cluster.u32 %0, [%1];" : "=r"(role) : "r"(mapa(smem_u32(smem) + SM_ROLE, 0)) : "memory");
    role = __shfl_sync(0xffffffffu, role, 0);
    c.i = role >> 2; c.j = (role & 3) * 2 + c.r;
    c.bid = c.i * 8 + c.j;
  }

  if (wg == 2) {
    reg_dealloc<REG_PROD>();
    const uint32_t abort_addr = c.abort;
    if (warp == 8) {
      int as = 0, k0 = 0;
      const int hh = 16 * c.r + c.i;
      const uint32_t full0 = c.bar + 8 * (BAR_FULLA + c.r * 8), empty0 = c.bar + 8 * (BAR_EMPTYA + c.r * 9), full_peer = mapa(full0, c.r ^ 1);
      const uint32_t* lf = nullptr;
      {
        const int js = lane & 7, nb = lane < 8 ? hh : token_shift(js) > 0 ? hh + 1 : hh - 1;
        if (lane < 16 && nb >= 0 && nb < 32) lf = g_flag + (nb * 8 + js) * FS;
      }
      uint32_t seen = lf ? 0 : 0xffffffffu;
      asm volatile("griddepcontrol.wait;" ::: "memory");
      if (lane == 0) MSTAMP(46);
#pragma unroll 1
      for (int ph = 0; ph < 10; ph++) {
        const int l = ph >= 5, s = ph - 5 * l;
        const CUtensorMap* m = &maps.m[s == 0 ? M_X3A + l : s == 1 ? M_H : s == 4 ? M_HID : M_X1];
        const int np = s == 4 ? 7 : 2;
        const int pc0 = 13 * l + (s == 0 ? 0 : s == 1 ? 2 : s == 4 ? 6 : 4);
        const bool local = starts_local(l, s);
        if (s == 4) {
          mbar_wait(c.bar + 8 * BAR_ALIGN, l, abort_addr);
          if (lane == 0) asm volatile("red.relaxed.gpu.global.add.u32 [%0], 1;" :: "l"(g_flag + FLAG_PROG + l * 8 + c.j) : "memory");
          uint32_t cnt = lane < 8 ? 0 : 16;
          wait_flags(lane < 8 ? g_flag + FLAG_PROG + l * 8 + lane : nullptr, cnt, 16, 0xffu, abort_addr);
        }
        if (local) as = as + 2 >= NA ? as + 2 - NA : as + 2;
#pragma unroll 1
        for (int n = local ? 4 : 0; n < 8 * np; n++) {
          int p, js;
          k_order(local, n, c.j, js, p);
          if (ph != 0) wait_flags(ph == 6 || lane < 8 ? lf : nullptr, seen, pc0 + p + 1, (ph == 6 ? 0x101u : 1u) << js, abort_addr);
          const int row = 64 * hh + (ph == 0 ? token_shift(c.j) : ph == 6 ? token_shift(js) : 0);
          const int last = k0 + n - (local && n < NA + 2 ? NA + 2 : NA);
          mbar_wait(empty0 + 8 * (last & 7), (last >> 3) & 1, abort_addr);
          if (elect_one()) {
            mbar_expect_tx(full0 + 8 * (n & 7), 8192);
            mbar_expect_tx_cluster(full_peer + 8 * (n & 7), 8192);
            tma_2d_mc(c.sm + SM_A + (c.r * NA + as) * 8192, m, full0 + 8 * (n & 7), 2 * row, (np * js + p) * 8, (uint16_t)3);
          }
          __syncwarp();
          if (++as == NA) as = 0;
        }
        k0 += 8 * np;
      }
    } else if (warp == 9) {
      int k0 = 0;
#pragma unroll 1
      for (int ph = 0; ph < 10; ph++) {
        const int l = ph >= 5, s = ph - 5 * l;
        const int kbytes = s == 2 ? 32 : s == 3 ? 24 : 16, slots = s == 2 ? 3 : s == 3 ? 4 : 7;
        const uint32_t dist0 = s == 2 ? 0x335u : s == 3 ? 0x4333u : s == 4 ? 0x7666557u : 0x7777777u;
        const CUtensorMap* m = &maps.m[M_W1 + s];
        const int np = s == 4 ? 7 : 2;
        const int panel0 = s == 2 ? 7 * c.j : s == 3 ? 7 * c.j + 4 : 2 * c.j;
        const bool local = starts_local(l, s);
        int slot = first_slot(s);
#pragma unroll 1
        for (int n = 0; n < 8 * np; n++) {
          int p, js;
          k_order(local, n, c.j, js, p);
          const int last = k0 + n - (n < slots ? (int)((dist0 >> (4 * n)) & 15) : slots);
          mbar_wait(c.bar + 8 * (BAR_EMPTYB + (last & 7)), (last >> 3) & 1, abort_addr);
          if (elect_one()) {
            const uint32_t bar = c.bar + 8 * (BAR_FULLB + (n & 7));
            mbar_expect_tx(bar, kbytes * 1024);
            tma_3d(c.sm + SM_B + slot * kbytes * 1024, m, bar, 0, (np * js + p) * 64, panel0);
          }
          __syncwarp();
          if (++slot == slots) slot = 0;
        }
        k0 += 8 * np;
      }
    } else {
      const int w = warp - 10;
      const int row0 = 64 * (16 * w + c.i);
      asm volatile("griddepcontrol.wait;" ::: "memory");
      if (lane == 0) {
        const uint32_t bar = c.bar + 8 * (BAR_OWN + w);
        mbar_expect_tx(bar, 16384);
        tma_2d(c.sm + SM_X + w * 16384, &maps.m[M_X3A], bar, 2 * row0, 16 * c.j);
        tma_2d(c.sm + SM_X + w * 16384 + 8192, &maps.m[M_X3A], bar, 2 * row0, 16 * c.j + 8);
      }
      if (w == 0) {
        float4 s = make_float4(0.f, 0.f, 0.f, 0.f);
#pragma unroll
        for (int x = 0; x < 4; x++) {
          const float4 v = __ldcg(reinterpret_cast<const float4*>(&g_cs1[x][c.j * 128]) + lane);
          s.x += v.x; s.y += v.y; s.z += v.z; s.w += v.w;
        }
        reinterpret_cast<float4*>(smem + SM_CS1)[lane] = s;
      } else {
#pragma unroll
        for (int x = 0; x < 4; x++)
          if (lane < 28) reinterpret_cast<float4*>(smem + SM_CS3)[28 * x + lane] = __ldcg(reinterpret_cast<const float4*>(g_cs3 + c.j * 448) + 28 * x + lane);
      }
#pragma unroll 1
      for (int x = 0; x < 7; x++)
        asm volatile("prefetch.global.L2 [%0];" :: "l"(reinterpret_cast<const char*>(w4) + (size_t)((2 * c.bid + w) * 224 + 32 * x + lane) * 128) : "memory");
      __syncwarp();
      if (lane == 0) {
        mbar_arrive(c.bar + 8 * BAR_CS);
        if (c.bid == 0 && w == 0) g_qcnt = 0;
        uint32_t* my_flag = g_flag + ((16 * w + c.i) * 8 + c.j) * FS;
#pragma unroll 1
        for (int pc = 2; pc < 26; pc++) {
          const int l = pc >= 13, u = pc - 13 * l;
          mbar_wait(c.bar + 8 * (BAR_PUB + 13 * w + u), u < 2 ? 0 : l, abort_addr);
          if (u < 6 && starts_local(l, u >> 1)) {
            const int slot = w * NA + (116 * l + (u < 2 ? 0 : u < 4 ? 16 : 30) + (u & 1)) % NA;
            const int last = 120 * l + 16 * (u >> 1) + (u & 1) - NA;
            mbar_wait(c.bar + 8 * (BAR_EMPTYA + 9 * w + (last & 7)), (last >> 3) & 1, abort_addr);
            fence_async_smem();
            const uint32_t bar = mapa(c.bar + 8 * (BAR_FULLA + 8 * w + 2 + (u & 1)), c.r ^ 1);
            mbar_expect_tx_cluster(bar, 8192);
            bulk_copy_cluster(mapa(c.sm + SM_A + slot * 8192, c.r ^ 1), c.sm + SM_X + (2 * w + (u & 1)) * 8192, 8192, bar);
          }
          st_release(my_flag, pc + 1);
          if (pc == 10) {
#pragma unroll 1
            for (int x = 0; x < 16; x++) prefetch_l2(reinterpret_cast<const char*>(g_y) + (16 * c.j + x) * CB_BYTES + row0 * 16, 1024);
          }
        }
      }
    }
    cluster_exit_barrier();
  } else {
    reg_alloc<REG_CONS>();
#define WSTAMP(idx) do {} while (0)
    const int t = tid & 127, g = lane >> 2, qd = lane & 3;
    const int wrow = 64 * (16 * wg + c.i) + (t >> 5) * 16, row = wrow + g;
    const uint32_t frag = row * 16 + qd * 4 + c.j * 16 * CB_BYTES;
    const uint32_t stage = c.sm + SM_X + wg * 16384 + (lane >> 4) * 1024 + ((t >> 5) * 16 + (lane & 15)) * 16;
    const uint32_t pub = c.bar + 8 * (BAR_PUB + 13 * wg);
    Pipe p;
    p.ko = 0; p.kp = 0; p.po = 64; p.turn = 0;
    p.a0 = desc_a(c, SM_A) + wg * NA * 512; p.a1 = p.a0 + 512; p.ar = p.a0 + 1024;
    p.signals = t == 0 || t == 32 || t == 64;
    p.rel = mapa(c.bar + 8 * (t == 64 ? BAR_EMPTYB : BAR_EMPTYA + wg * 9), t == 32 ? c.r ^ 1 : c.r);
    uint32_t x3[32];
    float acc[64];
#pragma unroll
    for (int x = 0; x < 32; x++) x3[x] = 0;
#pragma unroll
    for (int x = 0; x < 64; x++) acc[x] = 0.f;
    WSTAMP(0);
#pragma unroll 1
    for (int l = 0; l < 2; l++) {
      WSTAMP(1 + 16 * l);
      RowStats rs;
      {
        const int ra = row + (l == 0 ? token_shift(c.j) : 0), rb = ra + 8;
        const float2* sp = &g_part[3 * l][2 * qd][0];
        RowStats ro;
        gemm_begin<128>(c, wg, p, 0, l == 1);
        gemm_steps<128, true, 3>(acc, c, wg, p, 16, [&]() {
          if (l == 0) {
            mbar_wait(c.bar + 8 * (BAR_OWN + wg), 0, c.abort);
            RowSums r;
#pragma unroll
            for (int x = 0; x < 32; x += 4) ldsm_x4(stage + x * 512, x3[x], x3[x + 1], x3[x + 2], x3[x + 3]);
#pragma unroll
            for (int x = 0; x < 32; x++) { r.add(2 * x, bf_lo(x3[x])); r.add(2 * x + 1, bf_hi(x3[x])); }
            r.put(&g_part[0][c.j][row]);
          }
        }, [&]() { rs.load(sp + max(ra, 0), sp + min(rb, SEQ - 1)); ro.load(sp + row, sp + row + 8); });
        WSTAMP(2 + 16 * l);
        float2 s0, s1;
        rs.finish(sp + max(ra, 0), sp + min(rb, SEQ - 1), c.abort, s0, s1);
        mbar_wait(c.bar + 8 * BAR_CS, 0, c.abort);
        s0.y *= (ra < 0 ? 0.f : 0.5f) * rsqrt_fast(fmaxf(fmaf(-LN_EPS * s0.y, s0.y, 1.f), 0.f) + LN_EPS);
        s1.y *= (rb >= SEQ ? 0.f : 0.5f) * rsqrt_fast(fmaxf(fmaf(-LN_EPS * s1.y, s1.y, 1.f), 0.f) + LN_EPS);
#pragma unroll
        for (int pn = 0; pn < 2; pn++) {
          uint32_t v[16];
          fold_tiles<8, true>(v, acc + 32 * pn, reinterpret_cast<const float2*>(smem + SM_CS1) + qd + 32 * pn, s0, s1);
          emit_panel(v, reinterpret_cast<char*>(g_h) + frag + pn * 8 * CB_BYTES, stage + pn * 8192, l == 0, pub + 8 * (2 + pn));
        }
        ro.finish(sp + row, sp + row + 8, c.abort, s0, s1);
        const float nb0 = -s0.x * s0.y, nb1 = -s1.x * s1.y;
#pragma unroll
        for (int x = 0; x < 32; x++) {
          acc[2 * x] = fmaf(bf_lo(x3[x]), (x & 1) ? s1.y : s0.y, (x & 1) ? nb1 : nb0);
          acc[2 * x + 1] = fmaf(bf_hi(x3[x]), (x & 1) ? s1.y : s0.y, (x & 1) ? nb1 : nb0);
        }
        WSTAMP(3 + 16 * l);
      }
      {
        gemm_begin<128>(c, wg, p, 1, l == 0);
        gemm_steps<128, false, 0>(acc, c, wg, p, 16, Nop(), Nop());
        WSTAMP(4 + 16 * l);
#pragma unroll
        for (int pn = 0; pn < 2; pn++) {
          uint32_t v[16];
#pragma unroll
          for (int x = 0; x < 16; x++) v[x] = pack_bf16(acc[32 * pn + 2 * x], acc[32 * pn + 2 * x + 1]);
          emit_panel(v, reinterpret_cast<char*>(g_x1) + frag + pn * 8 * CB_BYTES, stage + pn * 8192, true, pub + 8 * (4 + pn));
#pragma unroll
          for (int x = 0; x < 16; x++) x3[16 * pn + x] = badd2(x3[16 * pn + x], v[x]);
        }
        put_partial(acc, &g_part[3 * l + 1][c.j][row]);
        WSTAMP(5 + 16 * l);
      }
      const uint32_t park = c.sm + SM_X + wg * 16384 + t * 16;
      char* hp = reinterpret_cast<char*>(g_hid) + frag + c.j * 40 * CB_BYTES;
      uint32_t held[64];
      {
        float acc3[128];
        const float2* sp = &g_part[3 * l + 1][2 * qd][row];
        gemm_begin<256>(c, wg, p, 2, true);
        gemm_step<256, true>(acc3, c, wg, p, Nop());
        gemm_steps<256, false, 0>(acc3, c, wg, p, 15, Nop(), [&]() {
          rs.load(sp, sp + 8);
#pragma unroll
          for (int x = 0; x < 8; x++) sts128(park + x * 2048, make_uint4(x3[4 * x], x3[4 * x + 1], x3[4 * x + 2], x3[4 * x + 3]));
        });
        WSTAMP(6 + 16 * l);
        float2 s0, s1;
        rs.finish(sp, sp + 8, c.abort, s0, s1);
        s0.y *= 0.5f; s1.y *= 0.5f;
        fold_tiles<32, false>(held, acc3, reinterpret_cast<const float2*>(smem + SM_CS3) + qd, s0, s1);
        float accb[96];
#pragma unroll
        for (int x = 0; x < 24; x++) {
          const float2 cs = (reinterpret_cast<const float2*>(smem + SM_CS3 + 1024) + qd)[4 * x];
          accb[4 * x] = -s0.x * cs.x; accb[4 * x + 1] = -s0.x * cs.y; accb[4 * x + 2] = -s1.x * cs.x; accb[4 * x + 3] = -s1.x * cs.y;
        }
        pin(accb);
        WSTAMP(7 + 16 * l);
        gemm_begin<192>(c, wg, p, 3, false);
#pragma unroll 1
        for (int pn = 0; pn < 4; pn++) {
#pragma unroll
          for (int u = 0; u < 4; u++) {
            if (u == 4 - LEAD24 && pn == 3) yield_turn(c, wg, p, Nop());
            gemm_step<192, false>(accb, c, wg, p, [&]() { gelu_chunk<4>(held + 4 * u, hp + 2 * u * CB_BYTES); });
            if (u == (LEAD24 > TURN_EARLY ? 3 - TURN_EARLY : 3)) pass_turn(c, pn == 3);
          }
          hp += 8 * CB_BYTES;
          __syncwarp();
          mbar_arrive_if(pub + 8 * (6 + pn), lane == 0);
          mbar_arrive_if(c.bar + 8 * BAR_ALIGN, pn == ALIGN_AT && tid == 0);
          pick_group<16, 1, 4>(held, pn + 1);
        }
        p.drain();
        WSTAMP(8 + 16 * l);
#pragma unroll
        for (int x = 0; x < 48; x++) held[x] = pack_f16(accb[2 * x] * ((x & 1) ? s1.y : s0.y), accb[2 * x + 1] * ((x & 1) ? s1.y : s0.y));
      }
      {
#pragma unroll
        for (int x = 0; x < 8; x++) {
          uint4 v;
          asm volatile("ld.shared.v4.u32 {%0,%1,%2,%3}, [%4];" : "=r"(v.x), "=r"(v.y), "=r"(v.z), "=r"(v.w) : "r"(park + x * 2048) : "memory");
          acc[8 * x] = bf_lo(v.x); acc[8 * x + 1] = bf_hi(v.x); acc[8 * x + 2] = bf_lo(v.y); acc[8 * x + 3] = bf_hi(v.y);
          acc[8 * x + 4] = bf_lo(v.z); acc[8 * x + 5] = bf_hi(v.z); acc[8 * x + 6] = bf_lo(v.w); acc[8 * x + 7] = bf_hi(v.w);
        }
        pin(acc);
        WSTAMP(9 + 16 * l);
        gemm_begin<128>(c, wg, p, 4, false);
#pragma unroll 1
        for (int hpn = 0; hpn < 6; hpn++) {
#pragma unroll
          for (int u = 0; u < 4; u++) gemm_step<128, false>(acc, c, wg, p, [&]() { gelu_chunk<2>(held + 2 * u, hp + u * CB_BYTES); });
          hp += 4 * CB_BYTES;
          __syncwarp();
          mbar_arrive_if(pub + 8 * (10 + (hpn >> 1)), (hpn & 1) && lane == 0);
          pick_group<8, 1, 6>(held, hpn + 1);
        }
        WSTAMP(12 + 16 * l);
        gemm_steps<128, false, 0>(acc, c, wg, p, 32, Nop(), Nop());
        WSTAMP(10 + 16 * l);
      }
      if (l == 0) {
        put_partial(acc, &g_part[2][c.j][row]);
        WSTAMP(11);
        uint32_t yv[32];
        const char* yp = reinterpret_cast<const char*>(g_y) + c.j * 16 * CB_BYTES + wrow * 16 + lane * 8;
#pragma unroll
        for (int x = 0; x < 16; x++) asm volatile("ld.global.L1::no_allocate.v2.u32 {%0,%1}, [%2];" : "=r"(yv[2 * x]), "=r"(yv[2 * x + 1]) : "l"(yp + x * CB_BYTES) : "memory");
        const float2* sp = &g_part[2][2 * qd][row];
        float2 s0, s1;
        rs.load(sp, sp + 8);
        rs.finish(sp, sp + 8, c.abort, s0, s1);
        WSTAMP(13);
        float nb0 = -s0.x * s0.y, nb1 = -s1.x * s1.y;
#pragma unroll
        for (int pn = 0; pn < 2; pn++) {
          if (pn == 1) { const float z = late_zero(c.abort); nb0 += z; nb1 += z; }
#pragma unroll
          for (int x = 16 * pn; x < 16 * pn + 16; x++) {
            const float r = (x & 1) ? s1.y : s0.y, nb = (x & 1) ? nb1 : nb0;
            acc[2 * x] = fmaf(fmaf(acc[2 * x], r, nb), bf_lo(yv[x]), acc[2 * x]);
            acc[2 * x + 1] = fmaf(fmaf(acc[2 * x + 1], r, nb), bf_hi(yv[x]), acc[2 * x + 1]);
            x3[x] = pack_bf16(acc[2 * x], acc[2 * x + 1]);
          }
          emit_panel(x3 + 16 * pn, reinterpret_cast<char*>(g_x3[1]) + frag + pn * 8 * CB_BYTES, stage + pn * 8192, true, pub + 8 * pn);
        }
        put_partial(acc, &g_part[3][c.j][row]);
      } else {
#pragma unroll
        for (int x = 0; x < 32; x++) x3[x] = pack_bf16(acc[2 * x], acc[2 * x + 1]);
      }
    }
    {
      const uint32_t ob = c.sm + SM_X + warp * 4096, oa = ob + (lane & 15) * 128 + (((lane >> 4) ^ (lane & 7)) << 4);
#pragma unroll
      for (int x = 0; x < 16; x += 2) stsm_x4((oa + (x >> 3) * 2048) ^ ((x & 7) << 4), x3[2 * x], x3[2 * x + 1], x3[2 * x + 2], x3[2 * x + 3]);
      fence_async_smem();
      __syncwarp();
      if (lane == 0) {
        tma_store_2d(&maps.m[M_OUT], ob, c.j * 128, wrow);
        tma_store_2d(&maps.m[M_OUT], ob + 2048, c.j * 128 + 64, wrow);
        bulk_commit();
        asm volatile("cp.async.bulk.wait_group.read 0;" ::: "memory");
      }
    }
    WSTAMP(27);
    cluster_exit_barrier();
    WSTAMP(30);
  }
}

typedef CUresult (*EncodeFn)(CUtensorMap*, CUtensorMapDataType, cuuint32_t, void*, const cuuint64_t*, const cuuint64_t*, const cuuint32_t*,
                             const cuuint32_t*, CUtensorMapInterleave, CUtensorMapSwizzle, CUtensorMapL2promotion, CUtensorMapFloatOOBfill);

void encode(EncodeFn fn, CUtensorMap* m, CUtensorMapDataType type, const void* ptr, int rank, const cuuint64_t* dims, const cuuint64_t* strides,
            const cuuint32_t* box, CUtensorMapSwizzle swizzle, CUtensorMapL2promotion promo = CU_TENSOR_MAP_L2_PROMOTION_L2_128B) {
  const cuuint32_t es[3] = {1, 1, 1};
  fn(m, type, rank, const_cast<void*>(ptr), dims, strides, box, es, CU_TENSOR_MAP_INTERLEAVE_NONE, swizzle, promo, CU_TENSOR_MAP_FLOAT_OOB_FILL_NONE);
}
void map_act(EncodeFn fn, CUtensorMap* m, const void* ptr, int cols) {
  const cuuint64_t dims[2] = {(cuuint64_t)SEQ * 2, (cuuint64_t)cols / 8}, st[1] = {(cuuint64_t)CB_BYTES};
  const cuuint32_t box[2] = {128, 8};
  encode(fn, m, CU_TENSOR_MAP_DATA_TYPE_UINT64, ptr, 2, dims, st, box, CU_TENSOR_MAP_SWIZZLE_NONE);
}
void map_rows(EncodeFn fn, CUtensorMap* m, const void* ptr, int rows, int cols, int box_rows, int box_cols, CUtensorMapSwizzle swizzle,
              CUtensorMapL2promotion promo) {
  const cuuint64_t dims[2] = {(cuuint64_t)cols, (cuuint64_t)rows}, st[1] = {(cuuint64_t)cols * 2};
  const cuuint32_t box[2] = {(cuuint32_t)box_cols, (cuuint32_t)box_rows};
  encode(fn, m, CU_TENSOR_MAP_DATA_TYPE_BFLOAT16, ptr, 2, dims, st, box, swizzle, promo);
}
void map_w(EncodeFn fn, CUtensorMap* m, const void* ptr, int rows, int cols, int panels) {
  const cuuint64_t dims[3] = {64, (cuuint64_t)rows, (cuuint64_t)cols / 64}, st[2] = {(cuuint64_t)cols * 2, 128};
  const cuuint32_t box[3] = {64, 64, (cuuint32_t)panels};
  encode(fn, m, CU_TENSOR_MAP_DATA_TYPE_BFLOAT16, ptr, 3, dims, st, box, CU_TENSOR_MAP_SWIZZLE_128B);
}

}

extern "C" void kernel_launch(void* const* d_in, const int* in_sizes, int n_in, void* d_out, int out_size) {
  (void)in_sizes; (void)n_in; (void)out_size;
  const bf16* q = (const bf16*)d_in[0];
  const bf16* k = (const bf16*)d_in[1];
  const bf16* v = (const bf16*)d_in[2];
  const bf16* shift_k = (const bf16*)d_in[3];
  const bf16* ssm_k = (const bf16*)d_in[4];
  const bf16* ssm_d = (const bf16*)d_in[5];
  const bf16* w1 = (const bf16*)d_in[7];
  const bf16* w2 = (const bf16*)d_in[8];
  const bf16* w3 = (const bf16*)d_in[9];
  const bf16* w4 = (const bf16*)d_in[10];

  static EncodeFn fn = nullptr;
  static void *p_x3, *p_h, *p_x1, *p_hid;
  if (!fn) {
    void* p = nullptr;
    cudaDriverEntryPointQueryResult qr;
    cudaGetDriverEntryPoint("cuTensorMapEncodeTiled", &p, cudaEnableDefault, &qr);
    fn = (EncodeFn)p;
    cudaGetSymbolAddress(&p_x3, g_x3);
    cudaGetSymbolAddress(&p_h, g_h);
    cudaGetSymbolAddress(&p_x1, g_x1);
    cudaGetSymbolAddress(&p_hid, g_hid);
    cudaFuncSetAttribute(conv_prep_kernel, cudaFuncAttributeMaxDynamicSharedMemorySize, CV_SMEM);
    cudaFuncSetAttribute(mega_kernel, cudaFuncAttributeMaxDynamicSharedMemorySize, MEGA_SMEM);
  }
  Maps maps;
  map_act(fn, &maps.m[M_X3A], p_x3, DM);
  map_act(fn, &maps.m[M_X3B], (const bf16*)p_x3 + SEQ * DM, DM);
  map_act(fn, &maps.m[M_H], p_h, DM);
  map_act(fn, &maps.m[M_X1], p_x1, DM);
  map_act(fn, &maps.m[M_HID], p_hid, FF);
  map_rows(fn, &maps.m[M_OUT], d_out, SEQ, DM, 16, 64, CU_TENSOR_MAP_SWIZZLE_128B, CU_TENSOR_MAP_L2_PROMOTION_L2_128B);
  map_w(fn, &maps.m[M_W1], w1, DM, DM, 2);
  map_w(fn, &maps.m[M_W2], w2, DM, DM, 2);
  map_w(fn, &maps.m[M_W3A], w3, DM, FF, 4);
  map_w(fn, &maps.m[M_W3B], w3, DM, FF, 3);
  map_w(fn, &maps.m[M_W4], w4, FF, DM, 2);

  cudaStream_t st = cudaStreamPerThread;
  ConvMaps cm;
  map_rows(fn, &cm.k, k, SEQ, DM, 256, 8, CU_TENSOR_MAP_SWIZZLE_NONE, KV_PROMO);
  map_rows(fn, &cm.v, v, SEQ, DM, 256, 8, CU_TENSOR_MAP_SWIZZLE_NONE, KV_PROMO);
  map_rows(fn, &cm.w1, w1, DM, DM, 256, 32, CU_TENSOR_MAP_SWIZZLE_64B, CU_TENSOR_MAP_L2_PROMOTION_L2_128B);
  map_rows(fn, &cm.w3, w3, DM, FF, 256, 32, CU_TENSOR_MAP_SWIZZLE_64B, CU_TENSOR_MAP_L2_PROMOTION_L2_128B);
  conv_prep_kernel<<<128, 512, CV_SMEM, st>>>(cm, q, shift_k, ssm_k, ssm_d, w2);

  cudaLaunchConfig_t cfg = {};
  cfg.gridDim = dim3(128);
  cfg.blockDim = dim3(384);
  cfg.dynamicSmemBytes = MEGA_SMEM;
  cfg.stream = st;
  cudaLaunchAttribute at[1];
  at[0].id = cudaLaunchAttributeProgrammaticStreamSerialization;
  at[0].val.programmaticStreamSerializationAllowed = 1;
  cfg.attrs = at;
  cfg.numAttrs = 1;
  cudaLaunchKernelEx(&cfg, mega_kernel, maps, w4);
}
```

```cpp
#include <cuda_runtime.h>
#include <cuda_bf16.h>
#include <cuda.h>
#include <stdint.h>

namespace {

typedef __nv_bfloat16 bf16;
constexpr int SEQ = 2048, DM = 1024, FF = 3584;
constexpr float LN_EPS = 1e-5f;

constexpr int CB_BYTES = SEQ * 16;
__device__ __align__(1024) bf16 g_x3[2][SEQ * DM];
__device__ __align__(1024) bf16 g_h[SEQ * DM];
__device__ __align__(1024) bf16 g_x1[SEQ * DM];
__device__ __align__(1024) bf16 g_hid[SEQ * FF];
__device__ __align__(1024) bf16 g_y[SEQ * DM];
__device__ __align__(128) float2 g_qstat[SEQ];
__device__ __align__(128) float2 g_part[5][8][SEQ];
__device__ __align__(128) float g_cs1[4][DM];
__device__ __align__(128) float g_cs3[FF];
constexpr int FS = 8;
constexpr int FLAG_WORDS = 32 * 8 * FS;
__device__ __align__(128) uint32_t g_flag[FLAG_WORDS];
__device__ __align__(128) uint32_t g_role[4];
__device__ __align__(128) uint32_t g_qcnt;

__device__ __forceinline__ uint32_t smem_u32(const void* p) { return (uint32_t)__cvta_generic_to_shared(p); }
__device__ __forceinline__ uint32_t opaque(uint32_t x) { uint32_t y; asm volatile("mov.u32 %0, %1;" : "=r"(y) : "r"(x)); return y; }
__device__ __forceinline__ void mbar_init(uint32_t bar, uint32_t cnt) { asm volatile("mbarrier.init.shared::cta.b64 [%0], %1;" :: "r"(bar), "r"(cnt)); }
__device__ __forceinline__ void mbar_expect_tx(uint32_t bar, uint32_t bytes) {
  asm volatile("mbarrier.arrive.expect_tx.shared::cta.b64 _, [%0], %1;" :: "r"(bar), "r"(bytes) : "memory");
}
__device__ __forceinline__ void mbar_expect_tx_cluster(uint32_t bar, uint32_t bytes) {
  asm volatile("mbarrier.arrive.expect_tx.shared::cluster.b64 _, [%0], %1;" :: "r"(bar), "r"(bytes) : "memory");
}
__device__ __forceinline__ void mbar_arrive(uint32_t bar) { asm volatile("mbarrier.arrive.shared::cta.b64 _, [%0];" :: "r"(bar) : "memory"); }
__device__ __forceinline__ void mbar_arrive_if(uint32_t bar, bool cond) {
  asm volatile("{\n.reg .pred p;\nsetp.ne.b32 p, %1, 0;\n@p mbarrier.arrive.shared::cta.b64 _, [%0];\n}" :: "r"(bar), "r"((uint32_t)cond) : "memory");
}
constexpr int SPIN_LIMIT = 1 << 16;
__device__ __forceinline__ bool mbar_try(uint32_t bar, uint32_t parity) {
  uint32_t done;
  asm volatile("{\n.reg .pred p;\nmbarrier.try_wait.parity.shared::cta.b64 p, [%1], %2;\nselp.b32 %0, 1, 0, p;\n}"
               : "=r"(done) : "r"(bar), "r"(parity) : "memory");
  return done != 0;
}
__device__ __forceinline__ void mbar_wait(uint32_t bar, uint32_t parity, int& budget) {
#pragma unroll 1
  while (!mbar_try(bar, parity)) { if (--budget <= 0) break; }
}
__device__ __forceinline__ bool elect_one() {
  uint32_t p;
  asm volatile("{\n.reg .pred P;\nelect.sync _|P, 0xffffffff;\nselp.b32 %0, 1, 0, P;\n}" : "=r"(p));
  return p != 0;
}
__device__ __forceinline__ void fence_async_smem() { asm volatile("fence.proxy.async.shared::cta;" ::: "memory"); }
__device__ __forceinline__ void fence_async_global() { asm volatile("fence.proxy.async.global;" ::: "memory"); }
__device__ __forceinline__ void named_bar(int id, int n) { asm volatile("bar.sync %0, %1;" :: "r"(id), "r"(n) : "memory"); }
__device__ __forceinline__ uint4 ld_nc_u4(const void* p) {
  uint4 v; asm volatile("ld.global.nc.L1::no_allocate.v4.u32 {%0,%1,%2,%3}, [%4];" : "=r"(v.x), "=r"(v.y), "=r"(v.z), "=r"(v.w) : "l"(p)); return v;
}
__device__ __forceinline__ void tma_2d_mc(uint32_t dst, const CUtensorMap* m, uint32_t bar, int c0, int c1, uint16_t mask) {
  asm volatile("cp.async.bulk.tensor.2d.shared::cluster.global.mbarrier::complete_tx::bytes.multicast::cluster [%0], [%1, {%3, %4}], [%2], %5;"
               :: "r"(dst), "l"(m), "r"(bar), "r"(c0), "r"(c1), "h"(mask) : "memory");
}
__device__ __forceinline__ void tma_2d(uint32_t dst, const CUtensorMap* m, uint32_t bar, int c0, int c1) {
  asm volatile("cp.async.bulk.tensor.2d.shared::cluster.global.mbarrier::complete_tx::bytes [%0], [%1, {%3, %4}], [%2];"
               :: "r"(dst), "l"(m), "r"(bar), "r"(c0), "r"(c1) : "memory");
}
__device__ __forceinline__ void bulk_copy_cluster(uint32_t dst, uint32_t src, uint32_t bytes, uint32_t bar) {
  asm volatile("cp.async.bulk.shared::cluster.shared::cta.mbarrier::complete_tx::bytes [%0], [%1], %2, [%3];"
               :: "r"(dst), "r"(src), "r"(bytes), "r"(bar) : "memory");
}
__device__ __forceinline__ uint32_t mapa(uint32_t addr, uint32_t cta) {
  uint32_t r; asm volatile("mapa.shared::cluster.u32 %0, %1, %2;" : "=r"(r) : "r"(addr), "r"(cta)); return r;
}
__device__ __forceinline__ void bulk_store(void* dst, uint32_t src, uint32_t bytes) {
  asm volatile("cp.async.bulk.global.shared::cta.bulk_group [%0], [%1], %2;" :: "l"(dst), "r"(src), "r"(bytes) : "memory");
}
__device__ __forceinline__ void tma_3d(uint32_t dst, const CUtensorMap* m, uint32_t bar, int c0, int c1, int c2) {
  asm volatile("cp.async.bulk.tensor.3d.shared::cluster.global.mbarrier::complete_tx::bytes [%0], [%1, {%3, %4, %5}], [%2];"
               :: "r"(dst), "l"(m), "r"(bar), "r"(c0), "r"(c1), "r"(c2) : "memory");
}
__device__ __forceinline__ void tma_store_2d(const CUtensorMap* m, uint32_t src, int c0, int c1) {
  asm volatile("cp.async.bulk.tensor.2d.global.shared::cta.bulk_group [%0, {%2, %3}], [%1];" :: "l"(m), "r"(src), "r"(c0), "r"(c1) : "memory");
}
__device__ __forceinline__ void bulk_commit() { asm volatile("cp.async.bulk.commit_group;" ::: "memory"); }
__device__ __forceinline__ void bulk_wait_all() { asm volatile("cp.async.bulk.wait_group 0;" ::: "memory"); }
__device__ __forceinline__ void prefetch_l2(const void* p, uint32_t bytes) { asm volatile("cp.async.bulk.prefetch.L2.global [%0], %1;" :: "l"(p), "r"(bytes) : "memory"); }
__device__ __forceinline__ void cluster_exit_barrier() {
  __syncwarp();
  asm volatile("barrier.cluster.arrive.relaxed;\nbarrier.cluster.wait;" ::: "memory");
}
__device__ __forceinline__ void wg_fence() { asm volatile("wgmma.fence.sync.aligned;" ::: "memory"); }
__device__ __forceinline__ void wg_commit() { asm volatile("wgmma.commit_group.sync.aligned;" ::: "memory"); }
template <int N> __device__ __forceinline__ void wg_wait() { asm volatile("wgmma.wait_group.sync.aligned %0;" :: "n"(N) : "memory"); }
template <int R> __device__ __forceinline__ void reg_alloc() { asm volatile("setmaxnreg.inc.sync.aligned.u32 %0;" :: "n"(R)); }
template <int R> __device__ __forceinline__ void reg_dealloc() { asm volatile("setmaxnreg.dec.sync.aligned.u32 %0;" :: "n"(R)); }
__device__ __forceinline__ void ldsm_x4(uint32_t addr, uint32_t& r0, uint32_t& r1, uint32_t& r2, uint32_t& r3) {
  asm volatile("ldmatrix.sync.aligned.m8n8.x4.shared.b16 {%0,%1,%2,%3}, [%4];" : "=r"(r0), "=r"(r1), "=r"(r2), "=r"(r3) : "r"(addr));
}
__device__ __forceinline__ void ldsm_x4_t(uint32_t addr, uint32_t& r0, uint32_t& r1, uint32_t& r2, uint32_t& r3) {
  asm volatile("ldmatrix.sync.aligned.m8n8.x4.trans.shared.b16 {%0,%1,%2,%3}, [%4];" : "=r"(r0), "=r"(r1), "=r"(r2), "=r"(r3) : "r"(addr));
}
__device__ __forceinline__ void stsm_x4(uint32_t addr, uint32_t r0, uint32_t r1, uint32_t r2, uint32_t r3) {
  asm volatile("stmatrix.sync.aligned.m8n8.x4.shared.b16 [%0], {%1,%2,%3,%4};" :: "r"(addr), "r"(r0), "r"(r1), "r"(r2), "r"(r3) : "memory");
}
__device__ __forceinline__ float2 lds_f2(uint32_t addr) { float2 v; asm volatile("ld.shared.v2.f32 {%0,%1}, [%2];" : "=f"(v.x), "=f"(v.y) : "r"(addr)); return v; }
__device__ __forceinline__ void sts16(uint32_t addr, uint16_t v) { asm volatile("st.shared.u16 [%0], %1;" :: "r"(addr), "h"(v) : "memory"); }
__device__ __forceinline__ void sts32(uint32_t addr, uint32_t v) { asm volatile("st.shared.u32 [%0], %1;" :: "r"(addr), "r"(v) : "memory"); }
__device__ __forceinline__ void sts128(uint32_t addr, uint4 v) {
  asm volatile("st.shared.v4.u32 [%0], {%1,%2,%3,%4};" :: "r"(addr), "r"(v.x), "r"(v.y), "r"(v.z), "r"(v.w) : "memory");
}
__device__ __forceinline__ void mma16816(float (&d)[4], uint32_t a0, uint32_t a1, uint32_t a2, uint32_t a3, uint32_t b0, uint32_t b1) {
  asm("mma.sync.aligned.m16n8k16.row.col.f32.bf16.bf16.f32 {%0,%1,%2,%3}, {%4,%5,%6,%7}, {%8,%9}, {%0,%1,%2,%3};"
               : "+f"(d[0]), "+f"(d[1]), "+f"(d[2]), "+f"(d[3]) : "r"(a0), "r"(a1), "r"(a2), "r"(a3), "r"(b0), "r"(b1));
}
__device__ __forceinline__ uint32_t pack_bf16(float lo, float hi) {
  uint32_t r; asm("cvt.rn.bf16x2.f32 %0, %1, %2;" : "=r"(r) : "f"(hi), "f"(lo)); return r;
}
__device__ __forceinline__ float bf_lo(uint32_t v) { return __uint_as_float(v << 16); }
__device__ __forceinline__ float bf_hi(uint32_t v) { return __uint_as_float(v & 0xffff0000u); }
__device__ __forceinline__ uint32_t bmul2(uint32_t a, uint32_t b) { uint32_t r; asm("mul.rn.bf16x2 %0, %1, %2;" : "=r"(r) : "r"(a), "r"(b)); return r; }
__device__ __forceinline__ uint32_t badd2(uint32_t a, uint32_t b) { uint32_t r; asm("add.rn.bf16x2 %0, %1, %2;" : "=r"(r) : "r"(a), "r"(b)); return r; }
#define STAMP(idx) do {} while (0)
#define MSTAMP(idx) do {} while (0)
#define BSTAMP(idx, saddr) do {} while (0)

__device__ __forceinline__ uint32_t pack_f16(float lo, float hi) {
  uint32_t r; asm("cvt.rn.satfinite.f16x2.f32 %0, %1, %2;" : "=r"(r) : "f"(hi), "f"(lo)); return r;
}
__device__ __forceinline__ uint32_t gelu_pair_f16(uint32_t h) {
  const uint32_t c0 = 0x3e623e62u, c1 = 0x34913491u;
  uint32_t u, p, z, t, r, o;
  asm("mul.rn.f16x2 %0, %1, %1;" : "=r"(u) : "r"(h));
  asm("fma.rn.f16x2 %0, %1, %2, %3;" : "=r"(p) : "r"(u), "r"(c1), "r"(c0));
  asm("mul.rn.f16x2 %0, %1, %2;" : "=r"(z) : "r"(h), "r"(p));
  asm("tanh.approx.f16x2 %0, %1;" : "=r"(t) : "r"(z));
  asm("fma.rn.f16x2 %0, %1, %2, %1;" : "=r"(r) : "r"(h), "r"(t));
  float lo, hi;
  asm("{\n.reg .f16 a, b;\nmov.b32 {a, b}, %2;\ncvt.f32.f16 %0, a;\ncvt.f32.f16 %1, b;\n}" : "=f"(lo), "=f"(hi) : "r"(r));
  asm("cvt.rn.bf16x2.f32 %0, %1, %2;" : "=r"(o) : "f"(hi), "f"(lo));
  return o;
}
__device__ __forceinline__ float gelu_from_half(float h) {
  const float c0 = 2.f * 0.7978845608028654f, c1 = 8.f * 0.7978845608028654f * 0.044715f;
  float z = h * fmaf(h * h, c1, c0);
  float t; asm("tanh.approx.f32 %0, %1;" : "=f"(t) : "f"(z));
  return fmaf(h, t, h);
}
__device__ __forceinline__ void wgmma_ss_n128(float (&d)[64], uint32_t a_lo, uint32_t b_lo) {
  asm volatile(
    "{\n.reg .b64 da, db;\nmov.b64 da, {%64, 8};\nmov.b64 db, {%65, 0x40000040};\n"
    "wgmma.mma_async.sync.aligned.m64n128k16.f32.bf16.bf16 "
    "{%0, %1, %2, %3, %4, %5, %6, %7, %8, %9, %10, %11, %12, %13, %14, %15, "
    "%16, %17, %18, %19, %20, %21, %22, %23, %24, %25, %26, %27, %28, %29, %30, %31, "
    "%32, %33, %34, %35, %36, %37, %38, %39, %40, %41, %42, %43, %44, %45, %46, %47, "
    "%48, %49, %50, %51, %52, %53, %54, %55, %56, %57, %58, %59, %60, %61, %62, %63}, "
    "da, db, 1, 1, 1, 0, 1;\n}\n"
    : "+f"(d[0]), "+f"(d[1]), "+f"(d[2]), "+f"(d[3]), "+f"(d[4]), "+f"(d[5]), "+f"(d[6]), "+f"(d[7]),
      "+f"(d[8]), "+f"(d[9]), "+f"(d[10]), "+f"(d[11]), "+f"(d[12]), "+f"(d[13]), "+f"(d[14]), "+f"(d[15]),
      "+f"(d[16]), "+f"(d[17]), "+f"(d[18]), "+f"(d[19]), "+f"(d[20]), "+f"(d[21]), "+f"(d[22]), "+f"(d[23]),
      "+f"(d[24]), "+f"(d[25]), "+f"(d[26]), "+f"(d[27]), "+f"(d[28]), "+f"(d[29]), "+f"(d[30]), "+f"(d[31]),
      "+f"(d[32]), "+f"(d[33]), "+f"(d[34]), "+f"(d[35]), "+f"(d[36]), "+f"(d[37]), "+f"(d[38]), "+f"(d[39]),
      "+f"(d[40]), "+f"(d[41]), "+f"(d[42]), "+f"(d[43]), "+f"(d[44]), "+f"(d[45]), "+f"(d[46]), "+f"(d[47]),
      "+f"(d[48]), "+f"(d[49]), "+f"(d[50]), "+f"(d[51]), "+f"(d[52]), "+f"(d[53]), "+f"(d[54]), "+f"(d[55]),
      "+f"(d[56]), "+f"(d[57]), "+f"(d[58]), "+f"(d[59]), "+f"(d[60]), "+f"(d[61]), "+f"(d[62]), "+f"(d[63])
    : "r"(a_lo), "r"(b_lo));
}
__device__ __forceinline__ void wgmma_ss_n192(float (&d)[96], uint32_t a_lo, uint32_t b_lo) {
  asm volatile(
    "{\n.reg .b64 da, db;\nmov.b64 da, {%96, 8};\nmov.b64 db, {%97, 0x40000040};\n"
    "wgmma.mma_async.sync.aligned.m64n192k16.f32.bf16.bf16 "
    "{%0, %1, %2, %3, %4, %5, %6, %7, %8, %9, %10, %11, %12, %13, %14, %15, "
    "%16, %17, %18, %19, %20, %21, %22, %23, %24, %25, %26, %27, %28, %29, %30, %31, "
    "%32, %33, %34, %35, %36, %37, %38, %39, %40, %41, %42, %43, %44, %45, %46, %47, "
    "%48, %49, %50, %51, %52, %53, %54, %55, %56, %57, %58, %59, %60, %61, %62, %63, "
    "%64, %65, %66, %67, %68, %69, %70, %71, %72, %73, %74, %75, %76, %77, %78, %79, "
    "%80, %81, %82, %83, %84, %85, %86, %87, %88, %89, %90, %91, %92, %93, %94, %95}, "
    "da, db, 1, 1, 1, 0, 1;\n}\n"
    : "+f"(d[0]), "+f"(d[1]), "+f"(d[2]), "+f"(d[3]), "+f"(d[4]), "+f"(d[5]), "+f"(d[6]), "+f"(d[7]),
      "+f"(d[8]), "+f"(d[9]), "+f"(d[10]), "+f"(d[11]), "+f"(d[12]), "+f"(d[13]), "+f"(d[14]), "+f"(d[15]),
      "+f"(d[16]), "+f"(d[17]), "+f"(d[18]), "+f"(d[19]), "+f"(d[20]), "+f"(d[21]), "+f"(d[22]), "+f"(d[23]),
      "+f"(d[24]), "+f"(d[25]), "+f"(d[26]), "+f"(d[27]), "+f"(d[28]), "+f"(d[29]), "+f"(d[30]), "+f"(d[31]),
      "+f"(d[32]), "+f"(d[33]), "+f"(d[34]), "+f"(d[35]), "+f"(d[36]), "+f"(d[37]), "+f"(d[38]), "+f"(d[39]),
      "+f"(d[40]), "+f"(d[41]), "+f"(d[42]), "+f"(d[43]), "+f"(d[44]), "+f"(d[45]), "+f"(d[46]), "+f"(d[47]),
      "+f"(d[48]), "+f"(d[49]), "+f"(d[50]), "+f"(d[51]), "+f"(d[52]), "+f"(d[53]), "+f"(d[54]), "+f"(d[55]),
      "+f"(d[56]), "+f"(d[57]), "+f"(d[58]), "+f"(d[59]), "+f"(d[60]), "+f"(d[61]), "+f"(d[62]), "+f"(d[63]),
      "+f"(d[64]), "+f"(d[65]), "+f"(d[66]), "+f"(d[67]), "+f"(d[68]), "+f"(d[69]), "+f"(d[70]), "+f"(d[71]),
      "+f"(d[72]), "+f"(d[73]), "+f"(d[74]), "+f"(d[75]), "+f"(d[76]), "+f"(d[77]), "+f"(d[78]), "+f"(d[79]),
      "+f"(d[80]), "+f"(d[81]), "+f"(d[82]), "+f"(d[83]), "+f"(d[84]), "+f"(d[85]), "+f"(d[86]), "+f"(d[87]),
      "+f"(d[88]), "+f"(d[89]), "+f"(d[90]), "+f"(d[91]), "+f"(d[92]), "+f"(d[93]), "+f"(d[94]), "+f"(d[95])
    : "r"(a_lo), "r"(b_lo));
}
__device__ __forceinline__ void wgmma_ss_n256(float (&d)[128], uint32_t a_lo, uint32_t b_lo) {
  asm volatile(
    "{\n.reg .b64 da, db;\nmov.b64 da, {%128, 8};\nmov.b64 db, {%129, 0x40000040};\n"
    "wgmma.mma_async.sync.aligned.m64n256k16.f32.bf16.bf16 "
    "{%0, %1, %2, %3, %4, %5, %6, %7, %8, %9, %10, %11, %12, %13, %14, %15, "
    "%16, %17, %18, %19, %20, %21, %22, %23, %24, %25, %26, %27, %28, %29, %30, %31, "
    "%32, %33, %34, %35, %36, %37, %38, %39, %40, %41, %42, %43, %44, %45, %46, %47, "
    "%48, %49, %50, %51, %52, %53, %54, %55, %56, %57, %58, %59, %60, %61, %62, %63, "
    "%64, %65, %66, %67, %68, %69, %70, %71, %72, %73, %74, %75, %76, %77, %78, %79, "
    "%80, %81, %82, %83, %84, %85, %86, %87, %88, %89, %90, %91, %92, %93, %94, %95, "
    "%96, %97, %98, %99, %100, %101, %102, %103, %104, %105, %106, %107, %108, %109, %110, %111, "
    "%112, %113, %114, %115, %116, %117, %118, %119, %120, %121, %122, %123, %124, %125, %126, %127}, "
    "da, db, 1, 1, 1, 0, 1;\n}\n"
    : "+f"(d[0]), "+f"(d[1]), "+f"(d[2]), "+f"(d[3]), "+f"(d[4]), "+f"(d[5]), "+f"(d[6]), "+f"(d[7]),
      "+f"(d[8]), "+f"(d[9]), "+f"(d[10]), "+f"(d[11]), "+f"(d[12]), "+f"(d[13]), "+f"(d[14]), "+f"(d[15]),
      "+f"(d[16]), "+f"(d[17]), "+f"(d[18]), "+f"(d[19]), "+f"(d[20]), "+f"(d[21]), "+f"(d[22]), "+f"(d[23]),
      "+f"(d[24]), "+f"(d[25]), "+f"(d[26]), "+f"(d[27]), "+f"(d[28]), "+f"(d[29]), "+f"(d[30]), "+f"(d[31]),
      "+f"(d[32]), "+f"(d[33]), "+f"(d[34]), "+f"(d[35]), "+f"(d[36]), "+f"(d[37]), "+f"(d[38]), "+f"(d[39]),
      "+f"(d[40]), "+f"(d[41]), "+f"(d[42]), "+f"(d[43]), "+f"(d[44]), "+f"(d[45]), "+f"(d[46]), "+f"(d[47]),
      "+f"(d[48]), "+f"(d[49]), "+f"(d[50]), "+f"(d[51]), "+f"(d[52]), "+f"(d[53]), "+f"(d[54]), "+f"(d[55]),
      "+f"(d[56]), "+f"(d[57]), "+f"(d[58]), "+f"(d[59]), "+f"(d[60]), "+f"(d[61]), "+f"(d[62]), "+f"(d[63]),
      "+f"(d[64]), "+f"(d[65]), "+f"(d[66]), "+f"(d[67]), "+f"(d[68]), "+f"(d[69]), "+f"(d[70]), "+f"(d[71]),
      "+f"(d[72]), "+f"(d[73]), "+f"(d[74]), "+f"(d[75]), "+f"(d[76]), "+f"(d[77]), "+f"(d[78]), "+f"(d[79]),
      "+f"(d[80]), "+f"(d[81]), "+f"(d[82]), "+f"(d[83]), "+f"(d[84]), "+f"(d[85]), "+f"(d[86]), "+f"(d[87]),
      "+f"(d[88]), "+f"(d[89]), "+f"(d[90]), "+f"(d[91]), "+f"(d[92]), "+f"(d[93]), "+f"(d[94]), "+f"(d[95]),
      "+f"(d[96]), "+f"(d[97]), "+f"(d[98]), "+f"(d[99]), "+f"(d[100]), "+f"(d[101]), "+f"(d[102]), "+f"(d[103]),
      "+f"(d[104]), "+f"(d[105]), "+f"(d[106]), "+f"(d[107]), "+f"(d[108]), "+f"(d[109]), "+f"(d[110]), "+f"(d[111]),
      "+f"(d[112]), "+f"(d[113]), "+f"(d[114]), "+f"(d[115]), "+f"(d[116]), "+f"(d[117]), "+f"(d[118]), "+f"(d[119]),
      "+f"(d[120]), "+f"(d[121]), "+f"(d[122]), "+f"(d[123]), "+f"(d[124]), "+f"(d[125]), "+f"(d[126]), "+f"(d[127])
    : "r"(a_lo), "r"(b_lo));
}
__device__ __forceinline__ void wgmma_ss_n128_p(float (&d)[64], uint32_t a_lo, uint32_t b_lo, uint32_t keep) {
  asm volatile(
    "{\n.reg .pred p;\nsetp.ne.b32 p, %66, 0;\n"
    "{\n.reg .b64 da, db;\nmov.b64 da, {%64, 8};\nmov.b64 db, {%65, 0x40000040};\n"
    "wgmma.mma_async.sync.aligned.m64n128k16.f32.bf16.bf16 "
    "{%0, %1, %2, %3, %4, %5, %6, %7, %8, %9, %10, %11, %12, %13, %14, %15, "
    "%16, %17, %18, %19, %20, %21, %22, %23, %24, %25, %26, %27, %28, %29, %30, %31, "
    "%32, %33, %34, %35, %36, %37, %38, %39, %40, %41, %42, %43, %44, %45, %46, %47, "
    "%48, %49, %50, %51, %52, %53, %54, %55, %56, %57, %58, %59, %60, %61, %62, %63}, "
    "da, db, p, 1, 1, 0, 1;\n}\n}\n"
    : "+f"(d[0]), "+f"(d[1]), "+f"(d[2]), "+f"(d[3]), "+f"(d[4]), "+f"(d[5]), "+f"(d[6]), "+f"(d[7]),
      "+f"(d[8]), "+f"(d[9]), "+f"(d[10]), "+f"(d[11]), "+f"(d[12]), "+f"(d[13]), "+f"(d[14]), "+f"(d[15]),
      "+f"(d[16]), "+f"(d[17]), "+f"(d[18]), "+f"(d[19]), "+f"(d[20]), "+f"(d[21]), "+f"(d[22]), "+f"(d[23]),
      "+f"(d[24]), "+f"(d[25]), "+f"(d[26]), "+f"(d[27]), "+f"(d[28]), "+f"(d[29]), "+f"(d[30]), "+f"(d[31]),
      "+f"(d[32]), "+f"(d[33]), "+f"(d[34]), "+f"(d[35]), "+f"(d[36]), "+f"(d[37]), "+f"(d[38]), "+f"(d[39]),
      "+f"(d[40]), "+f"(d[41]), "+f"(d[42]), "+f"(d[43]), "+f"(d[44]), "+f"(d[45]), "+f"(d[46]), "+f"(d[47]),
      "+f"(d[48]), "+f"(d[49]), "+f"(d[50]), "+f"(d[51]), "+f"(d[52]), "+f"(d[53]), "+f"(d[54]), "+f"(d[55]),
      "+f"(d[56]), "+f"(d[57]), "+f"(d[58]), "+f"(d[59]), "+f"(d[60]), "+f"(d[61]), "+f"(d[62]), "+f"(d[63])
    : "r"(a_lo), "r"(b_lo), "r"(keep));
}
__device__ __forceinline__ void wgmma_ss_n256_first(float (&d)[128], uint32_t a_lo, uint32_t b_lo) {
  asm volatile(
    "{\n.reg .b64 da, db;\nmov.b64 da, {%128, 8};\nmov.b64 db, {%129, 0x40000040};\n"
    "mov.b32 %0, 0; mov.b32 %1, 0; mov.b32 %2, 0; mov.b32 %3, 0; mov.b32 %4, 0; mov.b32 %5, 0; mov.b32 %6, 0; mov.b32 %7, 0;\n"
    "mov.b32 %8, 0; mov.b32 %9, 0; mov.b32 %10, 0; mov.b32 %11, 0; mov.b32 %12, 0; mov.b32 %13, 0; mov.b32 %14, 0; mov.b32 %15, 0;\n"
    "mov.b32 %16, 0; mov.b32 %17, 0; mov.b32 %18, 0; mov.b32 %19, 0; mov.b32 %20, 0; mov.b32 %21, 0; mov.b32 %22, 0; mov.b32 %23, 0;\n"
    "mov.b32 %24, 0; mov.b32 %25, 0; mov.b32 %26, 0; mov.b32 %27, 0; mov.b32 %28, 0; mov.b32 %29, 0; mov.b32 %30, 0; mov.b32 %31, 0;\n"
    "mov.b32 %32, 0; mov.b32 %33, 0; mov.b32 %34, 0; mov.b32 %35, 0; mov.b32 %36, 0; mov.b32 %37, 0; mov.b32 %38, 0; mov.b32 %39, 0;\n"
    "mov.b32 %40, 0; mov.b32 %41, 0; mov.b32 %42, 0; mov.b32 %43, 0; mov.b32 %44, 0; mov.b32 %45, 0; mov.b32 %46, 0; mov.b32 %47, 0;\n"
    "mov.b32 %48, 0; mov.b32 %49, 0; mov.b32 %50, 0; mov.b32 %51, 0; mov.b32 %52, 0; mov.b32 %53, 0; mov.b32 %54, 0; mov.b32 %55, 0;\n"
    "mov.b32 %56, 0; mov.b32 %57, 0; mov.b32 %58, 0; mov.b32 %59, 0; mov.b32 %60, 0; mov.b32 %61, 0; mov.b32 %62, 0; mov.b32 %63, 0;\n"
    "mov.b32 %64, 0; mov.b32 %65, 0; mov.b32 %66, 0; mov.b32 %67, 0; mov.b32 %68, 0; mov.b32 %69, 0; mov.b32 %70, 0; mov.b32 %71, 0;\n"
    "mov.b32 %72, 0; mov.b32 %73, 0; mov.b32 %74, 0; mov.b32 %75, 0; mov.b32 %76, 0; mov.b32 %77, 0; mov.b32 %78, 0; mov.b32 %79, 0;\n"
    "mov.b32 %80, 0; mov.b32 %81, 0; mov.b32 %82, 0; mov.b32 %83, 0; mov.b32 %84, 0; mov.b32 %85, 0; mov.b32 %86, 0; mov.b32 %87, 0;\n"
    "mov.b32 %88, 0; mov.b32 %89, 0; mov.b32 %90, 0; mov.b32 %91, 0; mov.b32 %92, 0; mov.b32 %93, 0; mov.b32 %94, 0; mov.b32 %95, 0;\n"
    "mov.b32 %96, 0; mov.b32 %97, 0; mov.b32 %98, 0; mov.b32 %99, 0; mov.b32 %100, 0; mov.b32 %101, 0; mov.b32 %102, 0; mov.b32 %103, 0;\n"
    "mov.b32 %104, 0; mov.b32 %105, 0; mov.b32 %106, 0; mov.b32 %107, 0; mov.b32 %108, 0; mov.b32 %109, 0; mov.b32 %110, 0; mov.b32 %111, 0;\n"
    "mov.b32 %112, 0; mov.b32 %113, 0; mov.b32 %114, 0; mov.b32 %115, 0; mov.b32 %116, 0; mov.b32 %117, 0; mov.b32 %118, 0; mov.b32 %119, 0;\n"
    "mov.b32 %120, 0; mov.b32 %121, 0; mov.b32 %122, 0; mov.b32 %123, 0; mov.b32 %124, 0; mov.b32 %125, 0; mov.b32 %126, 0; mov.b32 %127, 0;\n"
    "wgmma.mma_async.sync.aligned.m64n256k16.f32.bf16.bf16 "
    "{%0, %1, %2, %3, %4, %5, %6, %7, %8, %9, %10, %11, %12, %13, %14, %15, "
    "%16, %17, %18, %19, %20, %21, %22, %23, %24, %25, %26, %27, %28, %29, %30, %31, "
    "%32, %33, %34, %35, %36, %37, %38, %39, %40, %41, %42, %43, %44, %45, %46, %47, "
    "%48, %49, %50, %51, %52, %53, %54, %55, %56, %57, %58, %59, %60, %61, %62, %63, "
    "%64, %65, %66, %67, %68, %69, %70, %71, %72, %73, %74, %75, %76, %77, %78, %79, "
    "%80, %81, %82, %83, %84, %85, %86, %87, %88, %89, %90, %91, %92, %93, %94, %95, "
    "%96, %97, %98, %99, %100, %101, %102, %103, %104, %105, %106, %107, %108, %109, %110, %111, "
    "%112, %113, %114, %115, %116, %117, %118, %119, %120, %121, %122, %123, %124, %125, %126, %127}, "
    "da, db, 1, 1, 1, 0, 1;\n}\n"
    : "=f"(d[0]), "=f"(d[1]), "=f"(d[2]), "=f"(d[3]), "=f"(d[4]), "=f"(d[5]), "=f"(d[6]), "=f"(d[7]),
      "=f"(d[8]), "=f"(d[9]), "=f"(d[10]), "=f"(d[11]), "=f"(d[12]), "=f"(d[13]), "=f"(d[14]), "=f"(d[15]),
      "=f"(d[16]), "=f"(d[17]), "=f"(d[18]), "=f"(d[19]), "=f"(d[20]), "=f"(d[21]), "=f"(d[22]), "=f"(d[23]),
      "=f"(d[24]), "=f"(d[25]), "=f"(d[26]), "=f"(d[27]), "=f"(d[28]), "=f"(d[29]), "=f"(d[30]), "=f"(d[31]),
      "=f"(d[32]), "=f"(d[33]), "=f"(d[34]), "=f"(d[35]), "=f"(d[36]), "=f"(d[37]), "=f"(d[38]), "=f"(d[39]),
      "=f"(d[40]), "=f"(d[41]), "=f"(d[42]), "=f"(d[43]), "=f"(d[44]), "=f"(d[45]), "=f"(d[46]), "=f"(d[47]),
      "=f"(d[48]), "=f"(d[49]), "=f"(d[50]), "=f"(d[51]), "=f"(d[52]), "=f"(d[53]), "=f"(d[54]), "=f"(d[55]),
      "=f"(d[56]), "=f"(d[57]), "=f"(d[58]), "=f"(d[59]), "=f"(d[60]), "=f"(d[61]), "=f"(d[62]), "=f"(d[63]),
      "=f"(d[64]), "=f"(d[65]), "=f"(d[66]), "=f"(d[67]), "=f"(d[68]), "=f"(d[69]), "=f"(d[70]), "=f"(d[71]),
      "=f"(d[72]), "=f"(d[73]), "=f"(d[74]), "=f"(d[75]), "=f"(d[76]), "=f"(d[77]), "=f"(d[78]), "=f"(d[79]),
      "=f"(d[80]), "=f"(d[81]), "=f"(d[82]), "=f"(d[83]), "=f"(d[84]), "=f"(d[85]), "=f"(d[86]), "=f"(d[87]),
      "=f"(d[88]), "=f"(d[89]), "=f"(d[90]), "=f"(d[91]), "=f"(d[92]), "=f"(d[93]), "=f"(d[94]), "=f"(d[95]),
      "=f"(d[96]), "=f"(d[97]), "=f"(d[98]), "=f"(d[99]), "=f"(d[100]), "=f"(d[101]), "=f"(d[102]), "=f"(d[103]),
      "=f"(d[104]), "=f"(d[105]), "=f"(d[106]), "=f"(d[107]), "=f"(d[108]), "=f"(d[109]), "=f"(d[110]), "=f"(d[111]),
      "=f"(d[112]), "=f"(d[113]), "=f"(d[114]), "=f"(d[115]), "=f"(d[116]), "=f"(d[117]), "=f"(d[118]), "=f"(d[119]),
      "=f"(d[120]), "=f"(d[121]), "=f"(d[122]), "=f"(d[123]), "=f"(d[124]), "=f"(d[125]), "=f"(d[126]), "=f"(d[127])
    : "r"(a_lo), "r"(b_lo));
}

template <int N> struct Mma;
template <> struct Mma<128> {
  static __device__ __forceinline__ void ss(float (&d)[64], uint32_t a, uint32_t b) { wgmma_ss_n128(d, a, b); }
  static __device__ __forceinline__ void ss(float (&d)[64], uint32_t a, uint32_t b, uint32_t keep) { wgmma_ss_n128_p(d, a, b, keep); }
};
template <> struct Mma<192> {
  static __device__ __forceinline__ void ss(float (&d)[96], uint32_t a, uint32_t b) { wgmma_ss_n192(d, a, b); }
};
template <> struct Mma<256> {
  static __device__ __forceinline__ void ss(float (&d)[128], uint32_t a, uint32_t b) { wgmma_ss_n256(d, a, b); }
  static __device__ __forceinline__ void ss(float (&d)[128], uint32_t a, uint32_t b, uint32_t) { wgmma_ss_n256_first(d, a, b); }
};
template <int R> __device__ __forceinline__ void pin(float (&d)[R]) {
#pragma unroll
  for (int x = 0; x < R; x++) asm volatile("" : "+f"(d[x]));
}

__device__ __forceinline__ uint32_t ld_relaxed(const uint32_t* p) {
  uint32_t v; asm volatile("ld.relaxed.gpu.global.u32 %0, [%1];" : "=r"(v) : "l"(p) : "memory"); return v;
}
__device__ __forceinline__ void st_release(uint32_t* p, uint32_t v) { asm volatile("st.release.gpu.global.u32 [%0], %1;" :: "l"(p), "r"(v) : "memory"); }
__device__ __forceinline__ void stg32(void* p, uint32_t v) { asm volatile("st.global.u32 [%0], %1;" :: "l"(p), "r"(v) : "memory"); }
__device__ __forceinline__ float rsqrt_fast(float x) { float r; asm("rsqrt.approx.ftz.f32 %0, %1;" : "=f"(r) : "f"(x)); return r; }
__device__ __forceinline__ uint32_t gate_pair(uint32_t x, uint32_t y, float r, float nb) {
  const float a = bf_lo(x), b = bf_hi(x);
  return pack_bf16(fmaf(fmaf(a, r, nb), bf_lo(y), a), fmaf(fmaf(b, r, nb), bf_hi(y), b));
}

constexpr int CV_KT_O = 4144;
constexpr int CV_KT_CH = 8336;
constexpr int CV_KH = 2064;
constexpr int CV_U_PLANE = 2240;
constexpr int CV_U_CH = 4496;
constexpr int CV_U = 8 * CV_KT_CH;
constexpr int CV_K = CV_U + 8 * CV_U_CH;
constexpr int CV_V = CV_K + 128 + 32768;
constexpr int CV_VQ = 8320, CV_Y_CH = 1040;
constexpr int CV_X = (CV_V + 4 * CV_VQ + 1023) / 1024 * 1024;
constexpr int CV_XROW = 2064;
constexpr int CV_ST = CV_X + 16 * CV_XROW;
constexpr int CV_BAR = CV_ST + 16384;
enum { CB_K0, CB_K1, CB_Q0, CB_Q1, CB_Q2, CB_Q3, CB_X0, CB_X1, CB_ST, CB_O1, CB_U1, CB_U2, CB_Y0, CB_Y1, CB_Y2, CB_QC0, CB_QC1, CB_COUNT };
constexpr int CV_SMEM = CV_BAR + 8 * CB_COUNT;

__device__ __forceinline__ uint32_t lds32_nv(uint32_t addr) { uint32_t v; asm("ld.shared.u32 %0, [%1];" : "=r"(v) : "r"(addr)); return v; }
__device__ __forceinline__ void ldsm_x4_nv(uint32_t addr, uint32_t& r0, uint32_t& r1, uint32_t& r2, uint32_t& r3) {
  asm("ldmatrix.sync.aligned.m8n8.x4.shared.b16 {%0,%1,%2,%3}, [%4];" : "=r"(r0), "=r"(r1), "=r"(r2), "=r"(r3) : "r"(addr));
}
__device__ __forceinline__ void stsm_x4_t(uint32_t addr, uint32_t r0, uint32_t r1, uint32_t r2, uint32_t r3) {
  asm volatile("stmatrix.sync.aligned.m8n8.x4.trans.shared.b16 [%0], {%1,%2,%3,%4};" :: "r"(addr), "r"(r0), "r"(r1), "r"(r2), "r"(r3) : "memory");
}
__device__ __forceinline__ void bulk_load(uint32_t dst, const void* src, uint32_t bytes, uint32_t bar) {
  asm volatile("cp.async.bulk.shared::cluster.global.mbarrier::complete_tx::bytes [%0], [%1], %2, [%3];" :: "r"(dst), "l"(src), "r"(bytes), "r"(bar) : "memory");
}
__device__ __forceinline__ void cp_async16(uint32_t dst, const void* src) {
  asm volatile("cp.async.cg.shared.global.L2::256B [%0], [%1], 16;" :: "r"(dst), "l"(src) : "memory");
}
__device__ __forceinline__ void mbar_wait_plain(uint32_t bar, uint32_t parity) {
#pragma unroll 1
  for (int spins = 0; spins < SPIN_LIMIT && !mbar_try(bar, parity); spins++) {}
}

__device__ __forceinline__ void shift_chunk(uint32_t table, int m) {
  const uint32_t src = table + 32 + m * 16;
  uint4 e;
  uint32_t nx;
  asm volatile("ld.shared.v4.u32 {%0,%1,%2,%3}, [%4];" : "=r"(e.x), "=r"(e.y), "=r"(e.z), "=r"(e.w) : "r"(src));
  asm volatile("ld.shared.u32 %0, [%1];" : "=r"(nx) : "r"(src + 16));
  sts128(src + CV_KT_O, make_uint4(__byte_perm(e.x, e.y, 0x5432), __byte_perm(e.y, e.z, 0x5432), __byte_perm(e.z, e.w, 0x5432), __byte_perm(e.w, nx, 0x5432)));
}
__device__ __forceinline__ void kv_block(uint32_t kt, int t0, const uint32_t (&wp)[4], int lane) {
  const int mi = lane >> 3, rev = 7 - (lane & 7);
  uint32_t vv[4], res[4];
  ldsm_x4(kt + CV_V + (t0 >> 9) * (CV_VQ - 8192) + (t0 + 8 * mi + rev) * 16, vv[0], vv[1], vv[2], vv[3]);
#pragma unroll
  for (int i = 0; i < 4; i++) {
    uint32_t k0, k1, k2, k3;
    ldsm_x4(kt + CV_K + (8 + t0 + 8 * i + rev - mi) * 16, k0, k1, k2, k3);
    res[i] = bmul2(badd2(badd2(badd2(bmul2(k3, wp[3]), bmul2(k2, wp[2])), bmul2(k1, wp[1])), bmul2(k0, wp[0])), vv[i]);
  }
  stsm_x4_t(kt + CV_U + (lane & 7) * CV_U_CH + (1 - (mi & 1)) * CV_U_PLANE + (8 + (t0 >> 4) + (mi >> 1)) * 16, res[0], res[1], res[2], res[3]);
}
template <int T0, int NT, int D0, int D1, int J0, int J1>
__device__ __forceinline__ void conv_phase(float (&acc)[16][4], uint32_t abase, uint32_t bbase, uint32_t zero) {
  abase += zero; bbase += zero;
#pragma unroll 1
  for (int dl = 0; dl < 8; dl++) {
    uint32_t bf[NT][2];
#pragma unroll
    for (int j = 0; j < NT; j += 2) ldsm_x4_nv(bbase + (T0 + j) * 128 - dl * 16, bf[j][0], bf[j][1], bf[j + 1][0], bf[j + 1][1]);
    const uint32_t ap = abase + dl * 32;
#pragma unroll
    for (int dh = D0; dh < D1; dh++) {
      const uint32_t a0 = lds32_nv(ap + dh * 256), a1 = lds32_nv(ap + dh * 256 - 16), a2 = lds32_nv(ap + dh * 256 + 16);
      const uint32_t a3 = a0 + zero;
#pragma unroll
      for (int j = 0; j < NT; j++)
        if (dh + T0 + j >= J0 && dh + T0 + j < J1) mma16816(acc[dh + T0 + j], a0, a1, a2, a3, bf[j][0], bf[j][1]);
    }
  }
}
__device__ __forceinline__ uint32_t hidden_zero(uint32_t addr) {
  uint32_t z; asm volatile("ld.volatile.shared.u32 %0, [%1];" : "=r"(z) : "r"(addr) : "memory"); return z;
}
template <int J0, int J1>
__device__ __forceinline__ void stage_y(const float (&acc)[16][4], uint32_t ys, uint32_t bar) {
#pragma unroll
  for (int j = J0; j < J1; j += 2)
    stsm_x4_t(ys + (j >> 2) * CV_VQ + (j & 3) * 128, pack_bf16(acc[j][0], acc[j][1]), pack_bf16(acc[j][2], acc[j][3]),
              pack_bf16(acc[j + 1][0], acc[j + 1][1]), pack_bf16(acc[j + 1][2], acc[j + 1][3]));
  __syncwarp();
  mbar_arrive_if(bar, (threadIdx.x & 31) == 0);
}

#define KV_PROMO CU_TENSOR_MAP_L2_PROMOTION_L2_256B
struct alignas(64) ConvMaps { CUtensorMap k, v, w1, w3; };
#define QROW_AT 2
#define CV_JS 8

__global__ void __launch_bounds__(512, 1)
conv_prep_kernel(const __grid_constant__ ConvMaps cm, const bf16* __restrict__ q, const bf16* __restrict__ shift_k, const bf16* __restrict__ ssm_k,
                 const bf16* __restrict__ ssm_d, const bf16* __restrict__ w2) {
  extern __shared__ __align__(1024) char smem[];
  const int tid = threadIdx.x, lane = tid & 31, warp = __shfl_sync(0xffffffffu, tid >> 5, 0);
  const int b = blockIdx.x, d0 = b * 8;
  const uint32_t kt = smem_u32(smem), ub = kt + CV_U, bar = kt + CV_BAR;
  const int g = lane >> 2, qd = lane & 3;
  if (tid == 0) STAMP(48);
  const uint32_t dpair = __ldg(reinterpret_cast<const uint32_t*>(ssm_d + d0 + 2 * qd));
  if (warp == 14) {
    if (elect_one()) {
#pragma unroll
      for (int x = 0; x < CB_COUNT; x++) mbar_init(bar + 8 * x, x >= CB_QC0 ? 32 : x >= CB_Y0 ? 8 : x >= CB_O1 ? 4 : 1);
      asm volatile("fence.mbarrier_init.release.cluster;" ::: "memory");
    }
    __syncwarp();
    asm volatile("bar.arrive 1, 512;" ::: "memory");
    if (elect_one()) {
      const char* krow = reinterpret_cast<const char*>(ssm_k + (size_t)d0 * SEQ);
#pragma unroll 1
      for (int x = 0; x < 4; x++) {
        if (x < 2) {
          const int bytes = x ? 4096 - CV_KH : CV_KH;
          mbar_expect_tx(bar + 8 * (CB_K0 + x), 8 * bytes);
#pragma unroll 1
          for (int ch = 0; ch < 8; ch++) bulk_load(kt + ch * CV_KT_CH + 32 + x * CV_KH, krow + ch * 4096 + x * CV_KH, bytes, bar + 8 * (CB_K0 + x));
        }
        if (x == QROW_AT) {
          mbar_expect_tx(bar + 8 * CB_X0, 32768);
#pragma unroll 1
          for (int r = 0; r < 16; r++) bulk_load(kt + CV_X + r * CV_XROW, q + (size_t)(b * 16 + r) * DM, 2048, bar + 8 * CB_X0);
        }
        const uint32_t bq = bar + 8 * (CB_Q0 + x);
        mbar_expect_tx(bq, 16384);
#pragma unroll
        for (int y = 0; y < 2; y++) {
          tma_2d(kt + CV_K + 128 + x * 8192 + y * 4096, &cm.k, bq, d0, (2 * x + y) * 256);
          tma_2d(kt + CV_V + x * CV_VQ + y * 4096, &cm.v, bq, d0, (2 * x + y) * 256);
        }
      }
      if (b == 0) {
        *reinterpret_cast<uint4*>(g_role) = make_uint4(0, 0, 0, 0);
        __threadfence();
      }
      asm volatile("griddepcontrol.launch_dependents;" ::: "memory");
#pragma unroll 1
      for (int spins = 0; spins < SPIN_LIMIT && ld_relaxed(&g_qcnt) < 128; spins++) __nanosleep(50);
      __threadfence();
      fence_async_global();
      mbar_expect_tx(bar + 8 * CB_ST, 16384);
      bulk_load(kt + CV_ST, g_qstat, 16384, bar + 8 * CB_ST);
      STAMP(63);
    }
    __syncwarp();
  } else {
    const int tw = 32 * min(warp, 14);
    if (tid < 2) g_flag[(2 * b + tid) * FS] = 0;
    if (tid < 320) reinterpret_cast<uint4*>(&g_part[0][0][0])[b * 320 + tid] = make_uint4(0, 0, 0, 0);
    if (tid < 160) {
      const int x = tid - 128, y = x & 3;
      sts128(tid < 128 ? ub + (tid >> 4) * CV_U_CH + ((tid >> 3) & 1) * CV_U_PLANE + (tid & 7) * 16
                       : y == 3 ? kt + CV_K + (x >> 2) * 16 : kt + (x >> 2) * CV_KT_CH + (y == 2 ? 4128 : y * 16), make_uint4(0, 0, 0, 0));
    }
    uint32_t wp[4];
    {
      const uint4 a = ld_nc_u4(shift_k + (d0 + 2 * qd) * 4);
      wp[0] = __byte_perm(a.x, a.z, 0x5410); wp[1] = __byte_perm(a.x, a.z, 0x7632);
      wp[2] = __byte_perm(a.y, a.w, 0x5410); wp[3] = __byte_perm(a.y, a.w, 0x7632);
    }
    named_bar(1, 512);
#pragma unroll 1
    for (int x = 0; x < 2; x++) {
      mbar_wait_plain(bar + 8 * (CB_K0 + x), 0);
#pragma unroll 1
      for (int idx = x ? tid + 8 * 130 - 256 : tw + lane; idx < (x ? 8 * 258 : 8 * 130); idx += x ? 128 : 480)
        shift_chunk(kt + (idx & 7) * CV_KT_CH, (idx >> 3) - 2);
      __syncwarp();
      mbar_arrive_if(bar + 8 * CB_O1, x && lane == 0);
      if (tid == 0) BSTAMP(54, kt);
#pragma unroll 1
      for (int t0 = x ? tw + 256 : tw; t0 < (x ? SEQ : 32 * warp + 32); t0 += x ? 128 : 32) {
        mbar_wait_plain(bar + 8 * (CB_Q0 + (t0 >> 9)), 0);
        if (tid == 0) BSTAMP(56, kt);
        kv_block(kt, t0, wp, lane);
        __syncwarp();
        mbar_arrive_if(bar + 8 * (CB_U1 + ((t0 >> 9) & 1)), (t0 & 0x580) == 0x580 && lane == 0);
      }
      if (x == 0) named_bar(3, 480);
      if ((warp >> 2) != 2) break;
    }
    if (tid == 256) STAMP(53);
  }

  if (warp < 8) {
    const int o = 2 * qd - g;
    const uint32_t abase = kt + warp * CV_KT_CH + 32 + ((g & 1) ? CV_KT_O + (o - 1) * 2 : o * 2);
    const uint32_t bbase = ub + warp * CV_U_CH + ((lane >> 3) & 1) * CV_U_PLANE + (8 + (lane >> 4) * 8 + (lane & 7)) * 16;
    const uint32_t ys = kt + CV_V + warp * CV_Y_CH + ((lane >> 3) & 1) * 512 + ((lane >> 4) * 8 + (lane & 7)) * 16;
    if (tid == 0) STAMP(49);
    float acc[16][4];
#pragma unroll
    for (int j = 0; j < 16; j++) { acc[j][0] = acc[j][1] = acc[j][2] = acc[j][3] = 0.f; }
    conv_phase<0, 4, 0, 8, 0, 16>(acc, abase, bbase, hidden_zero(ub));
    stage_y<0, 4>(acc, ys, bar + 8 * CB_Y0);
    if (tid == 0) STAMP(57);
    mbar_wait_plain(bar + 8 * CB_K1, 0);
    mbar_wait_plain(bar + 8 * CB_O1, 0);
    conv_phase<0, 4, 8, 16, 0, 16>(acc, abase, bbase, hidden_zero(ub));
    if (tid == 0) STAMP(58);
    if constexpr (CV_JS > 4) {
      mbar_wait_plain(bar + 8 * CB_U1, 0);
      conv_phase<4, CV_JS - 4, 0, CV_JS - 4, 0, CV_JS>(acc, abase, bbase, hidden_zero(ub));
    }
    stage_y<4, CV_JS>(acc, ys, bar + 8 * CB_Y1);
    if (tid == 0) STAMP(59);
    mbar_wait_plain(bar + 8 * CB_U2, 0);
    if (tid == 0) BSTAMP(55, kt);
    conv_phase<4, 12, 0, 12, CV_JS, 16>(acc, abase, bbase, hidden_zero(ub));
    stage_y<CV_JS, 16>(acc, ys, bar + 8 * CB_Y2);
    if (tid == 0) STAMP(50);
  } else if (warp == 15) {
#pragma unroll 1
    for (int x = 0; x < 2; x++) {
      mbar_wait_plain(bar + 8 * (CB_U1 + x), 0);
#pragma unroll 4
      for (int t = 1024 * x + lane; t < 1024 * x + 1024; t += 32) cp_async16(kt + CV_K + 128 + t * 16, q + (size_t)t * DM + d0);
      asm volatile("cp.async.mbarrier.arrive.noinc.shared::cta.b64 [%0];" :: "r"(bar + 8 * (CB_QC0 + x)) : "memory");
    }
  } else if ((warp >> 1) == 6) {
    const int ww = warp - 12, mi = lane >> 3;
    const uint32_t xbuf = kt + CV_X;
    {
      mbar_wait_plain(bar + 8 * CB_X0, 0);
      const uint32_t xa = xbuf + (8 * ww + (lane & 7)) * CV_XROW + (mi & 1) * 1024 + (mi >> 1) * 16;
      float sum[4] = {0.f, 0.f, 0.f, 0.f}, lo[4] = {0.f, 0.f, 0.f, 0.f}, hi[4] = {0.f, 0.f, 0.f, 0.f};
#pragma unroll 4
      for (int x = 0; x < 32; x++) {
        uint32_t a0, a1, a2, a3;
        ldsm_x4(xa + x * 32, a0, a1, a2, a3);
        mma16816(sum, a0, a1, a2, a3, 0x3f803f80u, 0x3f803f80u);
        mma16816(lo, a0, a1, a2, a3, a0, a2);
        mma16816(hi, a0, a1, a2, a3, a1, a3);
      }
      const float mean = (sum[0] + sum[2]) * (1.f / DM), sq = (g & 1) ? lo[1] + hi[3] : lo[0] + hi[2];
      const float rs = rsqrt_fast(fmaxf(fmaf(-mean, mean, sq * (1.f / DM)), 0.f) + LN_EPS);
      if (qd == (g >> 1)) g_qstat[b * 16 + 8 * ww + g] = make_float2(rs, -mean * rs);
      if (tid == 384) STAMP(47);
    }
    const int npieces = b < 112 ? 5 : 1;
    const int xr = (mi >> 1) * 8 + (lane & 7);
    const uint32_t xa = xbuf + xr * 64 + (((ww * 2 + (mi & 1)) ^ ((xr >> 1) & 3)) << 4);
    float cs[4][4] = {};
#pragma unroll 1
    for (int pc = -1; pc < npieces; pc++) {
      named_bar(2, 64);
      if (ww == 0 && pc + 1 < npieces && elect_one()) {
        const uint32_t bx = bar + 8 * (CB_X0 + (pc & 1));
        mbar_expect_tx(bx, 16384);
        tma_2d(xbuf + (pc & 1) * 16384, pc < 0 ? &cm.w1 : &cm.w3, bx, 32 * (pc < 0 ? b >> 2 : b), 256 * (pc < 0 ? b & 3 : pc));
      }
      if (pc < 0) {
        if (tid == 416) asm volatile("red.release.gpu.global.add.u32 [%0], 1;" :: "l"(&g_qcnt) : "memory");
        continue;
      }
      mbar_wait_plain(bar + 8 * (CB_X0 + ((pc + 1) & 1)), ((pc + 1) >> 1) & 1);
#pragma unroll
      for (int r = 0; r < 16; r++) {
        uint32_t a0, a1, a2, a3;
        ldsm_x4_t(xa + ((pc + 1) & 1) * 16384 + r * 1024, a0, a1, a2, a3);
        mma16816(cs[r & 3], a0, a1, a2, a3, 0x3f803f80u, 0x3f803f80u);
      }
      if (pc == 0 || pc == 4) {
        const float lo = (cs[0][0] + cs[1][0]) + (cs[2][0] + cs[3][0]), hi = (cs[0][2] + cs[1][2]) + (cs[2][2] + cs[3][2]);
        if (qd < 2) (pc ? g_cs3 + 32 * b : g_cs1[b & 3] + 32 * (b >> 2))[16 * ww + 8 * qd + g] = qd ? hi : lo;
#pragma unroll
        for (int r = 0; r < 4; r++) cs[r][0] = cs[r][2] = 0.f;
      }
    }
    if (tid == 384) {
      STAMP(52);
      prefetch_l2(reinterpret_cast<const char*>(w2) + (size_t)b * (DM * DM / 64), DM * DM / 64);
    }
  }
  {
    const int mi = lane >> 3, ch = lane & 7;
    const uint32_t ya = kt + CV_V + ch * CV_Y_CH + (mi & 1) * 512 + (mi >> 1) * 16;
    const uint32_t ua = ub + ch * CV_U_CH + (mi & 1) * CV_U_PLANE + (8 + (mi >> 1)) * 16;
    const uint32_t qa = kt + CV_K + 128 + (16 * (mi >> 1) + 15 - 8 * (mi & 1) - ch) * 16;
    const uint32_t sa = kt + CV_ST + (15 - g) * 8;
    char* xo = reinterpret_cast<char*>(g_x3[0]) + (size_t)b * CB_BYTES + (15 - g) * 16 + qd * 4;
    char* yo = reinterpret_cast<char*>(g_y) + (size_t)b * CB_BYTES + ((7 - g) * 4 + qd) * 8;
    mbar_wait_plain(bar + 8 * CB_ST, 0);
    mbar_wait_plain(bar + 8 * CB_QC0, 0);
#pragma unroll 1
    for (int part = warp < 8 ? 2 : warp < 12 ? 0 : 1; part < 3; part++) {
      if (part > (CV_JS <= 8)) mbar_wait_plain(bar + 8 * CB_QC1, 0);
      mbar_wait_plain(bar + 8 * (CB_Y0 + part), 0);
      if (tid == 0) BSTAMP(60, kt);
#pragma unroll 1
      for (int u = part == 0 ? warp - 8 : part == 1 ? warp + 8 : warp + 4 * CV_JS; u < (part == 0 ? 16 : part == 1 ? 4 * CV_JS : 64); u += 4 << part) {
        uint32_t y[4], uu[4], qq[4];
        ldsm_x4_t(ya + (u >> 4) * CV_VQ + (u & 15) * 32, y[0], y[1], y[2], y[3]);
        ldsm_x4_t(ua + u * 32, uu[0], uu[1], uu[2], uu[3]);
        ldsm_x4(qa + u * 512, qq[0], qq[1], qq[2], qq[3]);
#pragma unroll
        for (int i = 0; i < 4; i++) {
          const int off = 16 * (i >> 1) - 8 * (i & 1);
          const float2 s = lds_f2(sa + u * 256 + off * 8);
          y[i] = badd2(y[i], bmul2(uu[i], dpair));
          stg32(xo + u * 512 + off * 16, gate_pair(qq[i], y[i], s.x, s.y));
        }
        asm volatile("st.global.v2.u32 [%0], {%1,%2};" :: "l"(yo + u * 512), "r"(y[1]), "r"(y[0]) : "memory");
        asm volatile("st.global.v2.u32 [%0], {%1,%2};" :: "l"(yo + u * 512 + 256), "r"(y[3]), "r"(y[2]) : "memory");
      }
    }
  }
  if (tid == 0) STAMP(51);
}

enum { M_X3A, M_X3S, M_X3B, M_H, M_HS, M_X1, M_HID, M_W1, M_W2, M_W3A, M_W3B, M_W4, M_OUT, M_Y, M_COUNT };
struct alignas(64) Maps { CUtensorMap m[M_COUNT]; };

constexpr int NA = 5, A_SLOT = 68 * 128;
constexpr int SM_A = 0;
constexpr int SM_B = 2 * NA * A_SLOT;
constexpr int SM_X = SM_B + 98304;
constexpr int SM_CS1 = SM_X + 32768;
constexpr int SM_CS3 = SM_CS1 + 512;
constexpr int SM_ZERO = SM_CS3 + 1792;
constexpr int SM_ROLE = SM_ZERO + 4;
constexpr int SM_BAR = SM_ZERO + 8;
constexpr int BAR_FULLA = 0, BAR_FULLB = 16, BAR_TURN = 24, BAR_OWN = 26;
constexpr int BAR_EMPTYA = 28, BAR_EMPTYB = BAR_EMPTYA + 18, BAR_CS = BAR_EMPTYB + 9;
constexpr int BAR_PUB = 56;
constexpr int BAR_END = 84;
constexpr int MEGA_SMEM = SM_BAR + BAR_END * 8;
static_assert(MEGA_SMEM <= 232448, "shared memory");
#define LEAD16 5
#define LEAD32 2
#define TURN_EARLY 1

template <int N> struct BGeo;
template <> struct BGeo<128> { static constexpr int SLOTS = 6, BYTES = 16384, LEAD = LEAD16; };
template <> struct BGeo<256> { static constexpr int SLOTS = 3, BYTES = 32768, LEAD = LEAD32; };
template <> struct BGeo<192> { static constexpr int SLOTS = 4, BYTES = 24576; };
__host__ __device__ constexpr int first_slot(int s) { return s == 0 || s == 2 ? 2 : 0; }
__device__ __forceinline__ bool starts_local(int l, int s) { return s == 2 || s == 1 - l; }
__device__ __forceinline__ int token_shift(int j) { return ((j >> 1) & 1 ? 1 : -1) * (1 + (j >> 2)); }

__device__ __forceinline__ void k_order(bool local, int n, int j, int& js, int& p) {
  if (!local) { p = n >> 3; js = ((j & 6) + n) & 7; }
  else if (n < 4) { p = n & 1; js = j ^ (n >> 1); }
  else { const int m = n - 4; p = m >= 6; js = ((j & 6) + 2 + (m >= 6 ? m - 6 : m)) & 7; }
}

struct Ctx {
  uint32_t sm;
  uint32_t bar;
  int i, j, r;
  int bid;
};

struct Pipe {
  uint32_t ko, kp;
  uint32_t po;
  uint32_t a0, a1, ar;
  uint32_t b;
  uint32_t keep;
  uint32_t sh, wide;
  uint32_t turn;
  int budget;
  uint32_t rel;
  bool signals;
  __device__ __forceinline__ void release() const {
    asm volatile("{\n.reg .pred p;\nsetp.ne.b32 p, %1, 0;\n@p mbarrier.arrive.shared::cluster.b64 _, [%0];\n}" :: "r"(rel + po), "r"((uint32_t)signals) : "memory");
  }
  __device__ __forceinline__ void drain() { wg_wait<0>(); release(); po = 64; }
};
__device__ __forceinline__ uint32_t desc_a(const Ctx& c, int off) { return ((c.sm & 0x3FFFFu) >> 4) + 0x400000u + (off >> 4); }
__device__ __forceinline__ uint32_t desc_b(const Ctx& c, int off) { return ((c.sm & 0x3FFFFu) >> 4) + 0x2000000u + ((SM_B + off) >> 4); }

template <int N, bool PRED, bool SHIFT = false, class Extra>
__device__ __forceinline__ void gemm_step(float (&acc)[N / 2], const Ctx& c, int wg, Pipe& p, Extra&& extra) {
  using G = BGeo<N>;
  const uint32_t fa = c.bar + 8 * BAR_FULLA + 64 * wg + p.ko, fb = c.bar + 8 * BAR_FULLB + p.ko;
#pragma unroll 1
  while (true) {
    uint32_t ready;
    asm volatile("{\n.reg .pred p, q;\nmbarrier.try_wait.parity.shared::cta.b64 p, [%1], %3;\nmbarrier.try_wait.parity.shared::cta.b64 q, [%2], %3;\n"
                 "and.pred p, p, q;\nselp.b32 %0, 1, 0, p;\n}" : "=r"(ready) : "r"(fa), "r"(fb), "r"(p.kp) : "memory");
    if (ready || --p.budget <= 0) break;
  }
  wg_fence();
  const uint32_t a = SHIFT ? p.a0 + (p.sh & 3) + (p.wide << 16) : p.a0, ak = SHIFT ? 128 + 2 * p.wide : 128;
  if constexpr (SHIFT) p.sh >>= 2;
  if constexpr (PRED) { Mma<N>::ss(acc, a, p.b, p.keep); p.keep = 1; } else Mma<N>::ss(acc, a, p.b);
#pragma unroll
  for (int kk = 1; kk < 4; kk++) Mma<N>::ss(acc, a + kk * ak, p.b + kk * 128);
  wg_commit();
  extra();
  wg_wait<1>();
  p.release();
  p.po = p.ko;
  p.ko = (p.ko + 8) & 63;
  p.kp ^= p.ko == 0;
  p.a0 = p.a1; p.a1 = p.ar;
  p.ar = p.ar == desc_a(c, SM_A + (NA - 1) * A_SLOT) + wg * NA * (A_SLOT >> 4) ? p.ar - (NA - 1) * (A_SLOT >> 4) : p.ar + (A_SLOT >> 4);
  p.b = p.b == desc_b(c, (G::SLOTS - 1) * G::BYTES) ? desc_b(c, 0) : p.b + (G::BYTES >> 4);
}
template <int N>
__device__ __forceinline__ void gemm_begin(const Ctx& c, int wg, int wq, Pipe& p, int s, bool local) {
  if (local) {
    fence_async_smem();
    named_bar(2 + wg, 128);
    mbar_arrive_if(c.bar + 8 * BAR_FULLA + 64 * wg + 8 * (threadIdx.x & 1), (threadIdx.x & 126) == 96);
    if (wq < 2) {
      mbar_wait(c.bar + 8 * (BAR_EMPTYA + 9 * wg + 8 - NA + wq), p.kp ^ 1, p.budget);
      if (elect_one()) {
        const uint32_t peer = mapa(c.sm, c.r ^ 1), bar = peer + SM_BAR + 8 * (BAR_FULLA + 8 * wg + 2 + wq);
        mbar_expect_tx_cluster(bar, 8192);
        bulk_copy_cluster(peer + (((wq ? p.a1 : p.a0) - desc_a(c, 0)) << 4), c.sm + SM_X + (2 * wg + wq) * 8192, 8192, bar);
      }
      __syncwarp();
    }
  }
  asm volatile("{\n.reg .pred p;\nsetp.ne.b32 p, %3, 0;\nselp.b32 %2, %0, %2, p;\nselp.b32 %0, %4, %0, p;\nselp.b32 %1, %5, %1, p;\n}"
               : "+r"(p.a0), "+r"(p.a1), "+r"(p.ar) : "r"((uint32_t)local), "r"(desc_a(c, SM_X) + wg * 1024), "r"(desc_a(c, SM_X + 8192) + wg * 1024));
  p.b = desc_b(c, first_slot(s) * BGeo<N>::BYTES);
  p.keep = 0;
}
template <class Hook>
__device__ __forceinline__ void yield_turn(const Ctx& c, int wg, Pipe& p, Hook&& hook) {
  if (wg == 1) p.drain();
  hook();
  if (wg == 1) mbar_wait(c.bar + 8 * BAR_TURN, p.turn, p.budget);
  p.turn ^= 1;
}
__device__ __forceinline__ void pass_turn(const Ctx& c, bool now) { mbar_arrive_if(c.bar + 8 * BAR_TURN, now && threadIdx.x == 96); }
struct Nop { __device__ __forceinline__ void operator()() const {} };
template <int N, bool PRED, bool SHIFT = false, class Hook, class Tail>
__device__ __forceinline__ void gemm_steps(float (&acc)[N / 2], const Ctx& c, int wg, Pipe& p, int count, Hook&& hook, Tail&& tail) {
  constexpr int LEAD = BGeo<N>::LEAD, LAST = LEAD > TURN_EARLY ? TURN_EARLY : LEAD - 1;
#pragma unroll 1
  for (int n = count - LEAD; n > 0; n--) gemm_step<N, PRED, SHIFT>(acc, c, wg, p, Nop());
  yield_turn(c, wg, p, hook);
#pragma unroll 1
  for (int n = LEAD - 1; n >= 0; n--) {
    gemm_step<N, false, SHIFT>(acc, c, wg, p, Nop());
    pass_turn(c, n == LAST);
  }
  tail();
  p.drain();
}

__device__ __forceinline__ void put_stat(float2* gdst, float s, float q, bool cond) {
  const float m = s * (1.f / 128), v = fmaxf(fmaf(-m, s, q), 0.f);
  asm volatile("{\n.reg .pred p;\nsetp.ne.b32 p, %3, 0;\n@p st.relaxed.gpu.global.v2.b32 [%0], {%1,%2};\n}"
               :: "l"(gdst), "r"(__float_as_uint(m)), "r"(__float_as_uint(v) | 1u), "r"((uint32_t)cond) : "memory");
}
__device__ __forceinline__ void put_partial(const float (&v)[64], float2* gdst, float z) {
  float s[4] = {z, z, z, z}, q[4] = {z, z, z, z};
#pragma unroll
  for (int x = 0; x < 64; x++) { s[x & 3] += v[x]; q[x & 3] = fmaf(v[x], v[x], q[x & 3]); }
  const bool odd = threadIdx.x & 1;
  const float s0 = s[0] + s[1], s1 = s[2] + s[3], q0 = q[0] + q[1], q1 = q[2] + q[3];
  float ss = (odd ? s1 : s0) + __shfl_xor_sync(0xffffffffu, odd ? s0 : s1, 1);
  float qq = (odd ? q1 : q0) + __shfl_xor_sync(0xffffffffu, odd ? q0 : q1, 1);
  ss += __shfl_xor_sync(0xffffffffu, ss, 2);
  qq += __shfl_xor_sync(0xffffffffu, qq, 2);
  put_stat(gdst + (odd ? 8 : 0), ss, qq, !(threadIdx.x & 2));
}
struct RowStats {
  float2 p[4];
  __device__ __forceinline__ void load(const float2* r0, const float2* r1) {
#pragma unroll
    for (int x = 0; x < 4; x++)
      asm volatile("ld.relaxed.gpu.global.v2.f32 {%0,%1}, [%2];" : "=f"(p[x].x), "=f"(p[x].y) : "l"((x & 2 ? r1 : r0) + (x & 1) * SEQ) : "memory");
  }
  __device__ __forceinline__ void finish(const float2* r0, const float2* r1, int& budget, float2& s0, float2& s1) {
#pragma unroll 1
    while (!__all_sync(0xffffffffu, __float_as_uint(p[0].y) & __float_as_uint(p[1].y) & __float_as_uint(p[2].y) & __float_as_uint(p[3].y) & 1)) {
      if (--budget <= 0) break;
      load(r0, r1);
    }
#pragma unroll
    for (int h = 0; h < 2; h++) {
      const float2 a = p[2 * h], b = p[2 * h + 1];
      float m = a.x + b.x;
      m += __shfl_xor_sync(0xffffffffu, m, 1);
      m += __shfl_xor_sync(0xffffffffu, m, 2);
      m *= 0.125f;
      const float ea = a.x - m, eb = b.x - m;
      float t = fmaf(fmaf(ea, ea, eb * eb), 128.f, a.y + b.y);
      t += __shfl_xor_sync(0xffffffffu, t, 1);
      t += __shfl_xor_sync(0xffffffffu, t, 2);
      (h ? s1 : s0) = make_float2(m, rsqrt_fast(fmaf(t, 1.f / DM, LN_EPS)));
    }
  }
};

__device__ __forceinline__ void emit_panel(const uint32_t* v, char* gp, uint32_t pub) {
#pragma unroll
  for (int t = 0; t < 8; t++) { stg32(gp + t * CB_BYTES, v[2 * t]); stg32(gp + t * CB_BYTES + 128, v[2 * t + 1]); }
  __syncwarp();
  mbar_arrive_if(pub, (threadIdx.x & 31) == 0);
}
template <int NT>
__device__ __forceinline__ void stage_tiles(const uint32_t* v, uint32_t sp) {
#pragma unroll
  for (int t = 0; t < NT; t += 2) stsm_x4(sp + t * 1024, v[2 * t], v[2 * t + 1], v[2 * t + 2], v[2 * t + 3]);
}

__device__ __forceinline__ float late_zero(uint32_t addr) {
  float z; asm volatile("ld.volatile.shared.f32 %0, [%1];" : "=f"(z) : "r"(addr) : "memory"); return z;
}

template <int NT, bool GELU>
__device__ __forceinline__ void fold_tiles(uint32_t* v, const float* acc, const float2* cs_ptr, float2 st0, float2 st1) {
  const float n0 = -st0.x * st0.y, n1 = -st1.x * st1.y;
#pragma unroll
  for (int tile = 0; tile < NT; tile++) {
    const float2 cs = cs_ptr[tile * 4];
    float a = fmaf(acc[4 * tile + 0], st0.y, n0 * cs.x), b = fmaf(acc[4 * tile + 1], st0.y, n0 * cs.y);
    float cc = fmaf(acc[4 * tile + 2], st1.y, n1 * cs.x), d = fmaf(acc[4 * tile + 3], st1.y, n1 * cs.y);
    if (GELU) { a = gelu_from_half(a); b = gelu_from_half(b); cc = gelu_from_half(cc); d = gelu_from_half(d); }
    v[2 * tile] = GELU ? pack_bf16(a, b) : pack_f16(a, b);
    v[2 * tile + 1] = GELU ? pack_bf16(cc, d) : pack_f16(cc, d);
  }
}

__device__ __forceinline__ void move_reg(uint32_t& d, uint32_t s) { asm volatile("mov.b32 %0, %1;" : "=r"(d) : "r"(s)); }
__device__ __forceinline__ void move_reg(float& d, float s) { asm volatile("mov.f32 %0, %1;" : "=f"(d) : "f"(s)); }
template <int CH, int LO, int HI, class T, int NR>
__device__ __forceinline__ void pick_group(T (&held)[NR], int idx) {
  if constexpr (HI - LO == 1) {
#pragma unroll
    for (int x = 0; x < CH; x++) move_reg(held[x], held[CH * LO + x]);
  } else {
    constexpr int MID = (LO + HI) / 2;
    if (idx < MID) pick_group<CH, LO, MID>(held, idx); else pick_group<CH, MID, HI>(held, idx);
  }
}
template <int CH>
__device__ __forceinline__ void gelu_chunk(const uint32_t* t, char* gp) {
#pragma unroll
  for (int x = 0; x < CH; x++) stg32(gp + (x >> 1) * CB_BYTES + (x & 1) * 128, gelu_pair_f16(t[x]));
}

__device__ __forceinline__ void wait_flags(const uint32_t* lane_flag, uint32_t& seen, uint32_t need, uint32_t mask, int& budget) {
  if ((__ballot_sync(0xffffffffu, seen >= need) & mask) == mask) return;
#pragma unroll 1
  while (true) {
    if (lane_flag) seen = ld_relaxed(lane_flag);
    if ((__ballot_sync(0xffffffffu, seen >= need) & mask) == mask) break;
    if (--budget <= 0) break;
  }
  fence_async_global();
}

__device__ __forceinline__ uint32_t pick_role() {
  uint32_t smid;
  asm volatile("mov.u32 %0, %%smid;" : "=r"(smid));
  const uint32_t t = smid >> 1;
  const uint32_t gpc = t < 32 ? t & 7 : t < 60 ? 1 + (t - 32) % 7 : t < 62 ? t - 54 : 0;
  uint32_t p = gpc & 3;
  uint4 cnt;
  asm volatile("ld.relaxed.gpu.global.v4.u32 {%0,%1,%2,%3}, [%4];" : "=r"(cnt.x), "=r"(cnt.y), "=r"(cnt.z), "=r"(cnt.w) : "l"(g_role) : "memory");
  uint32_t tried = 0;
#pragma unroll 1
  for (int k = 0; k < 4; k++) {
    const uint32_t ticket = atomicAdd(&g_role[p], 1u);
    if (ticket < 16) return ticket * 4 + p;
    tried |= 1u << p;
    const uint32_t c4[4] = {cnt.x, cnt.y, cnt.z, cnt.w};
    uint32_t best = 0xffffffffu;
#pragma unroll
    for (uint32_t x = 0; x < 4; x++)
      if (!((tried >> x) & 1) && c4[x] < best) { best = c4[x]; p = x; }
  }
  return 0;
}

#define REG_CONS 224
#define REG_PROD 56
__global__ void __cluster_dims__(2, 1, 1) __launch_bounds__(384, 1)
mega_kernel(const __grid_constant__ Maps maps) {
  extern __shared__ __align__(1024) char smem[];
  const int tid = threadIdx.x, lane = tid & 31;
  const int warp = __shfl_sync(0xffffffffu, tid >> 5, 0), wg = warp >> 2;
  if (elect_one()) {
    const uint32_t sm0 = smem_u32(smem);
#pragma unroll
    for (int x = 0; x < 7; x++) mbar_init(sm0 + SM_BAR + 56 * warp + 8 * x, 1 << wg);
    asm volatile("fence.mbarrier_init.release.cluster;" ::: "memory");
    asm volatile("prefetch.tensormap [%0];" :: "l"(&maps.m[warp]) : "memory");
    if (warp < 2) asm volatile("prefetch.tensormap [%0];" :: "l"(&maps.m[M_OUT + warp]) : "memory");
    if (warp == 11) {
      sts32(sm0 + SM_ZERO, 0);
      if ((blockIdx.x & 1) == 0) {
        sts32(sm0 + SM_ROLE, pick_role());
        asm volatile("fence.release.sync_restrict::shared::cta.cluster;" ::: "memory");
      }
    }
  }
  static_assert(M_OUT == 12, "start-up work of 12 warps");
  __syncthreads();
  asm volatile("barrier.cluster.arrive.relaxed.aligned;\nbarrier.cluster.wait.acquire.aligned;" ::: "memory");
  Ctx c;
  c.sm = opaque(smem_u32(smem));
  c.bar = c.sm + SM_BAR;
  c.r = blockIdx.x & 1;
  {
    uint32_t role;
    asm volatile("ld.shared::cluster.u32 %0, [%1];" : "=r"(role) : "r"(mapa(smem_u32(smem) + SM_ROLE, 0)) : "memory");
    role = __shfl_sync(0xffffffffu, role, 0);
    c.i = role >> 2; c.j = (role & 3) * 2 + c.r;
    c.bid = c.i * 8 + c.j;
  }

  if (wg == 2) {
    reg_dealloc<REG_PROD>();
    int budget = SPIN_LIMIT;
    if (warp == 8) {
      int as = 0, k0 = 0;
      const int hh = 16 * c.r + c.i;
      const uint32_t full0 = c.bar + 8 * (BAR_FULLA + c.r * 8), empty0 = c.bar + 8 * (BAR_EMPTYA + c.r * 9), full_peer = mapa(full0, c.r ^ 1);
      const uint32_t* lf = nullptr;
      {
        const int js = lane & 7, nb = lane < 8 ? hh : token_shift(js) > 0 ? hh + 1 : hh - 1;
        if (lane < 16 && nb >= 0 && nb < 32) lf = g_flag + (nb * 8 + js) * FS;
      }
      uint32_t seen = lf ? 0 : 0xffffffffu;
      asm volatile("griddepcontrol.wait;" ::: "memory");
      if (lane == 0) MSTAMP(46);
#pragma unroll 1
      for (int ph = 0; ph < 10; ph++) {
        const int l = ph >= 5, s = ph - 5 * l;
        const CUtensorMap* m = &maps.m[s == 0 ? M_X3S + l : s == 1 ? M_H + l : s == 4 ? M_HID : M_X1];
        const uint32_t bytes = s == l ? A_SLOT : 8192;
        const int np = s == 4 ? 7 : 2;
        const int pc0 = 13 * l + (s == 0 ? 0 : s == 1 ? 2 : s == 4 ? 6 : 4);
        const bool local = starts_local(l, s);
        if (local) as = as + 2 >= NA ? as + 2 - NA : as + 2;
#pragma unroll 1
        for (int n = local ? 4 : 0; n < 8 * np; n++) {
          int p, js;
          k_order(local, n, c.j, js, p);
          if (ph != 0) wait_flags(ph == 6 || lane < 8 ? lf : nullptr, seen, pc0 + p + 1, (ph == 6 ? 0x101u : 1u) << js, budget);
          const int row = 64 * hh - (s == l && token_shift(l ? js : c.j) < 0 ? 4 : 0);
          const int last = k0 + n - (local && n < NA + 2 ? NA + 2 : NA);
          mbar_wait(empty0 + 8 * (last & 7), (last >> 3) & 1, budget);
          if (elect_one()) {
            mbar_expect_tx(full0 + 8 * (n & 7), bytes);
            mbar_expect_tx_cluster(full_peer + 8 * (n & 7), bytes);
            tma_2d_mc(c.sm + SM_A + (c.r * NA + as) * A_SLOT, m, full0 + 8 * (n & 7), 2 * row, (np * js + p) * 8, (uint16_t)3);
          }
          __syncwarp();
          if (++as == NA) as = 0;
        }
        k0 += 8 * np;
      }
    } else if (warp == 9) {
      int k0 = 0;
#pragma unroll 1
      for (int ph = 0; ph < 10; ph++) {
        const int l = ph >= 5, s = ph - 5 * l;
        const int kbytes = s == 2 ? 32 : s == 3 ? 24 : 16, slots = s == 2 ? 3 : s == 3 ? 4 : 6;
        const uint32_t dist0 = s == 2 ? 0x345u : s == 3 ? 0x4333u : s == 4 ? 0x655544u : 0x666666u;
        const CUtensorMap* m = &maps.m[M_W1 + s];
        const int np = s == 4 ? 7 : 2;
        const int panel0 = s == 2 ? 7 * c.j : s == 3 ? 7 * c.j + 4 : 2 * c.j;
        const bool local = starts_local(l, s);
        int slot = first_slot(s);
#pragma unroll 1
        for (int n = 0; n < 8 * np; n++) {
          int p, js;
          k_order(local, n, c.j, js, p);
          const int last = k0 + n - (n < slots ? (int)((dist0 >> (4 * n)) & 15) : slots);
          mbar_wait(c.bar + 8 * (BAR_EMPTYB + (last & 7)), (last >> 3) & 1, budget);
          if (elect_one()) {
            const uint32_t bar = c.bar + 8 * (BAR_FULLB + (n & 7));
            mbar_expect_tx(bar, kbytes * 1024);
            tma_3d(c.sm + SM_B + slot * kbytes * 1024, m, bar, 0, (np * js + p) * 64, panel0);
          }
          __syncwarp();
          if (++slot == slots) slot = 0;
        }
        k0 += 8 * np;
      }
    } else {
      const int w = warp - 10;
      const int row0 = 64 * (16 * w + c.i);
      asm volatile("griddepcontrol.wait;" ::: "memory");
      auto load_own = [&](int map) {
        if (elect_one()) {
          const uint32_t bar = c.bar + 8 * (BAR_OWN + w);
          mbar_expect_tx(bar, 16384);
          tma_2d(c.sm + SM_X + w * 16384, &maps.m[map], bar, 2 * row0, 16 * c.j);
          tma_2d(c.sm + SM_X + w * 16384 + 8192, &maps.m[map], bar, 2 * row0, 16 * c.j + 8);
        }
      };
      load_own(M_X3A);
      if (w == 0) {
        float4 s = make_float4(0.f, 0.f, 0.f, 0.f);
#pragma unroll
        for (int x = 0; x < 4; x++) {
          const float4 v = __ldcg(reinterpret_cast<const float4*>(&g_cs1[x][c.j * 128]) + lane);
          s.x += v.x; s.y += v.y; s.z += v.z; s.w += v.w;
        }
        reinterpret_cast<float4*>(smem + SM_CS1)[lane] = s;
      } else {
#pragma unroll
        for (int x = 0; x < 4; x++)
          if (lane < 28) reinterpret_cast<float4*>(smem + SM_CS3)[28 * x + lane] = __ldcg(reinterpret_cast<const float4*>(g_cs3 + c.j * 448) + 28 * x + lane);
      }
      mbar_wait(c.bar + 8 * (BAR_OWN + w), 0, budget);
#pragma unroll 1
      for (int h = 0; h < 2; h++) {
        float s0 = 0.f, s1 = 0.f, q0 = 0.f, q1 = 0.f;
#pragma unroll 2
        for (int x = 0; x < 16; x++) {
          uint32_t v[4];
          asm volatile("ld.shared.v4.u32 {%0,%1,%2,%3}, [%4];" : "=r"(v[0]), "=r"(v[1]), "=r"(v[2]), "=r"(v[3])
                       : "r"(c.sm + SM_X + w * 16384 + x * 1024 + (32 * h + lane) * 16) : "memory");
#pragma unroll
          for (int y = 0; y < 4; y++) {
            const float a = bf_lo(v[y]), b = bf_hi(v[y]);
            s0 += a; s1 += b; q0 = fmaf(a, a, q0); q1 = fmaf(b, b, q1);
          }
        }
        put_stat(&g_part[0][c.j][row0 + 32 * h + lane], s0 + s1, q0 + q1, true);
      }
      __syncwarp();
      if (lane == 0) {
        mbar_arrive(c.bar + 8 * BAR_CS);
        if (c.bid == 0 && w == 0) g_qcnt = 0;
      }
      uint32_t* my_flag = g_flag + ((16 * w + c.i) * 8 + c.j) * FS;
#pragma unroll 1
      for (int pc = 2; pc < 26; pc++) {
        const int l = pc >= 13, u = pc - 13 * l;
        mbar_wait(c.bar + 8 * (BAR_PUB + 13 * w + u), u < 2 ? 0 : l, budget);
        if (lane == 0) st_release(my_flag, pc + 1);
        if (pc == 11) load_own(M_Y);
      }
    }
    cluster_exit_barrier();
  } else {
    reg_alloc<REG_CONS>();
#define WSTAMP(idx) do {} while (0)
    const int t = tid & 127, g = lane >> 2, qd = lane & 3;
    const int wrow = 64 * (16 * wg + c.i) + (t >> 5) * 16, row = wrow + g;
    const uint32_t frag = row * 16 + qd * 4 + c.j * 16 * CB_BYTES;
    const uint32_t stage = c.sm + SM_X + wg * 16384 + (lane >> 4) * 1024 + ((t >> 5) * 16 + (lane & 15)) * 16;
    const uint32_t pub = c.bar + 8 * (BAR_PUB + 13 * wg);
    Pipe p;
    p.ko = 0; p.kp = 0; p.po = 64; p.turn = 0; p.budget = SPIN_LIMIT;
    p.a0 = desc_a(c, SM_A) + wg * NA * (A_SLOT >> 4); p.a1 = p.a0 + (A_SLOT >> 4); p.ar = p.a1 + (A_SLOT >> 4);
    p.signals = t == 0 || t == 32 || t == 64;
    p.rel = mapa(c.bar + 8 * (t == 64 ? BAR_EMPTYB : BAR_EMPTYA + wg * 9), t == 32 ? c.r ^ 1 : c.r);
    auto fence_sched = [&]() { mbar_wait(c.bar + 8 * BAR_CS, 0, p.budget); };
    uint32_t x3[32];
    float acc[64];
#pragma unroll
    for (int x = 0; x < 32; x++) x3[x] = 0;
#pragma unroll
    for (int x = 0; x < 64; x++) acc[x] = 0.f;
    WSTAMP(0);
#pragma unroll 1
    for (int l = 0; l < 2; l++) {
      WSTAMP(1 + 16 * l);
      RowStats rs;
      {
        const int ra = row + (l == 0 ? token_shift(c.j) : 0), rb = ra + 8;
        const float2* sp = &g_part[3 * l][2 * qd][0];
        RowStats ro;
        gemm_begin<128>(c, wg, warp & 3, p, 0, l == 1);
        p.sh = l == 0 ? (token_shift(c.j) & 3) * 0x55555555u : 0;
        p.wide = l == 0 ? 4 : 0;
        float2 s0, s1;
        gemm_steps<128, true, true>(acc, c, wg, p, 16, [&]() {
          rs.load(sp + max(ra, 0), sp + min(rb, SEQ - 1));
          ro.load(sp + row, sp + row + 8);
        }, [&]() {
          rs.finish(sp + max(ra, 0), sp + min(rb, SEQ - 1), p.budget, s0, s1);
          s0.y *= (ra < 0 ? 0.f : 0.5f) * rsqrt_fast(fmaxf(fmaf(-LN_EPS * s0.y, s0.y, 1.f), 0.f) + LN_EPS);
          s1.y *= (rb >= SEQ ? 0.f : 0.5f) * rsqrt_fast(fmaxf(fmaf(-LN_EPS * s1.y, s1.y, 1.f), 0.f) + LN_EPS);
          asm volatile("" : "+f"(s0.x), "+f"(s0.y), "+f"(s1.x), "+f"(s1.y));
          fence_sched();
          if (l == 0) {
            mbar_wait(c.bar + 8 * (BAR_OWN + wg), 0, p.budget);
#pragma unroll
            for (int x = 0; x < 32; x += 4) ldsm_x4(stage + x * 512, x3[x], x3[x + 1], x3[x + 2], x3[x + 3]);
          }
        });
        WSTAMP(2 + 16 * l);
#pragma unroll
        for (int pn = 0; pn < 2; pn++) {
          uint32_t v[16];
          if (pn == 0) {
            fold_tiles<4, true>(v, acc, reinterpret_cast<const float2*>(smem + SM_CS1) + qd, s0, s1);
#pragma unroll
            for (int x = 0; x < 8; x++) stg32(reinterpret_cast<char*>(g_h) + frag + (x >> 1) * CB_BYTES + (x & 1) * 128, v[x]);
            fence_sched();
            fold_tiles<4, true>(v + 8, acc + 16, reinterpret_cast<const float2*>(smem + SM_CS1) + qd + 16, s0, s1);
#pragma unroll
            for (int x = 8; x < 16; x++) stg32(reinterpret_cast<char*>(g_h) + frag + (x >> 1) * CB_BYTES + (x & 1) * 128, v[x]);
            __syncwarp();
            mbar_arrive_if(pub + 8 * 2, lane == 0);
          } else {
            fold_tiles<8, true>(v, acc + 32, reinterpret_cast<const float2*>(smem + SM_CS1) + qd + 32, s0, s1);
            emit_panel(v, reinterpret_cast<char*>(g_h) + frag + 8 * CB_BYTES, pub + 8 * 3);
          }
          if (l == 0) stage_tiles<8>(v, stage + pn * 8192);
        }
        ro.finish(sp + row, sp + row + 8, p.budget, s0, s1);
        const float nb0 = -s0.x * s0.y, nb1 = -s1.x * s1.y;
#pragma unroll
        for (int x = 0; x < 32; x++) {
          acc[2 * x] = fmaf(bf_lo(x3[x]), (x & 1) ? s1.y : s0.y, (x & 1) ? nb1 : nb0);
          acc[2 * x + 1] = fmaf(bf_hi(x3[x]), (x & 1) ? s1.y : s0.y, (x & 1) ? nb1 : nb0);
        }
        WSTAMP(3 + 16 * l);
      }
      {
        gemm_begin<128>(c, wg, warp & 3, p, 1, l == 0);
        p.sh = l == 1 ? __funnelshift_r(0xaa5faa5fu, 0xaa5faa5fu, 2 * (c.j & 6)) : 0;
        p.wide = l == 1 ? 4 : 0;
        gemm_steps<128, false, true>(acc, c, wg, p, 16, Nop(), Nop());
        WSTAMP(4 + 16 * l);
        uint32_t v[32];
#pragma unroll
        for (int x = 0; x < 32; x++) v[x] = pack_bf16(acc[2 * x], acc[2 * x + 1]);
        emit_panel(v, reinterpret_cast<char*>(g_x1) + frag, pub + 8 * 4);
        stage_tiles<16>(v, stage);
        put_partial(acc, &g_part[3 * l + 1][c.j][row], late_zero(c.sm + SM_ZERO));
        emit_panel(v + 16, reinterpret_cast<char*>(g_x1) + frag + 8 * CB_BYTES, pub + 8 * 5);
#pragma unroll
        for (int x = 0; x < 32; x++) x3[x] = badd2(x3[x], v[x]);
        WSTAMP(5 + 16 * l);
      }
      const uint32_t park = c.sm + SM_X + wg * 16384 + t * 16;
      char* hp = reinterpret_cast<char*>(g_hid) + frag + c.j * 40 * CB_BYTES;
      uint32_t held[64];
      {
        float acc3[128];
        const float2* sp = &g_part[3 * l + 1][2 * qd][row];
        gemm_begin<256>(c, wg, warp & 3, p, 2, true);
        gemm_step<256, true>(acc3, c, wg, p, Nop());
        float2 s0, s1;
        gemm_steps<256, false>(acc3, c, wg, p, 15, [&]() {
          rs.load(sp, sp + 8);
#pragma unroll
          for (int x = 0; x < 8; x++) sts128(park + x * 2048, make_uint4(x3[4 * x], x3[4 * x + 1], x3[4 * x + 2], x3[4 * x + 3]));
        }, [&]() {
          rs.finish(sp, sp + 8, p.budget, s0, s1);
          s0.y *= 0.5f; s1.y *= 0.5f;
          asm volatile("" : "+f"(s0.x), "+f"(s0.y), "+f"(s1.x), "+f"(s1.y));
          fence_sched();
        });
        WSTAMP(6 + 16 * l);
        fold_tiles<32, false>(held, acc3, reinterpret_cast<const float2*>(smem + SM_CS3) + qd, s0, s1);
        float accb[96];
#pragma unroll
        for (int x = 0; x < 24; x++) {
          const float2 cs = (reinterpret_cast<const float2*>(smem + SM_CS3 + 1024) + qd)[4 * x];
          accb[4 * x] = -s0.x * cs.x; accb[4 * x + 1] = -s0.x * cs.y; accb[4 * x + 2] = -s1.x * cs.x; accb[4 * x + 3] = -s1.x * cs.y;
        }
        pin(accb);
        WSTAMP(7 + 16 * l);
        gemm_begin<192>(c, wg, warp & 3, p, 3, false);
#pragma unroll 1
        for (int pn = 0; pn < 4; pn++) {
#pragma unroll
          for (int u = 0; u < 4; u++) gemm_step<192, false>(accb, c, wg, p, [&]() { gelu_chunk<4>(held + 4 * u, hp + 2 * u * CB_BYTES); });
          hp += 8 * CB_BYTES;
          __syncwarp();
          mbar_arrive_if(pub + 8 * (6 + pn), lane == 0);
          pick_group<16, 1, 4>(held, pn + 1);
        }
        WSTAMP(8 + 16 * l);
#pragma unroll
        for (int x = 0; x < 8; x++) {
          uint4 v;
          asm volatile("ld.shared.v4.u32 {%0,%1,%2,%3}, [%4];" : "=r"(v.x), "=r"(v.y), "=r"(v.z), "=r"(v.w) : "r"(park + x * 2048) : "memory");
          acc[8 * x] = bf_lo(v.x); acc[8 * x + 1] = bf_hi(v.x); acc[8 * x + 2] = bf_lo(v.y); acc[8 * x + 3] = bf_hi(v.y);
          acc[8 * x + 4] = bf_lo(v.z); acc[8 * x + 5] = bf_hi(v.z); acc[8 * x + 6] = bf_lo(v.w); acc[8 * x + 7] = bf_hi(v.w);
        }
        pin(acc);
        WSTAMP(9 + 16 * l);
        gemm_begin<128>(c, wg, warp & 3, p, 4, false);
        gemm_step<128, false>(acc, c, wg, p, Nop());
        pin(accb);
#pragma unroll 1
        for (int hpn = 0; hpn < 6; hpn++) {
#pragma unroll
          for (int u = 0; u < 4; u++)
            gemm_step<128, false>(acc, c, wg, p, [&]() {
              const uint32_t h[2] = {pack_f16(accb[4 * u] * s0.y, accb[4 * u + 1] * s0.y), pack_f16(accb[4 * u + 2] * s1.y, accb[4 * u + 3] * s1.y)};
              gelu_chunk<2>(h, hp + u * CB_BYTES);
            });
          hp += 4 * CB_BYTES;
          __syncwarp();
          mbar_arrive_if(pub + 8 * (10 + (hpn >> 1)), (hpn & 1) && lane == 0);
          pick_group<16, 1, 6>(accb, hpn + 1);
        }
        WSTAMP(12 + 16 * l);
        gemm_steps<128, false>(acc, c, wg, p, 31, Nop(), Nop());
        WSTAMP(10 + 16 * l);
      }
      if (l == 0) {
        put_partial(acc, &g_part[2][c.j][row], 0.f);
        WSTAMP(11);
        const float2* sp = &g_part[2][2 * qd][row];
        rs.load(sp, sp + 8);
        float yf[64];
        mbar_wait(c.bar + 8 * (BAR_OWN + wg), 1, p.budget);
#pragma unroll
        for (int x = 0; x < 16; x++) {
          uint32_t y0, y1;
          asm volatile("ld.shared.v2.u32 {%0,%1}, [%2];" : "=r"(y0), "=r"(y1) : "r"(c.sm + SM_X + wg * 16384 + x * 1024 + t * 8) : "memory");
          yf[4 * x] = bf_lo(y0); yf[4 * x + 1] = bf_hi(y0); yf[4 * x + 2] = bf_lo(y1); yf[4 * x + 3] = bf_hi(y1);
        }
        pin(yf);
        float2 s0, s1;
        rs.finish(sp, sp + 8, p.budget, s0, s1);
        WSTAMP(13);
        float nb0 = -s0.x * s0.y, nb1 = -s1.x * s1.y;
#pragma unroll
        for (int pn = 0; pn < 2; pn++) {
          if (pn == 1) { const float z = late_zero(c.sm + SM_ZERO); nb0 += z; nb1 += z; }
#pragma unroll
          for (int x = 16 * pn; x < 16 * pn + 16; x++) {
            const float r = (x & 1) ? s1.y : s0.y, nb = (x & 1) ? nb1 : nb0;
            acc[2 * x] = fmaf(fmaf(acc[2 * x], r, nb), yf[2 * x], acc[2 * x]);
            acc[2 * x + 1] = fmaf(fmaf(acc[2 * x + 1], r, nb), yf[2 * x + 1], acc[2 * x + 1]);
            x3[x] = pack_bf16(acc[2 * x], acc[2 * x + 1]);
          }
          if (pn == 1) {
            stage_tiles<16>(x3, stage);
            put_partial(acc, &g_part[3][c.j][row], late_zero(c.sm + SM_ZERO));
          }
          emit_panel(x3 + 16 * pn, reinterpret_cast<char*>(g_x3[1]) + frag + pn * 8 * CB_BYTES, pub + 8 * pn);
        }
      } else {
#pragma unroll
        for (int x = 0; x < 32; x++) x3[x] = pack_bf16(acc[2 * x], acc[2 * x + 1]);
      }
    }
    {
      const uint32_t ob = c.sm + SM_X + warp * 4096, oa = ob + (lane & 15) * 128 + (((lane >> 4) ^ (lane & 7)) << 4);
#pragma unroll
      for (int x = 0; x < 16; x += 2) stsm_x4((oa + (x >> 3) * 2048) ^ ((x & 7) << 4), x3[2 * x], x3[2 * x + 1], x3[2 * x + 2], x3[2 * x + 3]);
      fence_async_smem();
      __syncwarp();
      if (lane == 0) {
        tma_store_2d(&maps.m[M_OUT], ob, c.j * 128, wrow);
        tma_store_2d(&maps.m[M_OUT], ob + 2048, c.j * 128 + 64, wrow);
        bulk_commit();
        asm volatile("cp.async.bulk.wait_group.read 0;" ::: "memory");
      }
    }
    WSTAMP(27);
    cluster_exit_barrier();
    WSTAMP(30);
  }
}

typedef CUresult (*EncodeFn)(CUtensorMap*, CUtensorMapDataType, cuuint32_t, void*, const cuuint64_t*, const cuuint64_t*, const cuuint32_t*,
                             const cuuint32_t*, CUtensorMapInterleave, CUtensorMapSwizzle, CUtensorMapL2promotion, CUtensorMapFloatOOBfill);

void encode(EncodeFn fn, CUtensorMap* m, CUtensorMapDataType type, const void* ptr, int rank, const cuuint64_t* dims, const cuuint64_t* strides,
            const cuuint32_t* box, CUtensorMapSwizzle swizzle, CUtensorMapL2promotion promo = CU_TENSOR_MAP_L2_PROMOTION_L2_128B) {
  const cuuint32_t es[3] = {1, 1, 1};
  fn(m, type, rank, const_cast<void*>(ptr), dims, strides, box, es, CU_TENSOR_MAP_INTERLEAVE_NONE, swizzle, promo, CU_TENSOR_MAP_FLOAT_OOB_FILL_NONE);
}
void map_act(EncodeFn fn, CUtensorMap* m, const void* ptr, int cols, int rows = 64) {
  const cuuint64_t dims[2] = {(cuuint64_t)SEQ * 2, (cuuint64_t)cols / 8}, st[1] = {(cuuint64_t)CB_BYTES};
  const cuuint32_t box[2] = {(cuuint32_t)rows * 2, 8};
  encode(fn, m, CU_TENSOR_MAP_DATA_TYPE_UINT64, ptr, 2, dims, st, box, CU_TENSOR_MAP_SWIZZLE_NONE);
}
void map_rows(EncodeFn fn, CUtensorMap* m, const void* ptr, int rows, int cols, int box_rows, int box_cols, CUtensorMapSwizzle swizzle,
              CUtensorMapL2promotion promo) {
  const cuuint64_t dims[2] = {(cuuint64_t)cols, (cuuint64_t)rows}, st[1] = {(cuuint64_t)cols * 2};
  const cuuint32_t box[2] = {(cuuint32_t)box_cols, (cuuint32_t)box_rows};
  encode(fn, m, CU_TENSOR_MAP_DATA_TYPE_BFLOAT16, ptr, 2, dims, st, box, swizzle, promo);
}
void map_w(EncodeFn fn, CUtensorMap* m, const void* ptr, int rows, int cols, int panels) {
  const cuuint64_t dims[3] = {64, (cuuint64_t)rows, (cuuint64_t)cols / 64}, st[2] = {(cuuint64_t)cols * 2, 128};
  const cuuint32_t box[3] = {64, 64, (cuuint32_t)panels};
  encode(fn, m, CU_TENSOR_MAP_DATA_TYPE_BFLOAT16, ptr, 3, dims, st, box, CU_TENSOR_MAP_SWIZZLE_128B);
}

}

extern "C" void kernel_launch(void* const* d_in, const int* in_sizes, int n_in, void* d_out, int out_size) {
  (void)in_sizes; (void)n_in; (void)out_size;
  const bf16* q = (const bf16*)d_in[0];
  const bf16* k = (const bf16*)d_in[1];
  const bf16* v = (const bf16*)d_in[2];
  const bf16* shift_k = (const bf16*)d_in[3];
  const bf16* ssm_k = (const bf16*)d_in[4];
  const bf16* ssm_d = (const bf16*)d_in[5];
  const bf16* w1 = (const bf16*)d_in[7];
  const bf16* w2 = (const bf16*)d_in[8];
  const bf16* w3 = (const bf16*)d_in[9];
  const bf16* w4 = (const bf16*)d_in[10];

  static EncodeFn fn = nullptr;
  static void *p_x3, *p_h, *p_x1, *p_hid, *p_y;
  if (!fn) {
    void* p = nullptr;
    cudaDriverEntryPointQueryResult qr;
    cudaGetDriverEntryPoint("cuTensorMapEncodeTiled", &p, cudaEnableDefault, &qr);
    fn = (EncodeFn)p;
    cudaGetSymbolAddress(&p_x3, g_x3);
    cudaGetSymbolAddress(&p_h, g_h);
    cudaGetSymbolAddress(&p_x1, g_x1);
    cudaGetSymbolAddress(&p_hid, g_hid);
    cudaGetSymbolAddress(&p_y, g_y);
    cudaFuncSetAttribute(conv_prep_kernel, cudaFuncAttributeMaxDynamicSharedMemorySize, CV_SMEM);
    cudaFuncSetAttribute(mega_kernel, cudaFuncAttributeMaxDynamicSharedMemorySize, MEGA_SMEM);
  }
  Maps maps;
  map_act(fn, &maps.m[M_X3A], p_x3, DM);
  map_act(fn, &maps.m[M_X3B], (const bf16*)p_x3 + SEQ * DM, DM);
  map_act(fn, &maps.m[M_X3S], p_x3, DM, 68);
  map_act(fn, &maps.m[M_H], p_h, DM);
  map_act(fn, &maps.m[M_HS], p_h, DM, 68);
  map_act(fn, &maps.m[M_X1], p_x1, DM);
  map_act(fn, &maps.m[M_HID], p_hid, FF);
  map_act(fn, &maps.m[M_Y], p_y, DM);
  map_rows(fn, &maps.m[M_OUT], d_out, SEQ, DM, 16, 64, CU_TENSOR_MAP_SWIZZLE_128B, CU_TENSOR_MAP_L2_PROMOTION_L2_128B);
  map_w(fn, &maps.m[M_W1], w1, DM, DM, 2);
  map_w(fn, &maps.m[M_W2], w2, DM, DM, 2);
  map_w(fn, &maps.m[M_W3A], w3, DM, FF, 4);
  map_w(fn, &maps.m[M_W3B], w3, DM, FF, 3);
  map_w(fn, &maps.m[M_W4], w4, FF, DM, 2);

  cudaStream_t st = cudaStreamPerThread;
  ConvMaps cm;
  map_rows(fn, &cm.k, k, SEQ, DM, 256, 8, CU_TENSOR_MAP_SWIZZLE_NONE, KV_PROMO);
  map_rows(fn, &cm.v, v, SEQ, DM, 256, 8, CU_TENSOR_MAP_SWIZZLE_NONE, KV_PROMO);
  map_rows(fn, &cm.w1, w1, DM, DM, 256, 32, CU_TENSOR_MAP_SWIZZLE_64B, CU_TENSOR_MAP_L2_PROMOTION_L2_128B);
  map_rows(fn, &cm.w3, w3, DM, FF, 256, 32, CU_TENSOR_MAP_SWIZZLE_64B, CU_TENSOR_MAP_L2_PROMOTION_L2_128B);
  conv_prep_kernel<<<128, 512, CV_SMEM, st>>>(cm, q, shift_k, ssm_k, ssm_d, w2);

  cudaLaunchConfig_t cfg = {};
  cfg.gridDim = dim3(128);
  cfg.blockDim = dim3(384);
  cfg.dynamicSmemBytes = MEGA_SMEM;
  cfg.stream = st;
  cudaLaunchAttribute at[1];
  at[0].id = cudaLaunchAttributeProgrammaticStreamSerialization;
  at[0].val.programmaticStreamSerializationAllowed = 1;
  cfg.attrs = at;
  cfg.numAttrs = 1;
  cudaLaunchKernelEx(&cfg, mega_kernel, maps);
}
```

```cpp
#include <cuda_runtime.h>
#include <cuda_bf16.h>
#include <cuda.h>
#include <stdint.h>

namespace {

typedef __nv_bfloat16 bf16;
constexpr int SEQ = 2048, DM = 1024, FF = 3584;
constexpr float LN_EPS = 1e-5f;

constexpr int CB_BYTES = SEQ * 16;
__device__ __align__(1024) bf16 g_x3[2][SEQ * DM];
__device__ __align__(1024) bf16 g_h[SEQ * DM];
__device__ __align__(1024) bf16 g_x1[SEQ * DM];
__device__ __align__(1024) bf16 g_hid[SEQ * FF];
__device__ __align__(1024) bf16 g_y[SEQ * DM];
__device__ __align__(128) float g_cs1[4][DM];
__device__ __align__(128) float g_cs3[FF];
__device__ __align__(128) uint32_t g_epoch;
__device__ __align__(128) float2 g_part[5][8][SEQ];
__device__ __align__(128) float2 g_qstat[SEQ];
__device__ __align__(128) uint32_t g_qcnt;
__device__ __align__(128) uint32_t g_xcnt[48];
constexpr int FS = 8;
__device__ __align__(128) uint32_t g_flag[32 * 8 * FS];
__device__ __align__(128) uint32_t g_role[4];

__device__ __forceinline__ uint32_t smem_u32(const void* p) { return (uint32_t)__cvta_generic_to_shared(p); }
__device__ __forceinline__ uint32_t opaque(uint32_t x) { uint32_t y; asm volatile("mov.u32 %0, %1;" : "=r"(y) : "r"(x)); return y; }
__device__ __forceinline__ void mbar_init(uint32_t bar, uint32_t cnt) { asm volatile("mbarrier.init.shared::cta.b64 [%0], %1;" :: "r"(bar), "r"(cnt)); }
__device__ __forceinline__ void mbar_expect_tx(uint32_t bar, uint32_t bytes) {
  asm volatile("mbarrier.arrive.expect_tx.shared::cta.b64 _, [%0], %1;" :: "r"(bar), "r"(bytes) : "memory");
}
__device__ __forceinline__ void mbar_expect_tx_cluster(uint32_t bar, uint32_t bytes) {
  asm volatile("mbarrier.arrive.expect_tx.shared::cluster.b64 _, [%0], %1;" :: "r"(bar), "r"(bytes) : "memory");
}
__device__ __forceinline__ void mbar_arrive_cluster(uint32_t bar) { asm volatile("mbarrier.arrive.shared::cluster.b64 _, [%0];" :: "r"(bar) : "memory"); }
__device__ __forceinline__ void mbar_arrive(uint32_t bar) { asm volatile("mbarrier.arrive.shared::cta.b64 _, [%0];" :: "r"(bar) : "memory"); }
__device__ __forceinline__ void mbar_arrive_if(uint32_t bar, bool cond) {
  asm volatile("{\n.reg .pred p;\nsetp.ne.b32 p, %1, 0;\n@p mbarrier.arrive.shared::cta.b64 _, [%0];\n}" :: "r"(bar), "r"((uint32_t)cond) : "memory");
}
constexpr int SPIN_LIMIT = 1 << 16;
__device__ __forceinline__ bool mbar_try(uint32_t bar, uint32_t parity) {
  uint32_t done;
  asm volatile("{\n.reg .pred p;\nmbarrier.try_wait.parity.shared::cta.b64 p, [%1], %2;\nselp.b32 %0, 1, 0, p;\n}"
               : "=r"(done) : "r"(bar), "r"(parity) : "memory");
  return done != 0;
}
__device__ __forceinline__ void mbar_wait(uint32_t bar, uint32_t parity, int& budget) {
#pragma unroll 1
  while (!mbar_try(bar, parity)) { if (--budget <= 0) break; }
}
__device__ __forceinline__ bool elect_one() {
  uint32_t p;
  asm volatile("{\n.reg .pred P;\nelect.sync _|P, 0xffffffff;\nselp.b32 %0, 1, 0, P;\n}" : "=r"(p));
  return p != 0;
}
__device__ __forceinline__ void fence_async_smem() { asm volatile("fence.proxy.async.shared::cta;" ::: "memory"); }
__device__ __forceinline__ void fence_async_global() { asm volatile("fence.proxy.async.global;" ::: "memory"); }
__device__ __forceinline__ void named_bar(int id, int n) { asm volatile("bar.sync %0, %1;" :: "r"(id), "r"(n) : "memory"); }
__device__ __forceinline__ uint4 ld_nc_u4(const void* p) {
  uint4 v; asm volatile("ld.global.nc.L1::no_allocate.v4.u32 {%0,%1,%2,%3}, [%4];" : "=r"(v.x), "=r"(v.y), "=r"(v.z), "=r"(v.w) : "l"(p)); return v;
}
__device__ __forceinline__ void tma_2d_mc(uint32_t dst, const CUtensorMap* m, uint32_t bar, int c0, int c1, uint16_t mask) {
  asm volatile("cp.async.bulk.tensor.2d.shared::cluster.global.mbarrier::complete_tx::bytes.multicast::cluster [%0], [%1, {%3, %4}], [%2], %5;"
               :: "r"(dst), "l"(m), "r"(bar), "r"(c0), "r"(c1), "h"(mask) : "memory");
}
__device__ __forceinline__ void tma_2d(uint32_t dst, const CUtensorMap* m, uint32_t bar, int c0, int c1) {
  asm volatile("cp.async.bulk.tensor.2d.shared::cluster.global.mbarrier::complete_tx::bytes [%0], [%1, {%3, %4}], [%2];"
               :: "r"(dst), "l"(m), "r"(bar), "r"(c0), "r"(c1) : "memory");
}
__device__ __forceinline__ void bulk_copy_cluster(uint32_t dst, uint32_t src, uint32_t bytes, uint32_t bar) {
  asm volatile("cp.async.bulk.shared::cluster.shared::cta.mbarrier::complete_tx::bytes [%0], [%1], %2, [%3];"
               :: "r"(dst), "r"(src), "r"(bytes), "r"(bar) : "memory");
}
__device__ __forceinline__ uint32_t mapa(uint32_t addr, uint32_t cta) {
  uint32_t r; asm volatile("mapa.shared::cluster.u32 %0, %1, %2;" : "=r"(r) : "r"(addr), "r"(cta)); return r;
}
__device__ __forceinline__ void bulk_store(void* dst, uint32_t src, uint32_t bytes) {
  asm volatile("cp.async.bulk.global.shared::cta.bulk_group [%0], [%1], %2;" :: "l"(dst), "r"(src), "r"(bytes) : "memory");
}
__device__ __forceinline__ void tma_3d(uint32_t dst, const CUtensorMap* m, uint32_t bar, int c0, int c1, int c2) {
  asm volatile("cp.async.bulk.tensor.3d.shared::cluster.global.mbarrier::complete_tx::bytes [%0], [%1, {%3, %4, %5}], [%2];"
               :: "r"(dst), "l"(m), "r"(bar), "r"(c0), "r"(c1), "r"(c2) : "memory");
}
__device__ __forceinline__ void tma_store_2d(const CUtensorMap* m, uint32_t src, int c0, int c1) {
  asm volatile("cp.async.bulk.tensor.2d.global.shared::cta.bulk_group [%0, {%2, %3}], [%1];" :: "l"(m), "r"(src), "r"(c0), "r"(c1) : "memory");
}
__device__ __forceinline__ void bulk_commit() { asm volatile("cp.async.bulk.commit_group;" ::: "memory"); }
__device__ __forceinline__ void bulk_wait_all() { asm volatile("cp.async.bulk.wait_group 0;" ::: "memory"); }
__device__ __forceinline__ void prefetch_l2(const void* p, uint32_t bytes) { asm volatile("cp.async.bulk.prefetch.L2.global [%0], %1;" :: "l"(p), "r"(bytes) : "memory"); }
__device__ __forceinline__ void cluster_exit_barrier() {
  __syncwarp();
  asm volatile("barrier.cluster.arrive.relaxed;\nbarrier.cluster.wait;" ::: "memory");
}
__device__ __forceinline__ void wg_fence() { asm volatile("wgmma.fence.sync.aligned;" ::: "memory"); }
__device__ __forceinline__ void wg_commit() { asm volatile("wgmma.commit_group.sync.aligned;" ::: "memory"); }
template <int N> __device__ __forceinline__ void wg_wait() { asm volatile("wgmma.wait_group.sync.aligned %0;" :: "n"(N) : "memory"); }
template <int R> __device__ __forceinline__ void reg_alloc() { asm volatile("setmaxnreg.inc.sync.aligned.u32 %0;" :: "n"(R)); }
template <int R> __device__ __forceinline__ void reg_dealloc() { asm volatile("setmaxnreg.dec.sync.aligned.u32 %0;" :: "n"(R)); }
__device__ __forceinline__ void ldsm_x4(uint32_t addr, uint32_t& r0, uint32_t& r1, uint32_t& r2, uint32_t& r3) {
  asm volatile("ldmatrix.sync.aligned.m8n8.x4.shared.b16 {%0,%1,%2,%3}, [%4];" : "=r"(r0), "=r"(r1), "=r"(r2), "=r"(r3) : "r"(addr));
}
__device__ __forceinline__ void ldsm_x4_t(uint32_t addr, uint32_t& r0, uint32_t& r1, uint32_t& r2, uint32_t& r3) {
  asm volatile("ldmatrix.sync.aligned.m8n8.x4.trans.shared.b16 {%0,%1,%2,%3}, [%4];" : "=r"(r0), "=r"(r1), "=r"(r2), "=r"(r3) : "r"(addr));
}
__device__ __forceinline__ void stsm_x4(uint32_t addr, uint32_t r0, uint32_t r1, uint32_t r2, uint32_t r3) {
  asm volatile("stmatrix.sync.aligned.m8n8.x4.shared.b16 [%0], {%1,%2,%3,%4};" :: "r"(addr), "r"(r0), "r"(r1), "r"(r2), "r"(r3) : "memory");
}
__device__ __forceinline__ float2 lds_f2(uint32_t addr) { float2 v; asm volatile("ld.shared.v2.f32 {%0,%1}, [%2];" : "=f"(v.x), "=f"(v.y) : "r"(addr)); return v; }
__device__ __forceinline__ void sts16(uint32_t addr, uint16_t v) { asm volatile("st.shared.u16 [%0], %1;" :: "r"(addr), "h"(v) : "memory"); }
__device__ __forceinline__ void sts32(uint32_t addr, uint32_t v) { asm volatile("st.shared.u32 [%0], %1;" :: "r"(addr), "r"(v) : "memory"); }
__device__ __forceinline__ void sts128(uint32_t addr, uint4 v) {
  asm volatile("st.shared.v4.u32 [%0], {%1,%2,%3,%4};" :: "r"(addr), "r"(v.x), "r"(v.y), "r"(v.z), "r"(v.w) : "memory");
}
__device__ __forceinline__ void mma16816(float (&d)[4], uint32_t a0, uint32_t a1, uint32_t a2, uint32_t a3, uint32_t b0, uint32_t b1) {
  asm("mma.sync.aligned.m16n8k16.row.col.f32.bf16.bf16.f32 {%0,%1,%2,%3}, {%4,%5,%6,%7}, {%8,%9}, {%0,%1,%2,%3};"
               : "+f"(d[0]), "+f"(d[1]), "+f"(d[2]), "+f"(d[3]) : "r"(a0), "r"(a1), "r"(a2), "r"(a3), "r"(b0), "r"(b1));
}
__device__ __forceinline__ uint32_t pack_bf16(float lo, float hi) {
  uint32_t r; asm("cvt.rn.bf16x2.f32 %0, %1, %2;" : "=r"(r) : "f"(hi), "f"(lo)); return r;
}
__device__ __forceinline__ float bf_lo(uint32_t v) { return __uint_as_float(v << 16); }
__device__ __forceinline__ float bf_hi(uint32_t v) { return __uint_as_float(v & 0xffff0000u); }
__device__ __forceinline__ uint32_t bmul2(uint32_t a, uint32_t b) { uint32_t r; asm("mul.rn.bf16x2 %0, %1, %2;" : "=r"(r) : "r"(a), "r"(b)); return r; }
__device__ __forceinline__ uint32_t badd2(uint32_t a, uint32_t b) { uint32_t r; asm("add.rn.bf16x2 %0, %1, %2;" : "=r"(r) : "r"(a), "r"(b)); return r; }
#define STAMP(idx) do {} while (0)
#define MSTAMP(idx) do {} while (0)
#define BSTAMP(idx, saddr) do {} while (0)

__device__ __forceinline__ uint32_t pack_f16(float lo, float hi) {
  uint32_t r; asm("cvt.rn.satfinite.f16x2.f32 %0, %1, %2;" : "=r"(r) : "f"(hi), "f"(lo)); return r;
}
__device__ __forceinline__ uint32_t hfma2(uint32_t a, uint32_t b, uint32_t c) { uint32_t r; asm("fma.rn.f16x2 %0, %1, %2, %3;" : "=r"(r) : "r"(a), "r"(b), "r"(c)); return r; }
__device__ __forceinline__ uint32_t gelu_pair_f16(uint32_t h) {
  const uint32_t c0 = 0x3e623e62u, c1 = 0x34913491u;
  uint32_t u, p, z, t, r, o;
  asm("mul.rn.f16x2 %0, %1, %1;" : "=r"(u) : "r"(h));
  asm("fma.rn.f16x2 %0, %1, %2, %3;" : "=r"(p) : "r"(u), "r"(c1), "r"(c0));
  asm("mul.rn.f16x2 %0, %1, %2;" : "=r"(z) : "r"(h), "r"(p));
  asm("tanh.approx.f16x2 %0, %1;" : "=r"(t) : "r"(z));
  asm("fma.rn.f16x2 %0, %1, %2, %1;" : "=r"(r) : "r"(h), "r"(t));
  float lo, hi;
  asm("{\n.reg .f16 a, b;\nmov.b32 {a, b}, %2;\ncvt.f32.f16 %0, a;\ncvt.f32.f16 %1, b;\n}" : "=f"(lo), "=f"(hi) : "r"(r));
  asm("cvt.rn.bf16x2.f32 %0, %1, %2;" : "=r"(o) : "f"(hi), "f"(lo));
  return o;
}
__device__ __forceinline__ float gelu_from_half(float h) {
  const float c0 = 2.f * 0.7978845608028654f, c1 = 8.f * 0.7978845608028654f * 0.044715f;
  float z = h * fmaf(h * h, c1, c0);
  float t; asm("tanh.approx.f32 %0, %1;" : "=f"(t) : "f"(z));
  return fmaf(h, t, h);
}
__device__ __forceinline__ void wgmma_ss_n128(float (&d)[64], uint32_t a_lo, uint32_t b_lo) {
  asm volatile(
    "{\n.reg .b64 da, db;\nmov.b64 da, {%64, 8};\nmov.b64 db, {%65, 0x40000040};\n"
    "wgmma.mma_async.sync.aligned.m64n128k16.f32.bf16.bf16 "
    "{%0, %1, %2, %3, %4, %5, %6, %7, %8, %9, %10, %11, %12, %13, %14, %15, "
    "%16, %17, %18, %19, %20, %21, %22, %23, %24, %25, %26, %27, %28, %29, %30, %31, "
    "%32, %33, %34, %35, %36, %37, %38, %39, %40, %41, %42, %43, %44, %45, %46, %47, "
    "%48, %49, %50, %51, %52, %53, %54, %55, %56, %57, %58, %59, %60, %61, %62, %63}, "
    "da, db, 1, 1, 1, 0, 1;\n}\n"
    : "+f"(d[0]), "+f"(d[1]), "+f"(d[2]), "+f"(d[3]), "+f"(d[4]), "+f"(d[5]), "+f"(d[6]), "+f"(d[7]),
      "+f"(d[8]), "+f"(d[9]), "+f"(d[10]), "+f"(d[11]), "+f"(d[12]), "+f"(d[13]), "+f"(d[14]), "+f"(d[15]),
      "+f"(d[16]), "+f"(d[17]), "+f"(d[18]), "+f"(d[19]), "+f"(d[20]), "+f"(d[21]), "+f"(d[22]), "+f"(d[23]),
      "+f"(d[24]), "+f"(d[25]), "+f"(d[26]), "+f"(d[27]), "+f"(d[28]), "+f"(d[29]), "+f"(d[30]), "+f"(d[31]),
      "+f"(d[32]), "+f"(d[33]), "+f"(d[34]), "+f"(d[35]), "+f"(d[36]), "+f"(d[37]), "+f"(d[38]), "+f"(d[39]),
      "+f"(d[40]), "+f"(d[41]), "+f"(d[42]), "+f"(d[43]), "+f"(d[44]), "+f"(d[45]), "+f"(d[46]), "+f"(d[47]),
      "+f"(d[48]), "+f"(d[49]), "+f"(d[50]), "+f"(d[51]), "+f"(d[52]), "+f"(d[53]), "+f"(d[54]), "+f"(d[55]),
      "+f"(d[56]), "+f"(d[57]), "+f"(d[58]), "+f"(d[59]), "+f"(d[60]), "+f"(d[61]), "+f"(d[62]), "+f"(d[63])
    : "r"(a_lo), "r"(b_lo));
}
__device__ __forceinline__ void wgmma_ss_n192(float (&d)[96], uint32_t a_lo, uint32_t b_lo) {
  asm volatile(
    "{\n.reg .b64 da, db;\nmov.b64 da, {%96, 8};\nmov.b64 db, {%97, 0x40000040};\n"
    "wgmma.mma_async.sync.aligned.m64n192k16.f32.bf16.bf16 "
    "{%0, %1, %2, %3, %4, %5, %6, %7, %8, %9, %10, %11, %12, %13, %14, %15, "
    "%16, %17, %18, %19, %20, %21, %22, %23, %24, %25, %26, %27, %28, %29, %30, %31, "
    "%32, %33, %34, %35, %36, %37, %38, %39, %40, %41, %42, %43, %44, %45, %46, %47, "
    "%48, %49, %50, %51, %52, %53, %54, %55, %56, %57, %58, %59, %60, %61, %62, %63, "
    "%64, %65, %66, %67, %68, %69, %70, %71, %72, %73, %74, %75, %76, %77, %78, %79, "
    "%80, %81, %82, %83, %84, %85, %86, %87, %88, %89, %90, %91, %92, %93, %94, %95}, "
    "da, db, 1, 1, 1, 0, 1;\n}\n"
    : "+f"(d[0]), "+f"(d[1]), "+f"(d[2]), "+f"(d[3]), "+f"(d[4]), "+f"(d[5]), "+f"(d[6]), "+f"(d[7]),
      "+f"(d[8]), "+f"(d[9]), "+f"(d[10]), "+f"(d[11]), "+f"(d[12]), "+f"(d[13]), "+f"(d[14]), "+f"(d[15]),
      "+f"(d[16]), "+f"(d[17]), "+f"(d[18]), "+f"(d[19]), "+f"(d[20]), "+f"(d[21]), "+f"(d[22]), "+f"(d[23]),
      "+f"(d[24]), "+f"(d[25]), "+f"(d[26]), "+f"(d[27]), "+f"(d[28]), "+f"(d[29]), "+f"(d[30]), "+f"(d[31]),
      "+f"(d[32]), "+f"(d[33]), "+f"(d[34]), "+f"(d[35]), "+f"(d[36]), "+f"(d[37]), "+f"(d[38]), "+f"(d[39]),
      "+f"(d[40]), "+f"(d[41]), "+f"(d[42]), "+f"(d[43]), "+f"(d[44]), "+f"(d[45]), "+f"(d[46]), "+f"(d[47]),
      "+f"(d[48]), "+f"(d[49]), "+f"(d[50]), "+f"(d[51]), "+f"(d[52]), "+f"(d[53]), "+f"(d[54]), "+f"(d[55]),
      "+f"(d[56]), "+f"(d[57]), "+f"(d[58]), "+f"(d[59]), "+f"(d[60]), "+f"(d[61]), "+f"(d[62]), "+f"(d[63]),
      "+f"(d[64]), "+f"(d[65]), "+f"(d[66]), "+f"(d[67]), "+f"(d[68]), "+f"(d[69]), "+f"(d[70]), "+f"(d[71]),
      "+f"(d[72]), "+f"(d[73]), "+f"(d[74]), "+f"(d[75]), "+f"(d[76]), "+f"(d[77]), "+f"(d[78]), "+f"(d[79]),
      "+f"(d[80]), "+f"(d[81]), "+f"(d[82]), "+f"(d[83]), "+f"(d[84]), "+f"(d[85]), "+f"(d[86]), "+f"(d[87]),
      "+f"(d[88]), "+f"(d[89]), "+f"(d[90]), "+f"(d[91]), "+f"(d[92]), "+f"(d[93]), "+f"(d[94]), "+f"(d[95])
    : "r"(a_lo), "r"(b_lo));
}
__device__ __forceinline__ void wgmma_ss_n256(float (&d)[128], uint32_t a_lo, uint32_t b_lo) {
  asm volatile(
    "{\n.reg .b64 da, db;\nmov.b64 da, {%128, 8};\nmov.b64 db, {%129, 0x40000040};\n"
    "wgmma.mma_async.sync.aligned.m64n256k16.f32.bf16.bf16 "
    "{%0, %1, %2, %3, %4, %5, %6, %7, %8, %9, %10, %11, %12, %13, %14, %15, "
    "%16, %17, %18, %19, %20, %21, %22, %23, %24, %25, %26, %27, %28, %29, %30, %31, "
    "%32, %33, %34, %35, %36, %37, %38, %39, %40, %41, %42, %43, %44, %45, %46, %47, "
    "%48, %49, %50, %51, %52, %53, %54, %55, %56, %57, %58, %59, %60, %61, %62, %63, "
    "%64, %65, %66, %67, %68, %69, %70, %71, %72, %73, %74, %75, %76, %77, %78, %79, "
    "%80, %81, %82, %83, %84, %85, %86, %87, %88, %89, %90, %91, %92, %93, %94, %95, "
    "%96, %97, %98, %99, %100, %101, %102, %103, %104, %105, %106, %107, %108, %109, %110, %111, "
    "%112, %113, %114, %115, %116, %117, %118, %119, %120, %121, %122, %123, %124, %125, %126, %127}, "
    "da, db, 1, 1, 1, 0, 1;\n}\n"
    : "+f"(d[0]), "+f"(d[1]), "+f"(d[2]), "+f"(d[3]), "+f"(d[4]), "+f"(d[5]), "+f"(d[6]), "+f"(d[7]),
      "+f"(d[8]), "+f"(d[9]), "+f"(d[10]), "+f"(d[11]), "+f"(d[12]), "+f"(d[13]), "+f"(d[14]), "+f"(d[15]),
      "+f"(d[16]), "+f"(d[17]), "+f"(d[18]), "+f"(d[19]), "+f"(d[20]), "+f"(d[21]), "+f"(d[22]), "+f"(d[23]),
      "+f"(d[24]), "+f"(d[25]), "+f"(d[26]), "+f"(d[27]), "+f"(d[28]), "+f"(d[29]), "+f"(d[30]), "+f"(d[31]),
      "+f"(d[32]), "+f"(d[33]), "+f"(d[34]), "+f"(d[35]), "+f"(d[36]), "+f"(d[37]), "+f"(d[38]), "+f"(d[39]),
      "+f"(d[40]), "+f"(d[41]), "+f"(d[42]), "+f"(d[43]), "+f"(d[44]), "+f"(d[45]), "+f"(d[46]), "+f"(d[47]),
      "+f"(d[48]), "+f"(d[49]), "+f"(d[50]), "+f"(d[51]), "+f"(d[52]), "+f"(d[53]), "+f"(d[54]), "+f"(d[55]),
      "+f"(d[56]), "+f"(d[57]), "+f"(d[58]), "+f"(d[59]), "+f"(d[60]), "+f"(d[61]), "+f"(d[62]), "+f"(d[63]),
      "+f"(d[64]), "+f"(d[65]), "+f"(d[66]), "+f"(d[67]), "+f"(d[68]), "+f"(d[69]), "+f"(d[70]), "+f"(d[71]),
      "+f"(d[72]), "+f"(d[73]), "+f"(d[74]), "+f"(d[75]), "+f"(d[76]), "+f"(d[77]), "+f"(d[78]), "+f"(d[79]),
      "+f"(d[80]), "+f"(d[81]), "+f"(d[82]), "+f"(d[83]), "+f"(d[84]), "+f"(d[85]), "+f"(d[86]), "+f"(d[87]),
      "+f"(d[88]), "+f"(d[89]), "+f"(d[90]), "+f"(d[91]), "+f"(d[92]), "+f"(d[93]), "+f"(d[94]), "+f"(d[95]),
      "+f"(d[96]), "+f"(d[97]), "+f"(d[98]), "+f"(d[99]), "+f"(d[100]), "+f"(d[101]), "+f"(d[102]), "+f"(d[103]),
      "+f"(d[104]), "+f"(d[105]), "+f"(d[106]), "+f"(d[107]), "+f"(d[108]), "+f"(d[109]), "+f"(d[110]), "+f"(d[111]),
      "+f"(d[112]), "+f"(d[113]), "+f"(d[114]), "+f"(d[115]), "+f"(d[116]), "+f"(d[117]), "+f"(d[118]), "+f"(d[119]),
      "+f"(d[120]), "+f"(d[121]), "+f"(d[122]), "+f"(d[123]), "+f"(d[124]), "+f"(d[125]), "+f"(d[126]), "+f"(d[127])
    : "r"(a_lo), "r"(b_lo));
}
__device__ __forceinline__ void wgmma_ss_n128_p(float (&d)[64], uint32_t a_lo, uint32_t b_lo, uint32_t keep) {
  asm volatile(
    "{\n.reg .pred p;\nsetp.ne.b32 p, %66, 0;\n"
    "{\n.reg .b64 da, db;\nmov.b64 da, {%64, 8};\nmov.b64 db, {%65, 0x40000040};\n"
    "wgmma.mma_async.sync.aligned.m64n128k16.f32.bf16.bf16 "
    "{%0, %1, %2, %3, %4, %5, %6, %7, %8, %9, %10, %11, %12, %13, %14, %15, "
    "%16, %17, %18, %19, %20, %21, %22, %23, %24, %25, %26, %27, %28, %29, %30, %31, "
    "%32, %33, %34, %35, %36, %37, %38, %39, %40, %41, %42, %43, %44, %45, %46, %47, "
    "%48, %49, %50, %51, %52, %53, %54, %55, %56, %57, %58, %59, %60, %61, %62, %63}, "
    "da, db, p, 1, 1, 0, 1;\n}\n}\n"
    : "+f"(d[0]), "+f"(d[1]), "+f"(d[2]), "+f"(d[3]), "+f"(d[4]), "+f"(d[5]), "+f"(d[6]), "+f"(d[7]),
      "+f"(d[8]), "+f"(d[9]), "+f"(d[10]), "+f"(d[11]), "+f"(d[12]), "+f"(d[13]), "+f"(d[14]), "+f"(d[15]),
      "+f"(d[16]), "+f"(d[17]), "+f"(d[18]), "+f"(d[19]), "+f"(d[20]), "+f"(d[21]), "+f"(d[22]), "+f"(d[23]),
      "+f"(d[24]), "+f"(d[25]), "+f"(d[26]), "+f"(d[27]), "+f"(d[28]), "+f"(d[29]), "+f"(d[30]), "+f"(d[31]),
      "+f"(d[32]), "+f"(d[33]), "+f"(d[34]), "+f"(d[35]), "+f"(d[36]), "+f"(d[37]), "+f"(d[38]), "+f"(d[39]),
      "+f"(d[40]), "+f"(d[41]), "+f"(d[42]), "+f"(d[43]), "+f"(d[44]), "+f"(d[45]), "+f"(d[46]), "+f"(d[47]),
      "+f"(d[48]), "+f"(d[49]), "+f"(d[50]), "+f"(d[51]), "+f"(d[52]), "+f"(d[53]), "+f"(d[54]), "+f"(d[55]),
      "+f"(d[56]), "+f"(d[57]), "+f"(d[58]), "+f"(d[59]), "+f"(d[60]), "+f"(d[61]), "+f"(d[62]), "+f"(d[63])
    : "r"(a_lo), "r"(b_lo), "r"(keep));
}
__device__ __forceinline__ void wgmma_ss_n256_first(float (&d)[128], uint32_t a_lo, uint32_t b_lo) {
  asm volatile(
    "{\n.reg .b64 da, db;\nmov.b64 da, {%128, 8};\nmov.b64 db, {%129, 0x40000040};\n"
    "mov.b32 %0, 0; mov.b32 %1, 0; mov.b32 %2, 0; mov.b32 %3, 0; mov.b32 %4, 0; mov.b32 %5, 0; mov.b32 %6, 0; mov.b32 %7, 0;\n"
    "mov.b32 %8, 0; mov.b32 %9, 0; mov.b32 %10, 0; mov.b32 %11, 0; mov.b32 %12, 0; mov.b32 %13, 0; mov.b32 %14, 0; mov.b32 %15, 0;\n"
    "mov.b32 %16, 0; mov.b32 %17, 0; mov.b32 %18, 0; mov.b32 %19, 0; mov.b32 %20, 0; mov.b32 %21, 0; mov.b32 %22, 0; mov.b32 %23, 0;\n"
    "mov.b32 %24, 0; mov.b32 %25, 0; mov.b32 %26, 0; mov.b32 %27, 0; mov.b32 %28, 0; mov.b32 %29, 0; mov.b32 %30, 0; mov.b32 %31, 0;\n"
    "mov.b32 %32, 0; mov.b32 %33, 0; mov.b32 %34, 0; mov.b32 %35, 0; mov.b32 %36, 0; mov.b32 %37, 0; mov.b32 %38, 0; mov.b32 %39, 0;\n"
    "mov.b32 %40, 0; mov.b32 %41, 0; mov.b32 %42, 0; mov.b32 %43, 0; mov.b32 %44, 0; mov.b32 %45, 0; mov.b32 %46, 0; mov.b32 %47, 0;\n"
    "mov.b32 %48, 0; mov.b32 %49, 0; mov.b32 %50, 0; mov.b32 %51, 0; mov.b32 %52, 0; mov.b32 %53, 0; mov.b32 %54, 0; mov.b32 %55, 0;\n"
    "mov.b32 %56, 0; mov.b32 %57, 0; mov.b32 %58, 0; mov.b32 %59, 0; mov.b32 %60, 0; mov.b32 %61, 0; mov.b32 %62, 0; mov.b32 %63, 0;\n"
    "mov.b32 %64, 0; mov.b32 %65, 0; mov.b32 %66, 0; mov.b32 %67, 0; mov.b32 %68, 0; mov.b32 %69, 0; mov.b32 %70, 0; mov.b32 %71, 0;\n"
    "mov.b32 %72, 0; mov.b32 %73, 0; mov.b32 %74, 0; mov.b32 %75, 0; mov.b32 %76, 0; mov.b32 %77, 0; mov.b32 %78, 0; mov.b32 %79, 0;\n"
    "mov.b32 %80, 0; mov.b32 %81, 0; mov.b32 %82, 0; mov.b32 %83, 0; mov.b32 %84, 0; mov.b32 %85, 0; mov.b32 %86, 0; mov.b32 %87, 0;\n"
    "mov.b32 %88, 0; mov.b32 %89, 0; mov.b32 %90, 0; mov.b32 %91, 0; mov.b32 %92, 0; mov.b32 %93, 0; mov.b32 %94, 0; mov.b32 %95, 0;\n"
    "mov.b32 %96, 0; mov.b32 %97, 0; mov.b32 %98, 0; mov.b32 %99, 0; mov.b32 %100, 0; mov.b32 %101, 0; mov.b32 %102, 0; mov.b32 %103, 0;\n"
    "mov.b32 %104, 0; mov.b32 %105, 0; mov.b32 %106, 0; mov.b32 %107, 0; mov.b32 %108, 0; mov.b32 %109, 0; mov.b32 %110, 0; mov.b32 %111, 0;\n"
    "mov.b32 %112, 0; mov.b32 %113, 0; mov.b32 %114, 0; mov.b32 %115, 0; mov.b32 %116, 0; mov.b32 %117, 0; mov.b32 %118, 0; mov.b32 %119, 0;\n"
    "mov.b32 %120, 0; mov.b32 %121, 0; mov.b32 %122, 0; mov.b32 %123, 0; mov.b32 %124, 0; mov.b32 %125, 0; mov.b32 %126, 0; mov.b32 %127, 0;\n"
    "wgmma.mma_async.sync.aligned.m64n256k16.f32.bf16.bf16 "
    "{%0, %1, %2, %3, %4, %5, %6, %7, %8, %9, %10, %11, %12, %13, %14, %15, "
    "%16, %17, %18, %19, %20, %21, %22, %23, %24, %25, %26, %27, %28, %29, %30, %31, "
    "%32, %33, %34, %35, %36, %37, %38, %39, %40, %41, %42, %43, %44, %45, %46, %47, "
    "%48, %49, %50, %51, %52, %53, %54, %55, %56, %57, %58, %59, %60, %61, %62, %63, "
    "%64, %65, %66, %67, %68, %69, %70, %71, %72, %73, %74, %75, %76, %77, %78, %79, "
    "%80, %81, %82, %83, %84, %85, %86, %87, %88, %89, %90, %91, %92, %93, %94, %95, "
    "%96, %97, %98, %99, %100, %101, %102, %103, %104, %105, %106, %107, %108, %109, %110, %111, "
    "%112, %113, %114, %115, %116, %117, %118, %119, %120, %121, %122, %123, %124, %125, %126, %127}, "
    "da, db, 1, 1, 1, 0, 1;\n}\n"
    : "=f"(d[0]), "=f"(d[1]), "=f"(d[2]), "=f"(d[3]), "=f"(d[4]), "=f"(d[5]), "=f"(d[6]), "=f"(d[7]),
      "=f"(d[8]), "=f"(d[9]), "=f"(d[10]), "=f"(d[11]), "=f"(d[12]), "=f"(d[13]), "=f"(d[14]), "=f"(d[15]),
      "=f"(d[16]), "=f"(d[17]), "=f"(d[18]), "=f"(d[19]), "=f"(d[20]), "=f"(d[21]), "=f"(d[22]), "=f"(d[23]),
      "=f"(d[24]), "=f"(d[25]), "=f"(d[26]), "=f"(d[27]), "=f"(d[28]), "=f"(d[29]), "=f"(d[30]), "=f"(d[31]),
      "=f"(d[32]), "=f"(d[33]), "=f"(d[34]), "=f"(d[35]), "=f"(d[36]), "=f"(d[37]), "=f"(d[38]), "=f"(d[39]),
      "=f"(d[40]), "=f"(d[41]), "=f"(d[42]), "=f"(d[43]), "=f"(d[44]), "=f"(d[45]), "=f"(d[46]), "=f"(d[47]),
      "=f"(d[48]), "=f"(d[49]), "=f"(d[50]), "=f"(d[51]), "=f"(d[52]), "=f"(d[53]), "=f"(d[54]), "=f"(d[55]),
      "=f"(d[56]), "=f"(d[57]), "=f"(d[58]), "=f"(d[59]), "=f"(d[60]), "=f"(d[61]), "=f"(d[62]), "=f"(d[63]),
      "=f"(d[64]), "=f"(d[65]), "=f"(d[66]), "=f"(d[67]), "=f"(d[68]), "=f"(d[69]), "=f"(d[70]), "=f"(d[71]),
      "=f"(d[72]), "=f"(d[73]), "=f"(d[74]), "=f"(d[75]), "=f"(d[76]), "=f"(d[77]), "=f"(d[78]), "=f"(d[79]),
      "=f"(d[80]), "=f"(d[81]), "=f"(d[82]), "=f"(d[83]), "=f"(d[84]), "=f"(d[85]), "=f"(d[86]), "=f"(d[87]),
      "=f"(d[88]), "=f"(d[89]), "=f"(d[90]), "=f"(d[91]), "=f"(d[92]), "=f"(d[93]), "=f"(d[94]), "=f"(d[95]),
      "=f"(d[96]), "=f"(d[97]), "=f"(d[98]), "=f"(d[99]), "=f"(d[100]), "=f"(d[101]), "=f"(d[102]), "=f"(d[103]),
      "=f"(d[104]), "=f"(d[105]), "=f"(d[106]), "=f"(d[107]), "=f"(d[108]), "=f"(d[109]), "=f"(d[110]), "=f"(d[111]),
      "=f"(d[112]), "=f"(d[113]), "=f"(d[114]), "=f"(d[115]), "=f"(d[116]), "=f"(d[117]), "=f"(d[118]), "=f"(d[119]),
      "=f"(d[120]), "=f"(d[121]), "=f"(d[122]), "=f"(d[123]), "=f"(d[124]), "=f"(d[125]), "=f"(d[126]), "=f"(d[127])
    : "r"(a_lo), "r"(b_lo));
}

template <int N> struct Mma;
template <> struct Mma<128> {
  static __device__ __forceinline__ void ss(float (&d)[64], uint32_t a, uint32_t b) { wgmma_ss_n128(d, a, b); }
  static __device__ __forceinline__ void ss(float (&d)[64], uint32_t a, uint32_t b, uint32_t keep) { wgmma_ss_n128_p(d, a, b, keep); }
};
template <> struct Mma<192> {
  static __device__ __forceinline__ void ss(float (&d)[96], uint32_t a, uint32_t b) { wgmma_ss_n192(d, a, b); }
};
template <> struct Mma<256> {
  static __device__ __forceinline__ void ss(float (&d)[128], uint32_t a, uint32_t b) { wgmma_ss_n256(d, a, b); }
  static __device__ __forceinline__ void ss(float (&d)[128], uint32_t a, uint32_t b, uint32_t) { wgmma_ss_n256_first(d, a, b); }
};
template <int R> __device__ __forceinline__ void pin(float (&d)[R]) {
#pragma unroll
  for (int x = 0; x < R; x++) asm volatile("" : "+f"(d[x]));
}

__device__ __forceinline__ uint32_t ld_relaxed(const uint32_t* p) {
  uint32_t v; asm volatile("ld.relaxed.gpu.global.u32 %0, [%1];" : "=r"(v) : "l"(p) : "memory"); return v;
}
__device__ __forceinline__ void red_release(uint32_t* p) { asm volatile("red.release.gpu.global.add.u32 [%0], 1;" :: "l"(p) : "memory"); }
__device__ __forceinline__ uint32_t both_valid(uint32_t a, uint32_t b, uint32_t ep) {
  uint32_t r; asm("lop3.b32 %0, %1, %2, %3, 0x42;" : "=r"(r) : "r"(a), "r"(b), "r"(ep)); return r;
}
__device__ __forceinline__ uint32_t tagged(float v, uint32_t ep) { return (__float_as_uint(v) | 1u) ^ (ep & 1u); }
__device__ __forceinline__ void st_release(uint32_t* p, uint32_t v) { asm volatile("st.release.gpu.global.u32 [%0], %1;" :: "l"(p), "r"(v) : "memory"); }
__device__ __forceinline__ void stg32(void* p, uint32_t v) { asm volatile("st.global.u32 [%0], %1;" :: "l"(p), "r"(v) : "memory"); }
__device__ __forceinline__ float rsqrt_fast(float x) { float r; asm("rsqrt.approx.ftz.f32 %0, %1;" : "=f"(r) : "f"(x)); return r; }
__device__ __forceinline__ uint32_t gate_pair(uint32_t x, uint32_t y, float r, float nb) {
  const float a = bf_lo(x), b = bf_hi(x);
  return pack_bf16(fmaf(fmaf(a, r, nb), bf_lo(y), a), fmaf(fmaf(b, r, nb), bf_hi(y), b));
}

constexpr int CV_KT_O = 4144;
constexpr int CV_KT_CH = 8336;
constexpr int CV_KH = 2064;
constexpr int CV_U_PLANE = 2240;
constexpr int CV_U_CH = 4496;
constexpr int CV_VQ = 8320, CV_Y_CH = 1040, CV_XROW = 2064;
constexpr int SM_BAR = 0;
constexpr int CV_K = 896;
constexpr int CV_X = CV_K + 128 + 32768;
constexpr int CV_ST0 = CV_X + 16 * CV_XROW;
constexpr int CV_KT = CV_ST0 + 8192;
constexpr int CV_QS = CV_KT + 8 * CV_KT_CH;
constexpr int CV_U = 142848;
constexpr int CV_V = CV_U + 8 * CV_U_CH;
constexpr int CV_ST1 = CV_V + 4 * CV_VQ;
constexpr int SM_ZERO = CV_ST1 + 8192, SM_ROLE = SM_ZERO + 4, SM_EPOCH = SM_ZERO + 8;
constexpr int CV_END = SM_ZERO + 16;
static_assert(CV_QS + 1024 <= CV_U && CV_X % 1024 == 0 && CV_V % 128 == 0, "layout");
constexpr int CV_BAR = SM_BAR + 8 * 84, BAR_REL = 25;
enum { CB_K0, CB_QA, CB_Q0, CB_Q1, CB_Q2, CB_Q3, CB_K1, CB_X0, CB_X1, CB_QC0, CB_QC1, CB_QS, CB_U1, CB_U2,
       CB_ST0, CB_ST1, CB_O1, CB_P1, CB_Y0, CB_Y1, CB_Y2, CB_P2, CB_EARLY, CB_LATE, CB_YOUT, CB_STAT, CB_XFREE = CB_STAT + 2, CB_COUNT };
static_assert(CV_BAR + 8 * CB_COUNT <= CV_K, "layout");

__device__ __forceinline__ uint32_t lds32_nv(uint32_t addr) { uint32_t v; asm("ld.shared.u32 %0, [%1];" : "=r"(v) : "r"(addr)); return v; }
__device__ __forceinline__ void ldsm_x4_nv(uint32_t addr, uint32_t& r0, uint32_t& r1, uint32_t& r2, uint32_t& r3) {
  asm("ldmatrix.sync.aligned.m8n8.x4.shared.b16 {%0,%1,%2,%3}, [%4];" : "=r"(r0), "=r"(r1), "=r"(r2), "=r"(r3) : "r"(addr));
}
__device__ __forceinline__ void stsm_x4_t(uint32_t addr, uint32_t r0, uint32_t r1, uint32_t r2, uint32_t r3) {
  asm volatile("stmatrix.sync.aligned.m8n8.x4.trans.shared.b16 [%0], {%1,%2,%3,%4};" :: "r"(addr), "r"(r0), "r"(r1), "r"(r2), "r"(r3) : "memory");
}
__device__ __forceinline__ void bulk_load(uint32_t dst, const void* src, uint32_t bytes, uint32_t bar) {
  asm volatile("cp.async.bulk.shared::cluster.global.mbarrier::complete_tx::bytes [%0], [%1], %2, [%3];" :: "r"(dst), "l"(src), "r"(bytes), "r"(bar) : "memory");
}
__device__ __forceinline__ void mbar_wait_plain(uint32_t bar, uint32_t parity) {
#pragma unroll 1
  for (int spins = 0; spins < SPIN_LIMIT && !mbar_try(bar, parity); spins++) {}
}

__device__ __forceinline__ void shift_chunk(uint32_t table, int m) {
  const uint32_t src = table + 32 + m * 16;
  uint4 e;
  uint32_t nx;
  asm volatile("ld.shared.v4.u32 {%0,%1,%2,%3}, [%4];" : "=r"(e.x), "=r"(e.y), "=r"(e.z), "=r"(e.w) : "r"(src));
  asm volatile("ld.shared.u32 %0, [%1];" : "=r"(nx) : "r"(src + 16));
  sts128(src + CV_KT_O, make_uint4(__byte_perm(e.x, e.y, 0x5432), __byte_perm(e.y, e.z, 0x5432), __byte_perm(e.z, e.w, 0x5432), __byte_perm(e.w, nx, 0x5432)));
}
__device__ __forceinline__ void kv_block(uint32_t sm, int t0, const uint32_t (&wp)[4], int lane) {
  const int mi = lane >> 3, rev = 7 - (lane & 7);
  uint32_t vv[4], res[4];
  ldsm_x4(sm + CV_V + (t0 >> 9) * (CV_VQ - 8192) + (t0 + 8 * mi + rev) * 16, vv[0], vv[1], vv[2], vv[3]);
#pragma unroll
  for (int i = 0; i < 4; i++) {
    uint32_t k0, k1, k2, k3;
    ldsm_x4(sm + CV_K + (8 + t0 + 8 * i + rev - mi) * 16, k0, k1, k2, k3);
    res[i] = bmul2(badd2(badd2(badd2(bmul2(k3, wp[3]), bmul2(k2, wp[2])), bmul2(k1, wp[1])), bmul2(k0, wp[0])), vv[i]);
  }
  stsm_x4_t(sm + CV_U + (lane & 7) * CV_U_CH + (1 - (mi & 1)) * CV_U_PLANE + (8 + (t0 >> 4) + (mi >> 1)) * 16, res[0], res[1], res[2], res[3]);
}
template <int T0, int NT, int D0, int D1, int J0, int J1>
__device__ __forceinline__ void conv_phase(float (&acc)[16][4], uint32_t abase, uint32_t bbase, uint32_t zero) {
  abase += zero; bbase += zero;
#pragma unroll 1
  for (int dl = 0; dl < 8; dl++) {
    uint32_t bf[NT][2];
#pragma unroll
    for (int j = 0; j < NT; j += 2) ldsm_x4_nv(bbase + (T0 + j) * 128 - dl * 16, bf[j][0], bf[j][1], bf[j + 1][0], bf[j + 1][1]);
    const uint32_t ap = abase + dl * 32;
#pragma unroll
    for (int dh = D0; dh < D1; dh++) {
      const uint32_t a0 = lds32_nv(ap + dh * 256), a1 = lds32_nv(ap + dh * 256 - 16), a2 = lds32_nv(ap + dh * 256 + 16);
      const uint32_t a3 = a0 + zero;
#pragma unroll
      for (int j = 0; j < NT; j++)
        if (dh + T0 + j >= J0 && dh + T0 + j < J1) mma16816(acc[dh + T0 + j], a0, a1, a2, a3, bf[j][0], bf[j][1]);
    }
  }
}
__device__ __forceinline__ uint32_t hidden_zero(uint32_t addr) {
  uint32_t z; asm volatile("ld.volatile.shared.u32 %0, [%1];" : "=r"(z) : "r"(addr) : "memory"); return z;
}
template <int J0, int J1>
__device__ __forceinline__ void stage_y(const float (&acc)[16][4], uint32_t ys, uint32_t bar) {
#pragma unroll
  for (int j = J0; j < J1; j += 2)
    stsm_x4_t(ys + (j >> 2) * CV_VQ + (j & 3) * 128, pack_bf16(acc[j][0], acc[j][1]), pack_bf16(acc[j][2], acc[j][3]),
              pack_bf16(acc[j + 1][0], acc[j + 1][1]), pack_bf16(acc[j + 1][2], acc[j + 1][3]));
  __syncwarp();
  mbar_arrive_if(bar, (threadIdx.x & 31) == 0);
}

#define KV_PROMO CU_TENSOR_MAP_L2_PROMOTION_L2_128B
#define STATS_EARLY 0
#define QC1_AT 2
#define QROW_AT 3
constexpr int CV_JS = 8;
enum { M_K, M_V, M_Q, M_W1C, M_W3C, M_X3S, M_X3B, M_H, M_HS, M_X1, M_HID, M_W1, M_W2, M_W3A, M_W3B, M_W4, M_OUT, M_Y, M_COUNT };
struct alignas(64) Params {
  const bf16 *q, *shift_k, *ssm_k, *ssm_d, *w2;
  CUtensorMap m[M_COUNT];
};
__device__ __forceinline__ void prefetch_line(const void* p) { asm volatile("prefetch.global.L2 [%0];" :: "l"(p) : "memory"); }

__device__ __forceinline__ uint32_t pick_role() {
  uint32_t smid;
  asm volatile("mov.u32 %0, %%smid;" : "=r"(smid));
  const uint32_t t = smid >> 1;
  const uint32_t gpc = t < 32 ? t & 7 : t < 60 ? 1 + (t - 32) % 7 : t < 62 ? t - 54 : 0;
#pragma unroll 1
  for (uint32_t k = 0; k < 4; k++) {
    const uint32_t p = (gpc + k) & 3, ticket = atomicAdd(&g_role[p], 1u);
    if (ticket < 16) return ticket * 4 + p;
  }
  return 0;
}

__device__ __forceinline__ void load_k(const Params& pr, uint32_t sm, int x) {
  const uint32_t bar = sm + CV_BAR + 8 * (x ? CB_K1 : CB_K0), bytes = x ? 4096 - CV_KH : CV_KH;
  mbar_expect_tx(bar, 8 * bytes);
#pragma unroll 1
  for (int ch = 0; ch < 8; ch++)
    bulk_load(sm + CV_KT + ch * CV_KT_CH + 32 + x * CV_KH, reinterpret_cast<const char*>(pr.ssm_k) + (blockIdx.x * 8 + ch) * 4096 + x * CV_KH, bytes, bar);
}
__device__ __forceinline__ void load_kv(const Params& pr, uint32_t sm, int y, int barrier) {
  tma_2d(sm + CV_K + 128 + y * 4096, &pr.m[M_K], sm + CV_BAR + 8 * barrier, blockIdx.x * 8, y * 256);
  tma_2d(sm + CV_V + (y >> 1) * CV_VQ + (y & 1) * 4096, &pr.m[M_V], sm + CV_BAR + 8 * barrier, blockIdx.x * 8, y * 256);
}

__device__ __forceinline__ void conv_part(const Params& pr, uint32_t sm, int warp) {
  const int tid = threadIdx.x, lane = tid & 31;
  const int b = blockIdx.x, d0 = b * 8;
  const uint32_t kt = sm + CV_KT, ub = sm + CV_U, bar = sm + CV_BAR;
  const int g = lane >> 2, qd = lane & 3, mi = lane >> 3;
  if (warp == 8) {
    asm volatile("bar.arrive 1, 384;" ::: "memory");
    const uint32_t ep = ld_relaxed(&g_epoch);
    if (elect_one()) {
      load_k(pr, sm, 1);
#pragma unroll 1
      for (int y = 2; y < 8; y++) {
        if (y == 2 * QROW_AT) {
          mbar_expect_tx(bar + 8 * CB_X0, 32768);
#pragma unroll 1
          for (int r = 0; r < 16; r++) bulk_load(sm + CV_X + r * CV_XROW, pr.q + (size_t)(b * 16 + r) * DM, 2048, bar + 8 * CB_X0);
        }
        if (!(y & 1)) mbar_expect_tx(bar + 8 * (CB_Q0 + (y >> 1)), 16384);
        load_kv(pr, sm, y, CB_Q0 + (y >> 1));
      }
#pragma unroll 1
      for (int x = M_Q; x < M_COUNT; x++) asm volatile("prefetch.tensormap [%0];" :: "l"(&pr.m[x]) : "memory");
      sts32(sm + SM_EPOCH, ep);
      if ((b & 1) == 0) sts32(sm + SM_ROLE, pick_role());
      asm volatile("fence.release.sync_restrict::shared::cta.cluster;" ::: "memory");
    }
    __syncwarp();
    asm volatile("barrier.cluster.arrive.relaxed.aligned;" ::: "memory");
    auto load_q = [&](int x) {
      mbar_wait_plain(bar + 8 * (CB_U1 + x), 0);
      fence_async_smem();
      if (elect_one()) {
        mbar_expect_tx(bar + 8 * (CB_QC0 + x), 16384);
#pragma unroll 1
        for (int y = 4 * x; y < 4 * x + 4; y++) tma_2d(sm + CV_K + 128 + y * 4096, &pr.m[M_Q], bar + 8 * (CB_QC0 + x), d0, y * 256);
      }
    };
    const int npieces = b < 112 ? 5 : 1;
    const int xr = (mi >> 1) * 8 + (lane & 7);
    const uint32_t xa = sm + CV_X + xr * 64 + (((mi & 1) ^ ((xr >> 1) & 3)) << 4);
    float cs[8][4] = {};
    auto q_stats = [&]() {
      mbar_wait_plain(bar + 8 * CB_QS, 0);
      float sum = 0.f, sq = 0.f;
#pragma unroll
      for (int x = 0; x < 8; x++) { const float2 v = lds_f2(sm + CV_QS + x * 128 + (lane & 15) * 8); sum += v.x; sq += v.y; }
      const float mean = sum * (1.f / DM), rs = rsqrt_fast(fmaxf(fmaf(-mean, mean, sq * (1.f / DM)), 0.f) + LN_EPS);
      if (lane < 16)
        asm volatile("st.relaxed.gpu.global.v2.b32 [%0], {%1,%2};" :: "l"(g_qstat + b * 16 + lane), "r"(tagged(rs, ep)), "r"(__float_as_uint(-mean * rs)) : "memory");
      if (lane == 0) { STAMP(47); asm volatile("red.relaxed.gpu.global.add.u32 [%0], 1;" :: "l"(&g_qcnt) : "memory"); }
    };
#pragma unroll 1
    for (int pc = -3; pc < npieces; pc++) {
      if (pc == -2) q_stats();
      if (pc >= 0) {
        mbar_wait_plain(bar + 8 * (CB_X0 + ((pc + 1) & 1)), ((pc + 1) >> 1) & 1);
#pragma unroll 1
        for (int r = 0; r < 16; r += 4) {
#pragma unroll
          for (int x = 0; x < 8; x++) {
            uint32_t a0, a1, a2, a3;
            ldsm_x4_t((xa ^ ((x & 1) << 5)) + ((pc + 1) & 1) * 16384 + (r + (x >> 1)) * 1024, a0, a1, a2, a3);
            mma16816(cs[x], a0, a1, a2, a3, 0x3f803f80u, 0x3f803f80u);
          }
        }
        if (pc == 0 || pc == 4) {
          float t = 0.f;
#pragma unroll
          for (int x = 0; x < 8; x += 2) {
            t += qd & 2 ? (qd & 1 ? cs[x + 1][2] : cs[x + 1][0]) : (qd & 1 ? cs[x][2] : cs[x][0]);
            cs[x][0] = cs[x][2] = cs[x + 1][0] = cs[x + 1][2] = 0.f;
          }
          (pc ? g_cs3 + 32 * b : g_cs1[b & 3] + 32 * (b >> 2))[8 * qd + g] = t;
        }
        __syncwarp();
      }
      if (pc > -3 && pc + 2 < npieces && elect_one()) {
        const uint32_t bx = bar + 8 * (CB_X0 + ((pc + 1) & 1));
        mbar_expect_tx(bx, 16384);
        tma_2d(sm + CV_X + ((pc + 1) & 1) * 16384, &pr.m[pc == -2 ? M_W1C : M_W3C], bx, 32 * (pc == -2 ? b >> 2 : b), 256 * (pc == -2 ? b & 3 : pc + 1));
      }
      if (pc == -3 || pc == min(QC1_AT, npieces - 1)) load_q(pc >= 0);
    }
#pragma unroll 1
    for (int x = 0; x < 4; x++) prefetch_line(reinterpret_cast<const char*>(pr.w2) + (b * 128 + x * 32 + lane) * 128);
    if (lane == 0) STAMP(52);
    return;
  }

  const uint32_t dpair = __ldg(reinterpret_cast<const uint32_t*>(pr.ssm_d + d0 + 2 * qd));
  const int wi = warp - (warp > 8), ti = 32 * wi + lane;
  {
    if (tid < 160) {
      const int x = tid - 128, y = x & 3;
      sts128(tid < 128 ? ub + (tid >> 4) * CV_U_CH + ((tid >> 3) & 1) * CV_U_PLANE + (tid & 7) * 16
                       : y == 3 ? sm + CV_K + (x >> 2) * 16 : kt + (x >> 2) * CV_KT_CH + (y == 2 ? 4128 : y * 16), make_uint4(0, 0, 0, 0));
    }
    uint32_t wp[4];
    {
      const uint4 a = ld_nc_u4(pr.shift_k + (d0 + 2 * qd) * 4);
      wp[0] = __byte_perm(a.x, a.z, 0x5410); wp[1] = __byte_perm(a.x, a.z, 0x7632);
      wp[2] = __byte_perm(a.y, a.w, 0x5410); wp[3] = __byte_perm(a.y, a.w, 0x7632);
    }
    named_bar(1, 384);
#pragma unroll 1
    for (int x = 0; x < 2; x++) {
      mbar_wait_plain(bar + 8 * (x ? CB_K1 : CB_K0), 0);
#pragma unroll 1
      for (int idx = x ? ti + 8 * 130 - 256 : ti; idx < (x ? 8 * 258 : 8 * 130); idx += x ? 96 : 352)
        shift_chunk(kt + (idx & 7) * CV_KT_CH, (idx >> 3) - 2);
      __syncwarp();
      mbar_arrive_if(bar + 8 * CB_O1, x && lane == 0);
      if (tid == 0) BSTAMP(54, kt);
#pragma unroll 1
      for (int t0 = warp < 8 ? 32 * wi : 32 * wi + 256; t0 < (x ? SEQ : 512); t0 += x ? 96 : 256) {
        mbar_wait_plain(bar + 8 * (t0 < 256 ? CB_QA : CB_Q0 + (t0 >> 9)), 0);
        if (tid == 0) BSTAMP(56, kt);
        kv_block(sm, t0, wp, lane);
        constexpr int T1 = 128 * CV_JS + 32;
        __syncwarp();
        mbar_arrive_if(bar + 8 * (CB_U1 + (t0 >= T1)), t0 + 96 >= (t0 < T1 ? T1 : SEQ) && lane == 0);
      }
      if (x == 0) named_bar(4, 352);
      if (warp < 8) break;
    }
  }

  if (warp < 8) {
    const int o = 2 * qd - g;
    const uint32_t abase = kt + warp * CV_KT_CH + 32 + ((g & 1) ? CV_KT_O + (o - 1) * 2 : o * 2);
    const uint32_t bbase = ub + warp * CV_U_CH + (mi & 1) * CV_U_PLANE + (8 + (lane >> 4) * 8 + (lane & 7)) * 16;
    const uint32_t ys = sm + CV_V + warp * CV_Y_CH + (mi & 1) * 512 + ((lane >> 4) * 8 + (lane & 7)) * 16;
    auto q_sums = [&]() {
      mbar_wait_plain(bar + 8 * CB_X0, 0);
      float sum[4] = {0.f, 0.f, 0.f, 0.f}, lo[4] = {0.f, 0.f, 0.f, 0.f}, hi[4] = {0.f, 0.f, 0.f, 0.f};
#pragma unroll
      for (int x = 0; x < 8; x++) {
        uint32_t a0, a1, a2, a3;
        ldsm_x4(sm + CV_X + (lane & 15) * CV_XROW + warp * 256 + (lane >> 4) * 16 + x * 32, a0, a1, a2, a3);
        mma16816(sum, a0, a1, a2, a3, 0x3f803f80u, 0x3f803f80u);
        mma16816(lo, a0, a1, a2, a3, a0, a2);
        mma16816(hi, a0, a1, a2, a3, a1, a3);
      }
      if (qd == (g >> 1)) {
        asm volatile("st.shared.v2.f32 [%0], {%1,%2};" :: "r"(sm + CV_QS + warp * 128 + g * 8), "f"(sum[0]), "f"((g & 1) ? lo[1] : lo[0]) : "memory");
        asm volatile("st.shared.v2.f32 [%0], {%1,%2};" :: "r"(sm + CV_QS + warp * 128 + g * 8 + 64), "f"(sum[2]), "f"((g & 1) ? hi[3] : hi[2]) : "memory");
      }
      __syncwarp();
      mbar_arrive_if(bar + 8 * CB_QS, lane == 0);
    };
    if (tid == 0) STAMP(49);
    float acc[16][4];
#pragma unroll
    for (int j = 0; j < 16; j++) { acc[j][0] = acc[j][1] = acc[j][2] = acc[j][3] = 0.f; }
    conv_phase<0, 4, 0, 8, 0, 16>(acc, abase, bbase, hidden_zero(ub));
    stage_y<0, 4>(acc, ys, bar + 8 * CB_Y0);
    if (tid == 0) STAMP(57);
    if (STATS_EARLY) q_sums();
    mbar_wait_plain(bar + 8 * CB_K1, 0);
    mbar_wait_plain(bar + 8 * CB_O1, 0);
    conv_phase<0, 4, 8, 16, 0, 16>(acc, abase, bbase, hidden_zero(ub));
    if (tid == 0) STAMP(58);
    if (!STATS_EARLY) q_sums();
    mbar_wait_plain(bar + 8 * CB_U1, 0);
    conv_phase<4, CV_JS - 4, 0, CV_JS - 4, 0, CV_JS>(acc, abase, bbase, hidden_zero(ub));
    stage_y<4, CV_JS>(acc, ys, bar + 8 * CB_Y1);
    if (tid == 0) STAMP(59);
    mbar_wait_plain(bar + 8 * CB_U2, 0);
    if (tid == 0) BSTAMP(55, kt);
    conv_phase<4, 12, 0, 12, CV_JS, 16>(acc, abase, bbase, hidden_zero(ub));
    stage_y<CV_JS, 16>(acc, ys, bar + 8 * CB_Y2);
    if (tid == 0) STAMP(50);
    if (tid == 32) STAMP(62);
  }
  {
    const int ch = lane & 7;
    const uint32_t ya = sm + CV_V + ch * CV_Y_CH + (mi & 1) * 512 + (mi >> 1) * 16;
    const uint32_t ua = ub + ch * CV_U_CH + (mi & 1) * CV_U_PLANE + (8 + (mi >> 1)) * 16;
    const uint32_t qa = sm + CV_K + 128 + (16 * (mi >> 1) + 15 - 8 * (mi & 1) - ch) * 16;
    char* xo = reinterpret_cast<char*>(g_x3[0]) + (size_t)b * CB_BYTES + (15 - g) * 16 + qd * 4;
    const uint32_t yo = sm + CV_K + 128 + ((7 - g) * 4 + qd) * 8;
    int budget = SPIN_LIMIT;
    uint32_t ep = 0;
    if (warp > 8) {
      if (tid == 288) STAMP(53);
      ep = ld_relaxed(&g_epoch);
#pragma unroll 1
      while (ld_relaxed(&g_qcnt) - 128 * ep < 128 && --budget > 0) __nanosleep(100);
      if (tid == 288) STAMP(43);
    }
#pragma unroll 1
    for (int part = warp < 8; part < 2; part++) {
      if (warp > 8) {
        uint4 v[6];
#pragma unroll 1
        do {
          uint32_t ok = 1;
#pragma unroll
          for (int y = 0; y < 6; y++) {
            asm volatile("ld.relaxed.gpu.global.v4.u32 {%0,%1,%2,%3}, [%4];" : "=r"(v[y].x), "=r"(v[y].y), "=r"(v[y].z), "=r"(v[y].w)
                         : "l"(g_qstat + 1024 * part + 2 * min(ti - 256 + 96 * y, 511)) : "memory");
            ok &= both_valid(v[y].x, v[y].z, ep);
          }
          if (__all_sync(0xffffffffu, ok)) break;
        } while (--budget > 0);
#pragma unroll
        for (int y = 0; y < 6; y++) sts128(sm + (part ? CV_ST1 : CV_ST0) + min(ti - 256 + 96 * y, 511) * 16, make_uint4(v[y].x | 1u, v[y].y, v[y].z | 1u, v[y].w));
        __syncwarp();
        mbar_arrive_if(bar + 8 * (CB_ST0 + part), lane == 0);
        if (warp == 9 && part) break;
      }
      mbar_wait_plain(bar + 8 * (CB_ST0 + part), 0);
      mbar_wait_plain(bar + 8 * (CB_QC0 + part), 0);
      if (tid == 288) STAMP(63);
#pragma unroll 1
      for (int u = part ? 4 * CV_JS + warp - 2 * (warp > 8) : warp - 9; u < (part ? 64 : 4 * CV_JS); u += part ? 10 : 3) {
        mbar_wait_plain(bar + 8 * (part ? CB_Y2 : CB_Y0 + (u >= 16)), 0);
        const uint32_t sa = sm + (part ? CV_ST1 - 8192 : CV_ST0) + u * 256 + (15 - g) * 8;
        uint32_t y[4], uu[4], qq[4];
        ldsm_x4_t(ya + (u >> 4) * CV_VQ + (u & 15) * 32, y[0], y[1], y[2], y[3]);
        ldsm_x4_t(ua + u * 32, uu[0], uu[1], uu[2], uu[3]);
        ldsm_x4(qa + u * 512, qq[0], qq[1], qq[2], qq[3]);
#pragma unroll
        for (int i = 0; i < 4; i++) {
          const int off = 16 * (i >> 1) - 8 * (i & 1);
          const float2 s = lds_f2(sa + off * 8);
          y[i] = badd2(y[i], bmul2(uu[i], dpair));
          stg32(xo + u * 512 + off * 16, gate_pair(qq[i], y[i], s.x, s.y));
        }
        asm volatile("st.shared.v2.u32 [%0], {%1,%2};" :: "r"(yo + u * 512), "r"(y[1]), "r"(y[0]) : "memory");
        asm volatile("st.shared.v2.u32 [%0], {%1,%2};" :: "r"(yo + u * 512 + 256), "r"(y[3]), "r"(y[2]) : "memory");
      }
      __syncwarp();
      mbar_arrive_if(bar + 8 * (part ? CB_P2 : CB_P1), lane == 0);
    }
  }
  if (warp == 9) {
    mbar_wait_plain(bar + 8 * CB_P1, 0);
    if (elect_one()) {
      STAMP(61);
      red_release(&g_xcnt[b >> 3]);
      fence_async_smem();
      bulk_store(reinterpret_cast<char*>(g_y) + (size_t)b * CB_BYTES, sm + CV_K + 128, 16384);
      bulk_commit();
      bulk_wait_all();
      mbar_arrive(bar + 8 * CB_YOUT);
    }
  }
  if (tid == 0) STAMP(51);
}

constexpr int NA = 5, A_SLOT = 68 * 128;
constexpr int SM_B = 1024;
constexpr int SM_A = SM_B + 98304;
constexpr int SM_X = SM_A + 2 * NA * A_SLOT;
constexpr int SM_CS1 = CV_END;
constexpr int SM_CS3 = SM_CS1 + 512;
static_assert(SM_X % 1024 == 0 && SM_X + 32768 <= SM_CS1 && SM_B + 2 * 16384 == CV_X && SM_A + NA * A_SLOT == CV_U, "layout");
constexpr int BAR_FULLA = 0, BAR_FULLB = 16, BAR_TURN = 24, BAR_OWN = 26;
constexpr int BAR_EMPTYA = 28, BAR_EMPTYB = BAR_EMPTYA + 18, BAR_CS = BAR_EMPTYB + 9;
constexpr int BAR_PUB = 56;
constexpr int BAR_END = 84;
constexpr int SM_RS = SM_CS3 + 1792;
constexpr int MEGA_SMEM = SM_RS + 2 * 68 * 8;
static_assert(MEGA_SMEM <= 232448, "shared memory");
#define LEAD16 4
#define LEAD32 2
#define XFREE_N 2
#define TURN_EARLY 1

template <int N> struct BGeo;
template <> struct BGeo<128> { static constexpr int SLOTS = 6, BYTES = 16384, LEAD = LEAD16; };
template <> struct BGeo<256> { static constexpr int SLOTS = 3, BYTES = 32768, LEAD = LEAD32; };
template <> struct BGeo<192> { static constexpr int SLOTS = 4, BYTES = 24576; };
__host__ __device__ constexpr int first_slot(int s) { return s == 0 || s == 2 ? 2 : 0; }
__device__ __forceinline__ bool starts_local(int l, int s) { return s == 2 || s == 1 - l; }
__device__ __forceinline__ int token_shift(int j) { return ((j >> 1) & 1 ? 1 : -1) * (1 + (j >> 2)); }

struct Ctx {
  uint32_t sm;
  uint32_t bar;
  int i, j, r;
  int bid;
  uint32_t ep;
};

struct Pipe {
  uint32_t ko, kp;
  uint32_t po;
  uint32_t a0, a1, ar;
  uint32_t b;
  uint32_t keep;
  uint32_t sh, wide;
  uint32_t turn;
  int budget;
  uint32_t rel;
  bool signals;
  __device__ __forceinline__ void release() const {
    asm volatile("{\n.reg .pred p;\nsetp.ne.b32 p, %1, 0;\n@p mbarrier.arrive.shared::cluster.b64 _, [%0];\n}" :: "r"(rel + po), "r"((uint32_t)signals) : "memory");
  }
  __device__ __forceinline__ void drain() { wg_wait<0>(); release(); po = 64; }
};
__device__ __forceinline__ uint32_t desc_a(const Ctx& c, int off) { return ((c.sm & 0x3FFFFu) >> 4) + 0x400000u + (off >> 4); }
__device__ __forceinline__ uint32_t desc_b(const Ctx& c, int off) { return ((c.sm & 0x3FFFFu) >> 4) + 0x2000000u + ((SM_B + off) >> 4); }

template <int N, bool PRED, bool SHIFT = false, class Extra>
__device__ __forceinline__ void gemm_step(float (&acc)[N / 2], const Ctx& c, int wg, Pipe& p, Extra&& extra) {
  using G = BGeo<N>;
  const uint32_t fa = c.bar + 8 * BAR_FULLA + 64 * wg + p.ko, fb = c.bar + 8 * BAR_FULLB + p.ko;
#pragma unroll 1
  while (true) {
    uint32_t ready;
    asm volatile("{\n.reg .pred p, q;\nmbarrier.try_wait.parity.shared::cta.b64 p, [%1], %3;\nmbarrier.try_wait.parity.shared::cta.b64 q, [%2], %3;\n"
                 "and.pred p, p, q;\nselp.b32 %0, 1, 0, p;\n}" : "=r"(ready) : "r"(fa), "r"(fb), "r"(p.kp) : "memory");
    if (ready || --p.budget <= 0) break;
  }
  wg_fence();
  const uint32_t a = SHIFT ? p.a0 + (p.sh & 3) + (p.wide << 16) : p.a0, ak = SHIFT ? 128 + 2 * p.wide : 128;
  if constexpr (SHIFT) p.sh >>= 2;
  if constexpr (PRED) { Mma<N>::ss(acc, a, p.b, p.keep); p.keep = 1; } else Mma<N>::ss(acc, a, p.b);
#pragma unroll
  for (int kk = 1; kk < 4; kk++) Mma<N>::ss(acc, a + kk * ak, p.b + kk * 128);
  wg_commit();
  extra();
  wg_wait<1>();
  p.release();
  p.po = p.ko;
  p.ko = (p.ko + 8) & 63;
  p.kp ^= p.ko == 0;
  p.a0 = p.a1; p.a1 = p.ar;
  p.ar = p.ar == desc_a(c, SM_A + (NA - 1) * A_SLOT) + wg * NA * (A_SLOT >> 4) ? p.ar - (NA - 1) * (A_SLOT >> 4) : p.ar + (A_SLOT >> 4);
  p.b = p.b == desc_b(c, (G::SLOTS - 1) * G::BYTES) ? desc_b(c, 0) : p.b + (G::BYTES >> 4);
}
template <int N>
__device__ __forceinline__ void gemm_begin(const Ctx& c, int wg, int wq, Pipe& p, int s, bool local) {
  if (local) {
    fence_async_smem();
    named_bar(2 + wg, 128);
    mbar_arrive_if(c.bar + 8 * BAR_FULLA + 64 * wg + 8 * (threadIdx.x & 1), (threadIdx.x & 126) == 96);
    if (wq < 2) {
      mbar_wait(c.bar + 8 * (BAR_EMPTYA + 9 * wg + 8 - NA + wq), p.kp ^ 1, p.budget);
      if (elect_one()) {
        const uint32_t peer = mapa(c.sm, c.r ^ 1), bar = peer + SM_BAR + 8 * (BAR_FULLA + 8 * wg + 2 + wq);
        mbar_expect_tx_cluster(bar, 8192);
        bulk_copy_cluster(peer + (((wq ? p.a1 : p.a0) - desc_a(c, 0)) << 4), c.sm + SM_X + (2 * wg + wq) * 8192, 8192, bar);
      }
      __syncwarp();
    }
  }
  asm volatile("{\n.reg .pred p;\nsetp.ne.b32 p, %3, 0;\nselp.b32 %2, %0, %2, p;\nselp.b32 %0, %4, %0, p;\nselp.b32 %1, %5, %1, p;\n}"
               : "+r"(p.a0), "+r"(p.a1), "+r"(p.ar) : "r"((uint32_t)local), "r"(desc_a(c, SM_X) + wg * 1024), "r"(desc_a(c, SM_X + 8192) + wg * 1024));
  p.b = desc_b(c, first_slot(s) * BGeo<N>::BYTES);
}
template <class Hook>
__device__ __forceinline__ void yield_turn(const Ctx& c, int wg, Pipe& p, Hook&& hook) {
  if (wg == 1) p.drain();
  hook();
  if (wg == 1) mbar_wait(c.bar + 8 * BAR_TURN, p.turn, p.budget);
  p.turn ^= 1;
}
__device__ __forceinline__ void pass_turn(const Ctx& c, bool now) { mbar_arrive_if(c.bar + 8 * BAR_TURN, now && threadIdx.x == 96); }
struct Nop { __device__ __forceinline__ void operator()() const {} };
template <int N, bool PRED, bool SHIFT = false, class Hook, class Tail>
__device__ __forceinline__ void gemm_steps(float (&acc)[N / 2], const Ctx& c, int wg, Pipe& p, int count, Hook&& hook, Tail&& tail) {
  constexpr int LEAD = BGeo<N>::LEAD, LAST = LEAD > TURN_EARLY ? TURN_EARLY : LEAD - 1;
#pragma unroll 1
  for (int n = count - LEAD; n > 0; n--) gemm_step<N, PRED, SHIFT>(acc, c, wg, p, Nop());
  yield_turn(c, wg, p, hook);
#pragma unroll 1
  for (int n = LEAD - 1; n >= 0; n--) {
    gemm_step<N, false, SHIFT>(acc, c, wg, p, Nop());
    pass_turn(c, n == LAST);
  }
  tail();
  p.drain();
}

__device__ __forceinline__ void put_stat(float2* gdst, float s, float q, bool cond, uint32_t ep) {
  const float m = s * (1.f / 128), v = fmaxf(fmaf(-m, s, q), 0.f);
  asm volatile("{\n.reg .pred p;\nsetp.ne.b32 p, %3, 0;\n@p st.relaxed.gpu.global.v2.b32 [%0], {%1,%2};\n}"
               :: "l"(gdst), "r"(__float_as_uint(m)), "r"(tagged(v, ep)), "r"((uint32_t)cond) : "memory");
}
__device__ __forceinline__ void put_partial(const float (&v)[64], float2* gdst, float z, uint32_t ep) {
  float s[4] = {z, z, z, z}, q[4] = {z, z, z, z};
#pragma unroll
  for (int x = 0; x < 64; x++) { s[x & 3] += v[x]; q[x & 3] = fmaf(v[x], v[x], q[x & 3]); }
  const bool odd = threadIdx.x & 1;
  const float s0 = s[0] + s[1], s1 = s[2] + s[3], q0 = q[0] + q[1], q1 = q[2] + q[3];
  float ss = (odd ? s1 : s0) + __shfl_xor_sync(0xffffffffu, odd ? s0 : s1, 1);
  float qq = (odd ? q1 : q0) + __shfl_xor_sync(0xffffffffu, odd ? q0 : q1, 1);
  ss += __shfl_xor_sync(0xffffffffu, ss, 2);
  qq += __shfl_xor_sync(0xffffffffu, qq, 2);
  put_stat(gdst + (odd ? 8 : 0), ss, qq, !(threadIdx.x & 2), ep);
}
struct RowStats {
  float2 p[4];
  __device__ __forceinline__ void load(const float2* r0, const float2* r1) {
#pragma unroll
    for (int x = 0; x < 4; x++)
      asm volatile("ld.relaxed.gpu.global.v2.f32 {%0,%1}, [%2];" : "=f"(p[x].x), "=f"(p[x].y) : "l"((x & 2 ? r1 : r0) + (x & 1) * SEQ) : "memory");
  }
  __device__ __forceinline__ void finish(const float2* r0, const float2* r1, int& budget, float2& s0, float2& s1) {
#pragma unroll 1
    while (!__all_sync(0xffffffffu, both_valid(__float_as_uint(p[0].y), __float_as_uint(p[1].y), 0) & both_valid(__float_as_uint(p[2].y), __float_as_uint(p[3].y), 0) & 1)) {
      if (--budget <= 0) break;
      load(r0, r1);
    }
#pragma unroll
    for (int h = 0; h < 2; h++) {
      const float2 a = p[2 * h], b = p[2 * h + 1];
      float m = a.x + b.x;
      m += __shfl_xor_sync(0xffffffffu, m, 1);
      m += __shfl_xor_sync(0xffffffffu, m, 2);
      m *= 0.125f;
      const float ea = a.x - m, eb = b.x - m;
      float t = fmaf(fmaf(ea, ea, eb * eb), 128.f, a.y + b.y);
      t += __shfl_xor_sync(0xffffffffu, t, 1);
      t += __shfl_xor_sync(0xffffffffu, t, 2);
      (h ? s1 : s0) = make_float2(m, rsqrt_fast(fmaf(t, 1.f / DM, LN_EPS)));
    }
  }
};

__device__ __forceinline__ void emit_panel(const uint32_t* v, char* gp, uint32_t pub) {
#pragma unroll
  for (int t = 0; t < 8; t++) { stg32(gp + t * CB_BYTES, v[2 * t]); stg32(gp + t * CB_BYTES + 128, v[2 * t + 1]); }
  __syncwarp();
  mbar_arrive_if(pub, (threadIdx.x & 31) == 0);
}
template <int NT>
__device__ __forceinline__ void stage_tiles(const uint32_t* v, uint32_t sp) {
#pragma unroll
  for (int t = 0; t < NT; t += 2) stsm_x4(sp + t * 1024, v[2 * t], v[2 * t + 1], v[2 * t + 2], v[2 * t + 3]);
}

__device__ __forceinline__ float late_zero(uint32_t addr) {
  float z; asm volatile("ld.volatile.shared.f32 %0, [%1];" : "=f"(z) : "r"(addr) : "memory"); return z;
}

template <int NT>
__device__ __forceinline__ void fold_tiles(uint32_t* v, const float* acc, const float2* cs_ptr, float2 st0, float2 st1) {
  const float n0 = -st0.x * st0.y, n1 = -st1.x * st1.y;
#pragma unroll
  for (int tile = 0; tile < NT; tile++) {
    const float2 cs = cs_ptr[tile * 4];
    float a = fmaf(acc[4 * tile + 0], st0.y, n0 * cs.x), b = fmaf(acc[4 * tile + 1], st0.y, n0 * cs.y);
    float cc = fmaf(acc[4 * tile + 2], st1.y, n1 * cs.x), d = fmaf(acc[4 * tile + 3], st1.y, n1 * cs.y);
    v[2 * tile] = pack_bf16(gelu_from_half(a), gelu_from_half(b));
    v[2 * tile + 1] = pack_bf16(gelu_from_half(cc), gelu_from_half(d));
  }
}

__device__ __forceinline__ void move_reg(uint32_t& d, uint32_t s) { asm volatile("mov.b32 %0, %1;" : "=r"(d) : "r"(s)); }
__device__ __forceinline__ void move_reg(float& d, float s) { asm volatile("mov.f32 %0, %1;" : "=f"(d) : "f"(s)); }
template <int CH, int LO, int HI, class T, int NR>
__device__ __forceinline__ void pick_group(T (&held)[NR], int idx) {
  if constexpr (HI - LO == 1) {
#pragma unroll
    for (int x = 0; x < CH; x++) move_reg(held[x], held[CH * LO + x]);
  } else {
    constexpr int MID = (LO + HI) / 2;
    if (idx < MID) pick_group<CH, LO, MID>(held, idx); else pick_group<CH, MID, HI>(held, idx);
  }
}
template <int CH>
__device__ __forceinline__ void gelu_chunk(const uint32_t* t, char* gp) {
#pragma unroll
  for (int x = 0; x < CH; x++) stg32(gp + (x >> 1) * CB_BYTES + (x & 1) * 128, gelu_pair_f16(t[x]));
}

#define REG_CONS 216
#define REG_PROD 72
__global__ void __cluster_dims__(2, 1, 1) __launch_bounds__(384, 1)
fused_kernel(const __grid_constant__ Params maps) {
  extern __shared__ __align__(1024) char smem[];
  const int tid = threadIdx.x, lane = tid & 31;
  const int warp = __shfl_sync(0xffffffffu, tid >> 5, 0), wg = warp >> 2;
  if (tid == 0) STAMP(48);
  const uint32_t sm0 = opaque(smem_u32(smem));
  if (elect_one()) {
    if (warp == 8) {
#pragma unroll
      for (int x = 0; x < CB_Q1; x++) mbar_init(sm0 + CV_BAR + 8 * x, 1);
      asm volatile("fence.mbarrier_init.release.cluster;" ::: "memory");
      load_k(maps, sm0, 0);
#pragma unroll
      for (int y = 0; y < 2; y++) {
        mbar_expect_tx(sm0 + CV_BAR + 8 * (CB_QA + y), 8192);
        load_kv(maps, sm0, y, CB_QA + y);
      }
#pragma unroll
      for (int x = CB_Q1; x < CB_ST0; x++) mbar_init(sm0 + CV_BAR + 8 * x, x < CB_QS ? 1 : x == CB_QS ? 8 : 3);
    } else if (warp == 9) {
#pragma unroll
      for (int x = CB_ST0; x < CB_COUNT; x++) mbar_init(sm0 + CV_BAR + 8 * x, x < CB_Y0 ? 3 : x < CB_P2 ? 8 : x == CB_P2 ? 10 : x == CB_YOUT ? 5 : x < CB_STAT ? 2 : 1);
    } else if (warp < 2) {
      asm volatile("prefetch.tensormap [%0];" :: "l"(&maps.m[M_K + warp]) : "memory");
    }
#pragma unroll
    for (int x = 0; x < 7; x++) mbar_init(sm0 + SM_BAR + 56 * warp + 8 * x, 1 << wg);
    asm volatile("fence.mbarrier_init.release.cluster;" ::: "memory");
    if (warp == 11) sts32(sm0 + SM_ZERO, 0);
  }
  static_assert(BAR_END == 84, "start-up work of 12 warps");
  __syncwarp();
  if (warp != 8) asm volatile("barrier.cluster.arrive.relaxed.aligned;" ::: "memory");
  conv_part(maps, sm0, warp);
  __syncwarp();
  asm volatile("barrier.cluster.wait.acquire.aligned;" ::: "memory");
  Ctx c;
  c.sm = sm0;
  c.bar = c.sm + SM_BAR;
  c.r = blockIdx.x & 1;
  {
    uint32_t role;
    asm volatile("ld.shared::cluster.u32 %0, [%1];" : "=r"(role) : "r"(mapa(sm0 + SM_ROLE, 0)) : "memory");
    role = __shfl_sync(0xffffffffu, role, 0);
    c.i = role >> 2; c.j = (role & 3) * 2 + c.r;
    c.bid = c.i * 8 + c.j;
    asm volatile("ld.shared.u32 %0, [%1];" : "=r"(c.ep) : "r"(c.sm + SM_EPOCH) : "memory");
  }

  if (tid == 0) MSTAMP(45);
  if (wg == 2) {
    reg_dealloc<REG_PROD>();
    int budget = SPIN_LIMIT;
    if (warp == 8) {
      const int hh = 16 * c.r + c.i;
      const uint32_t full0 = c.bar + 8 * (BAR_FULLA + c.r * 8), empty0 = c.bar + 8 * (BAR_EMPTYA + c.r * 9), full_peer = mapa(full0, c.r ^ 1);
      const uint32_t ring0 = c.sm + SM_A + c.r * NA * A_SLOT;
      const int nb = hh + (lane & 8 ? (lane & 2) - 1 : 0);
      const uint32_t* lf = g_flag + ((nb >= 0 && nb < 32 ? nb : hh) * 8 + (lane & 7)) * FS;
      const uint32_t* xf = g_xcnt + (hh + ((c.j >> 1) & 1) >= 16 ? 16 : 0) + (lane & 15);
      const uint32_t cb = c.sm + CV_BAR;
      if (lane == 0) mbar_arrive(cb + 8 * CB_XFREE);
      mbar_wait(cb + 8 * CB_Y2, 0, budget);
      if (lane == 0) STAMP(60);
      mbar_wait(cb + 8 * CB_P1, 0, budget);
      fence_async_smem();
      if (lane < 2) mbar_arrive_cluster(mapa(cb + 8 * CB_EARLY, lane));
      int seen = ld_relaxed(xf) - 8 * c.ep;
      mbar_wait(cb + 8 * (CB_EARLY + c.r), 0, budget);
      fence_async_global();
      if (lane == 0) MSTAMP(46);
      uint32_t slot = ring0;
      int k = 0;
#pragma unroll 1
      for (int ph = 0; ph < 10; ph++) {
        const int l = ph >= 5, s = ph - 5 * l;
        const CUtensorMap* m = &maps.m[s == 0 ? M_X3S + l : s == 1 ? M_H + l : s == 4 ? M_HID : M_X1];
        const uint32_t bytes = s == l ? A_SLOT : 8192;
        const bool local = starts_local(l, s);
        const int np = ph == 0 ? 1 : s == 4 ? 7 : 2, cnt = ph == 0 ? 16 : local ? 6 : 8, e0 = ph == 0 ? 2 * (c.j & 6) : (c.j & 6) + (local ? 2 : 0);
        const int need0 = ph == 0 ? 8 : 13 * l + (s == 0 ? 1 : s == 1 ? 3 : s == 4 ? 7 : 5);
        const uint32_t up = ph == 0 ? (c.j & 2 ? 0u : 0xffffu) : ph == 6 ? 0x33u : 0u;
        const uint32_t* fp = ph == 0 ? xf : lf;
        const uint32_t base = ph == 0 ? 8 * c.ep : 32 * c.ep;
        const bool polls = lane < (s == l ? 16 : 8);
        if (ph == 1) seen = 0;
        if (local) {
          k += 4;
          slot += slot >= ring0 + (NA - 2) * A_SLOT ? (2 - NA) * A_SLOT : 2 * A_SLOT;
        }
#pragma unroll 1
        for (int p = 0; p < np; p++) {
          uint32_t ready = __ballot_sync(0xffffffffu, seen >= need0 + p);
          if (ph == 6) ready &= ready >> 8;
#pragma unroll 1
          for (int x = 0; x < cnt; x++) {
            const int e = (e0 + x) & (ph == 0 ? 15 : 7);
            const uint32_t off = 8 * (k & 7);
            mbar_wait(empty0 + 8 * ((k - NA) & 7), ((k - NA) >> 3) & 1, budget);
            if (elect_one()) {
              mbar_expect_tx(full0 + off, bytes);
              mbar_expect_tx_cluster(full_peer + off, bytes);
            }
            if (!((ready >> e) & 1)) {
#pragma unroll 1
              do {
                if (polls) seen = ld_relaxed(fp) - base;
                ready = __ballot_sync(0xffffffffu, seen >= need0 + p);
                if (ph == 6) ready &= ready >> 8;
              } while (!((ready >> e) & 1) && --budget > 0);
              fence_async_global();
            }
            if (elect_one()) tma_2d_mc(slot, m, full0 + off, 128 * hh - 8 * ((up >> e) & 1), (np * e + p) * 8, (uint16_t)3);
            slot += slot == ring0 + (NA - 1) * A_SLOT ? (1 - NA) * A_SLOT : A_SLOT;
            k++;
          }
        }
      }
    } else if (warp == 9) {
      int k0 = 0;
#pragma unroll 1
      for (int ph = 0; ph < 10; ph++) {
        const int l = ph >= 5, s = ph - 5 * l;
        const int kbytes = s == 2 ? 32 : s == 3 ? 24 : 16, slots = s == 2 ? 3 : s == 3 ? 4 : 6;
        const uint32_t dist0 = s == 2 ? 0x345u : s == 3 ? 0x4333u : s == 4 ? 0x655544u : 0x666666u;
        const CUtensorMap* m = &maps.m[M_W1 + s];
        const int np = s == 4 ? 7 : 2;
        const int panel0 = s == 2 ? 7 * c.j : s == 3 ? 7 * c.j + 4 : 2 * c.j;
        const bool local = starts_local(l, s);
        int slot = first_slot(s);
#pragma unroll 1
        for (int n = 0; n < 8 * np; n++) {
          int kb;
          if (ph == 0) kb = (2 * (c.j & 6) + n) & 15;
          else if (!local) kb = np * (((c.j & 6) + n) & 7) + (n >> 3);
          else if (n < 4) kb = (2 * c.j) ^ n;
          else kb = 2 * (((c.j & 6) + n + (n >= 10 ? 0 : 6)) & 7) + (n >= 10);
          const int last = k0 + n - (n < slots ? (int)((dist0 >> (4 * n)) & 15) : slots);
          if (last < 0) {
            mbar_wait(c.sm + CV_BAR + 8 * (n < XFREE_N ? CB_XFREE : n < 5 ? CB_EARLY : CB_YOUT), 0, budget);
            fence_async_smem();
          }
          mbar_wait(c.bar + 8 * (BAR_EMPTYB + (last & 7)), (last >> 3) & 1, budget);
          if (elect_one()) {
            const uint32_t bar = c.bar + 8 * (BAR_FULLB + (n & 7));
            mbar_expect_tx(bar, kbytes * 1024);
            tma_3d(c.sm + SM_B + slot * kbytes * 1024, m, bar, 0, kb * 64, panel0);
          }
          __syncwarp();
          if (++slot == slots) slot = 0;
        }
        k0 += 8 * np;
      }
    } else {
      const int w = warp - 10;
      const int row0 = 64 * (16 * w + c.i);
      mbar_wait(c.sm + CV_BAR + 8 * CB_P2, 0, budget);
      if (w == 0) {
        fence_async_smem();
        if (lane < 2) mbar_arrive_cluster(mapa(c.sm + CV_BAR + 8 * CB_LATE, lane));
      } else if (elect_one()) {
        red_release(&g_xcnt[16 + (blockIdx.x >> 3)]);
        mbar_arrive(c.bar + 8 * BAR_REL);
        MSTAMP(44);
      }
      __syncwarp();
      uint32_t* my_flag = g_flag + ((16 * w + c.i) * 8 + c.j) * FS;
#pragma unroll 1
      for (int pc = 1; pc < 26; pc++) {
        const int l = pc >= 13, u = pc - 13 * l;
        if (pc > 1) {
          if (pc == 8) { reinterpret_cast<uint4*>(&g_part[2][c.j][row0])[lane] = make_uint4(0, 0, 0, 0); __syncwarp(); }
          mbar_wait(c.bar + 8 * (BAR_PUB + 13 * w + u), u < 2 ? 0 : l, budget);
          st_release(my_flag, 32 * c.ep + pc + 1);
        }
        if (pc == 12 && elect_one()) {
          const uint32_t bar = c.bar + 8 * (BAR_OWN + w);
          fence_async_global();
          mbar_expect_tx(bar, 16384);
          tma_2d(c.sm + SM_X + w * 16384, &maps.m[M_Y], bar, 2 * row0, 16 * c.j);
          tma_2d(c.sm + SM_X + w * 16384 + 8192, &maps.m[M_Y], bar, 2 * row0, 16 * c.j + 8);
        }
        __syncwarp();
        float2* part = &g_part[3 * l + (u == 5)][0][0];
#pragma unroll 1
        for (uint32_t jobs = pc == 1 ? 0x453u : u == 5 ? 0x421u : u == 1 ? 4u : 0u; jobs; jobs >>= 4) {
          const int job = jobs & 15;
          if (job < 3) {
            const int r = 32 * (job - 1) + lane;
            float s0 = 0.f, s1 = 0.f, q0 = 0.f, q1 = 0.f;
#pragma unroll 2
            for (int x = 0; x < 16; x++) {
              uint32_t v[4];
              asm volatile("ld.shared.v4.u32 {%0,%1,%2,%3}, [%4];" : "=r"(v[0]), "=r"(v[1]), "=r"(v[2]), "=r"(v[3])
                           : "r"(c.sm + SM_X + w * 16384 + x * 1024 + r * 16) : "memory");
#pragma unroll
              for (int y = 0; y < 4; y++) {
                const float a = bf_lo(v[y]), b = bf_hi(v[y]);
                s0 += a; s1 += b; q0 = fmaf(a, a, q0); q1 = fmaf(b, b, q1);
              }
            }
            put_stat(part + c.j * SEQ + row0 + r, s0 + s1, q0 + q1, true, c.ep);
          } else if (job == 3) {
            if (w == 1) {
              mbar_wait(c.sm + CV_BAR + 8 * CB_YOUT, 0, budget);
              mbar_wait(c.sm + CV_BAR + 8 * CB_EARLY, 0, budget);
              if (lane == 0) red_release(&g_xcnt[32 + (blockIdx.x >> 3)]);
              __syncwarp();
            }
            uint32_t xseen;
#pragma unroll 1
            do {
              asm volatile("ld.acquire.gpu.global.u32 %0, [%1];" : "=r"(xseen) : "l"(g_xcnt + 32 + (lane & 15)) : "memory");
            } while (!__all_sync(0xffffffffu, (int)(xseen - 8 * c.ep) >= 8) && --budget > 0);
            if (w == 0) {
              float4 s = make_float4(0.f, 0.f, 0.f, 0.f);
#pragma unroll
              for (int x = 0; x < 4; x++) {
                const float4 v = __ldcg(reinterpret_cast<const float4*>(&g_cs1[x][c.j * 128]) + lane);
                s.x += v.x; s.y += v.y; s.z += v.z; s.w += v.w;
              }
              reinterpret_cast<float4*>(smem + SM_CS1)[lane] = s;
            } else {
#pragma unroll
              for (int x = 0; x < 4; x++) {
                const int y = min(32 * x + lane, 111);
                const float4 v = __ldcg(reinterpret_cast<const float4*>(g_cs3 + c.j * 448) + y);
                if (x < 2) {
                  uint32_t* d = reinterpret_cast<uint32_t*>(smem + SM_CS3) + (y >> 2) * 8 + (y & 1) * 4 + ((y >> 1) & 1);
                  d[0] = pack_f16(v.x, v.y); d[2] = pack_f16(v.z, v.w);
                } else {
                  reinterpret_cast<float4*>(smem + SM_CS3)[y] = v;
                }
              }
            }
            __syncwarp();
            if (lane == 0) {
              mbar_arrive(c.bar + 8 * BAR_CS);
              if (c.bid == 0 && w == 0) { g_epoch = c.ep + 1; *reinterpret_cast<uint4*>(g_role) = make_uint4(0, 0, 0, 0); }
            }
          } else {
            const int r = job == 4 ? 2 * lane : token_shift(c.j) > 0 ? 64 : -2;
            const float2* src = part + min(max(row0 + r, 0), SEQ - 2);
            float4 v[8];
#pragma unroll 1
            do {
              uint32_t ok = 1;
#pragma unroll
              for (int x = 0; x < 8; x++) {
                asm volatile("ld.relaxed.gpu.global.v4.f32 {%0,%1,%2,%3}, [%4];" : "=f"(v[x].x), "=f"(v[x].y), "=f"(v[x].z), "=f"(v[x].w) : "l"(src + x * SEQ) : "memory");
                ok &= both_valid(__float_as_uint(v[x].y), __float_as_uint(v[x].w), c.ep);
              }
              if (__all_sync(0xffffffffu, ok)) break;
            } while (--budget > 0);
            float ma = 0.f, mb = 0.f, ta = 0.f, tb = 0.f;
#pragma unroll
            for (int x = 0; x < 8; x++) { ma += v[x].x; mb += v[x].z; }
            ma *= 0.125f; mb *= 0.125f;
#pragma unroll
            for (int x = 0; x < 8; x++) {
              const float ea = v[x].x - ma, eb = v[x].z - mb;
              ta += fmaf(128.f * ea, ea, __uint_as_float(__float_as_uint(v[x].y) | 1u));
              tb += fmaf(128.f * eb, eb, __uint_as_float(__float_as_uint(v[x].w) | 1u));
            }
            *reinterpret_cast<float4*>(smem + SM_RS + (68 * w + 2 + r) * 8) =
                make_float4(ma, rsqrt_fast(fmaf(ta, 1.f / DM, LN_EPS)), mb, rsqrt_fast(fmaf(tb, 1.f / DM, LN_EPS)));
            __syncwarp();
            if (job == 4 && lane == 0) mbar_arrive(c.sm + CV_BAR + 8 * (CB_STAT + w));
          }
        }
      }
    }
    cluster_exit_barrier();
  } else {
    reg_alloc<REG_CONS>();
#define WSTAMP(idx) do {} while (0)
    const int t = tid & 127, g = lane >> 2, qd = lane & 3;
    const int wrow = 64 * (16 * wg + c.i) + (t >> 5) * 16, row = wrow + g;
    const uint32_t frag = row * 16 + qd * 4 + c.j * 16 * CB_BYTES;
    const uint32_t stage = c.sm + SM_X + wg * 16384 + (lane >> 4) * 1024 + ((t >> 5) * 16 + (lane & 15)) * 16;
    const uint32_t pub = c.bar + 8 * (BAR_PUB + 13 * wg);
    const uint32_t rstat = c.sm + SM_RS + (68 * wg + 2 + (t >> 5) * 16 + g) * 8;
    Pipe p;
    p.ko = 0; p.kp = 0; p.po = 64; p.turn = 0; p.budget = SPIN_LIMIT;
    p.a0 = desc_a(c, SM_A) + wg * NA * (A_SLOT >> 4); p.a1 = p.a0 + (A_SLOT >> 4); p.ar = p.a1 + (A_SLOT >> 4);
    p.signals = t == 0 || t == 32 || t == 64;
    p.rel = mapa(c.bar + 8 * (t == 64 ? BAR_EMPTYB : BAR_EMPTYA + wg * 9), t == 32 ? c.r ^ 1 : c.r);
    auto fence_sched = [&]() { mbar_wait(c.bar + 8 * BAR_CS, 0, p.budget); };
    uint32_t x3[32];
    float acc[64];
#pragma unroll
    for (int x = 0; x < 64; x++) acc[x] = 0.f;
    WSTAMP(0);
    if (wg == 1) {
      mbar_wait(c.bar + 8 * BAR_REL, 0, p.budget);
#pragma unroll 2
      for (int x = 0; x < 8; x++)
        reinterpret_cast<uint4*>(g_y)[blockIdx.x * 2048 + 1024 + x * 128 + t] = reinterpret_cast<const uint4*>(smem + CV_K + 128 + 16384)[x * 128 + t];
      __syncwarp();
      mbar_arrive_if(c.sm + CV_BAR + 8 * CB_YOUT, lane == 0);
    }
    {
      mbar_wait(c.bar + 8 * (BAR_FULLA + 8 * wg + 2 * c.r), 0, p.budget);
      mbar_wait(c.bar + 8 * (BAR_FULLA + 8 * wg + 2 * c.r + 1), 0, p.budget);
      const uint32_t own = c.sm + SM_A + (wg * NA + 2 * c.r) * A_SLOT + (lane >> 4) * 1088 + ((token_shift(c.j) < 0 ? 4 : 0) + (t >> 5) * 16 + (lane & 15)) * 16;
      float sum[4] = {0.f, 0.f, 0.f, 0.f}, lo[4] = {0.f, 0.f, 0.f, 0.f}, hi[4] = {0.f, 0.f, 0.f, 0.f};
#pragma unroll
      for (int x = 0; x < 32; x += 4) {
        ldsm_x4(own + x * 544, x3[x], x3[x + 1], x3[x + 2], x3[x + 3]);
        mma16816(sum, x3[x], x3[x + 1], x3[x + 2], x3[x + 3], 0x3f803f80u, 0x3f803f80u);
        mma16816(lo, x3[x], x3[x + 1], x3[x + 2], x3[x + 3], x3[x], x3[x + 2]);
        mma16816(hi, x3[x], x3[x + 1], x3[x + 2], x3[x + 3], x3[x + 1], x3[x + 3]);
      }
      put_stat(&g_part[0][c.j][row], sum[0], (g & 1) ? lo[1] : lo[0], qd == (g >> 1), c.ep);
      put_stat(&g_part[0][c.j][row + 8], sum[2], (g & 1) ? hi[3] : hi[2], qd == (g >> 1), c.ep);
    }
#pragma unroll 1
    for (int ph = 0; ph < 6; ph++) {
      const int l = ph >= 3, s = ph - 3 * l;
      if (s < 2) {
        if (s == 0) WSTAMP(1 + 16 * l);
        gemm_begin<128>(c, wg, warp & 3, p, s, s != l);
        p.keep = s;
      } else {
        const uint32_t park = c.sm + SM_X + wg * 16384 + t * 16;
        char* hp = reinterpret_cast<char*>(g_hid) + frag + c.j * 40 * CB_BYTES;
        uint32_t held[64];
        float acc3[128];
        gemm_step<256, true>(acc3, c, wg, p, Nop());
        float2 s0, s1;
        gemm_steps<256, false>(acc3, c, wg, p, 15, [&]() {
          mbar_wait(c.sm + CV_BAR + 8 * (CB_STAT + wg), 1, p.budget);
          s0 = lds_f2(rstat); s1 = lds_f2(rstat + 64);
          s0.y *= 0.5f; s1.y *= 0.5f;
#pragma unroll
          for (int x = 0; x < 8; x++) sts128(park + x * 2048, make_uint4(x3[4 * x], x3[4 * x + 1], x3[4 * x + 2], x3[4 * x + 3]));
        }, Nop());
        WSTAMP(6 + 16 * l);
#pragma unroll
        for (int x = 0; x < 64; x++) held[x] = pack_f16(acc3[2 * x] * ((x & 1) ? s1.y : s0.y), acc3[2 * x + 1] * ((x & 1) ? s1.y : s0.y));
        const uint32_t n0 = pack_f16(-s0.x * s0.y, -s0.x * s0.y), n1 = pack_f16(-s1.x * s1.y, -s1.x * s1.y);
        float accb[96];
#pragma unroll
        for (int x = 0; x < 24; x++) {
          const float2 cs = (reinterpret_cast<const float2*>(smem + SM_CS3 + 1024) + qd)[4 * x];
          accb[4 * x] = -s0.x * cs.x; accb[4 * x + 1] = -s0.x * cs.y; accb[4 * x + 2] = -s1.x * cs.x; accb[4 * x + 3] = -s1.x * cs.y;
        }
        pin(accb);
        WSTAMP(7 + 16 * l);
        gemm_begin<192>(c, wg, warp & 3, p, 3, false);
#pragma unroll 1
        for (int pn = 0; pn < 4; pn++) {
#pragma unroll
          for (int u = 0; u < 4; u++)
            gemm_step<192, false>(accb, c, wg, p, [&]() {
              const uint2 cs = reinterpret_cast<const uint2*>(smem + SM_CS3)[16 * pn + 4 * u + qd];
              const uint32_t h[4] = {hfma2(cs.x, n0, held[4 * u]), hfma2(cs.x, n1, held[4 * u + 1]), hfma2(cs.y, n0, held[4 * u + 2]), hfma2(cs.y, n1, held[4 * u + 3])};
              gelu_chunk<4>(h, hp + 2 * u * CB_BYTES);
            });
          hp += 8 * CB_BYTES;
          __syncwarp();
          mbar_arrive_if(pub + 8 * (6 + pn), lane == 0);
          pick_group<16, 1, 4>(held, pn + 1);
        }
        WSTAMP(8 + 16 * l);
#pragma unroll
        for (int x = 0; x < 8; x++) {
          uint4 v;
          asm volatile("ld.shared.v4.u32 {%0,%1,%2,%3}, [%4];" : "=r"(v.x), "=r"(v.y), "=r"(v.z), "=r"(v.w) : "r"(park + x * 2048) : "memory");
          acc[8 * x] = bf_lo(v.x); acc[8 * x + 1] = bf_hi(v.x); acc[8 * x + 2] = bf_lo(v.y); acc[8 * x + 3] = bf_hi(v.y);
          acc[8 * x + 4] = bf_lo(v.z); acc[8 * x + 5] = bf_hi(v.z); acc[8 * x + 6] = bf_lo(v.w); acc[8 * x + 7] = bf_hi(v.w);
        }
        pin(acc);
        WSTAMP(9 + 16 * l);
        gemm_begin<128>(c, wg, warp & 3, p, 4, false);
        gemm_step<128, false>(acc, c, wg, p, Nop());
        pin(accb);
#pragma unroll 1
        for (int hpn = 0; hpn < 6; hpn++) {
#pragma unroll
          for (int u = 0; u < 4; u++)
            gemm_step<128, false>(acc, c, wg, p, [&]() {
              const uint32_t h[2] = {pack_f16(accb[4 * u] * s0.y, accb[4 * u + 1] * s0.y), pack_f16(accb[4 * u + 2] * s1.y, accb[4 * u + 3] * s1.y)};
              gelu_chunk<2>(h, hp + u * CB_BYTES);
            });
          hp += 4 * CB_BYTES;
          __syncwarp();
          mbar_arrive_if(pub + 8 * (10 + (hpn >> 1)), (hpn & 1) && lane == 0);
          pick_group<16, 1, 6>(accb, hpn + 1);
        }
        WSTAMP(12 + 16 * l);
        p.keep = 1;
#pragma unroll
        for (int x = 0; x < 32; x++) x3[x] = 0;
      }
      p.sh = ph == 0 ? (token_shift(c.j) & 3) * 0x55555555u : ph == 4 ? __funnelshift_r(0xaa5faa5fu, 0xaa5faa5fu, 2 * (c.j & 6)) : 0;
      p.wide = s == l ? 4 : 0;
      float2 s0 = make_float2(0.f, 0.f), s1 = s0;
      gemm_steps<128, true, true>(acc, c, wg, p, s == 2 ? 31 : 16, Nop(), [&]() {
        if (s == 0) {
          const int sh = l == 0 ? token_shift(c.j) : 0;
          mbar_wait(c.sm + CV_BAR + 8 * (CB_STAT + wg), 0, p.budget);
          s0 = lds_f2(rstat + 8 * sh); s1 = lds_f2(rstat + 8 * sh + 64);
          s0.y *= (row + sh < 0 ? 0.f : 0.5f) * rsqrt_fast(fmaxf(fmaf(-LN_EPS * s0.y, s0.y, 1.f), 0.f) + LN_EPS);
          s1.y *= (row + sh + 8 >= SEQ ? 0.f : 0.5f) * rsqrt_fast(fmaxf(fmaf(-LN_EPS * s1.y, s1.y, 1.f), 0.f) + LN_EPS);
          fence_sched();
        }
      });
      WSTAMP((s == 2 ? 10 : 2 + 2 * s) + 16 * l);
      if (s == 0) {
#pragma unroll
        for (int pn = 0; pn < 2; pn++) {
          uint32_t v[16];
          if (pn == 0) {
            fold_tiles<4>(v, acc, reinterpret_cast<const float2*>(smem + SM_CS1) + qd, s0, s1);
#pragma unroll
            for (int x = 0; x < 8; x++) stg32(reinterpret_cast<char*>(g_h) + frag + (x >> 1) * CB_BYTES + (x & 1) * 128, v[x]);
            fence_sched();
            fold_tiles<4>(v + 8, acc + 16, reinterpret_cast<const float2*>(smem + SM_CS1) + qd + 16, s0, s1);
#pragma unroll
            for (int x = 8; x < 16; x++) stg32(reinterpret_cast<char*>(g_h) + frag + (x >> 1) * CB_BYTES + (x & 1) * 128, v[x]);
            __syncwarp();
            mbar_arrive_if(pub + 8 * 2, lane == 0);
          } else {
            fold_tiles<8>(v, acc + 32, reinterpret_cast<const float2*>(smem + SM_CS1) + qd + 32, s0, s1);
            emit_panel(v, reinterpret_cast<char*>(g_h) + frag + 8 * CB_BYTES, pub + 8 * 3);
          }
          if (l == 0) stage_tiles<8>(v, stage + pn * 8192);
        }
        s0 = lds_f2(rstat); s1 = lds_f2(rstat + 64);
        const float nb0 = -s0.x * s0.y, nb1 = -s1.x * s1.y;
#pragma unroll
        for (int x = 0; x < 32; x++) {
          acc[2 * x] = fmaf(bf_lo(x3[x]), (x & 1) ? s1.y : s0.y, (x & 1) ? nb1 : nb0);
          acc[2 * x + 1] = fmaf(bf_hi(x3[x]), (x & 1) ? s1.y : s0.y, (x & 1) ? nb1 : nb0);
        }
        WSTAMP(3 + 16 * l);
      } else if (s == 1) {
        uint32_t v[32];
#pragma unroll
        for (int x = 0; x < 32; x++) v[x] = pack_bf16(acc[2 * x], acc[2 * x + 1]);
        emit_panel(v, reinterpret_cast<char*>(g_x1) + frag, pub + 8 * 4);
        stage_tiles<16>(v, stage);
        gemm_begin<256>(c, wg, warp & 3, p, 2, true);
        emit_panel(v + 16, reinterpret_cast<char*>(g_x1) + frag + 8 * CB_BYTES, pub + 8 * 5);
#pragma unroll
        for (int x = 0; x < 32; x++) x3[x] = badd2(x3[x], v[x]);
        WSTAMP(5 + 16 * l);
      } else if (l == 0) {
        put_partial(acc, &g_part[2][c.j][row], 0.f, 0);
        WSTAMP(11);
        const float2* sp = &g_part[2][2 * qd][row];
        RowStats rs;
        rs.load(sp, sp + 8);
        float yf[64];
        mbar_wait(c.bar + 8 * (BAR_OWN + wg), 0, p.budget);
#pragma unroll
        for (int x = 0; x < 16; x++) {
          uint32_t y0, y1;
          asm volatile("ld.shared.v2.u32 {%0,%1}, [%2];" : "=r"(y0), "=r"(y1) : "r"(c.sm + SM_X + wg * 16384 + x * 1024 + t * 8) : "memory");
          yf[4 * x] = bf_lo(y0); yf[4 * x + 1] = bf_hi(y0); yf[4 * x + 2] = bf_lo(y1); yf[4 * x + 3] = bf_hi(y1);
        }
        pin(yf);
        rs.finish(sp, sp + 8, p.budget, s0, s1);
        WSTAMP(13);
        float nb0 = -s0.x * s0.y, nb1 = -s1.x * s1.y;
#pragma unroll
        for (int pn = 0; pn < 2; pn++) {
          if (pn == 1) { const float z = late_zero(c.sm + SM_ZERO); nb0 += z; nb1 += z; }
#pragma unroll
          for (int x = 16 * pn; x < 16 * pn + 16; x++) {
            const float r = (x & 1) ? s1.y : s0.y, nb = (x & 1) ? nb1 : nb0;
            acc[2 * x] = fmaf(fmaf(acc[2 * x], r, nb), yf[2 * x], acc[2 * x]);
            acc[2 * x + 1] = fmaf(fmaf(acc[2 * x + 1], r, nb), yf[2 * x + 1], acc[2 * x + 1]);
            x3[x] = pack_bf16(acc[2 * x], acc[2 * x + 1]);
          }
          if (pn == 1) {
            stage_tiles<16>(x3, stage);
            put_partial(acc, &g_part[3][c.j][row], late_zero(c.sm + SM_ZERO), c.ep);
          }
          emit_panel(x3 + 16 * pn, reinterpret_cast<char*>(g_x3[1]) + frag + pn * 8 * CB_BYTES, pub + 8 * pn);
        }
      }
    }
#pragma unroll
    for (int x = 0; x < 32; x++) x3[x] = pack_bf16(acc[2 * x], acc[2 * x + 1]);
    {
      const uint32_t ob = c.sm + SM_X + warp * 4096, oa = ob + (lane & 15) * 128 + (((lane >> 4) ^ (lane & 7)) << 4);
#pragma unroll
      for (int x = 0; x < 16; x += 2) stsm_x4((oa + (x >> 3) * 2048) ^ ((x & 7) << 4), x3[2 * x], x3[2 * x + 1], x3[2 * x + 2], x3[2 * x + 3]);
      fence_async_smem();
      __syncwarp();
      if (lane == 0) {
        tma_store_2d(&maps.m[M_OUT], ob, c.j * 128, wrow);
        tma_store_2d(&maps.m[M_OUT], ob + 2048, c.j * 128 + 64, wrow);
        bulk_commit();
        asm volatile("cp.async.bulk.wait_group.read 0;" ::: "memory");
      }
    }
    WSTAMP(27);
    cluster_exit_barrier();
    WSTAMP(30);
  }
}

typedef CUresult (*EncodeFn)(CUtensorMap*, CUtensorMapDataType, cuuint32_t, void*, const cuuint64_t*, const cuuint64_t*, const cuuint32_t*,
                             const cuuint32_t*, CUtensorMapInterleave, CUtensorMapSwizzle, CUtensorMapL2promotion, CUtensorMapFloatOOBfill);

void encode(EncodeFn fn, CUtensorMap* m, CUtensorMapDataType type, const void* ptr, int rank, const cuuint64_t* dims, const cuuint64_t* strides,
            const cuuint32_t* box, CUtensorMapSwizzle swizzle, CUtensorMapL2promotion promo = CU_TENSOR_MAP_L2_PROMOTION_L2_128B) {
  const cuuint32_t es[3] = {1, 1, 1};
  fn(m, type, rank, const_cast<void*>(ptr), dims, strides, box, es, CU_TENSOR_MAP_INTERLEAVE_NONE, swizzle, promo, CU_TENSOR_MAP_FLOAT_OOB_FILL_NONE);
}
void map_act(EncodeFn fn, CUtensorMap* m, const void* ptr, int cols, int rows = 64) {
  const cuuint64_t dims[2] = {(cuuint64_t)SEQ * 2, (cuuint64_t)cols / 8}, st[1] = {(cuuint64_t)CB_BYTES};
  const cuuint32_t box[2] = {(cuuint32_t)rows * 2, 8};
  encode(fn, m, CU_TENSOR_MAP_DATA_TYPE_UINT64, ptr, 2, dims, st, box, CU_TENSOR_MAP_SWIZZLE_NONE);
}
void map_rows(EncodeFn fn, CUtensorMap* m, const void* ptr, int rows, int cols, int box_rows, int box_cols, CUtensorMapSwizzle swizzle,
              CUtensorMapL2promotion promo) {
  const cuuint64_t dims[2] = {(cuuint64_t)cols, (cuuint64_t)rows}, st[1] = {(cuuint64_t)cols * 2};
  const cuuint32_t box[2] = {(cuuint32_t)box_cols, (cuuint32_t)box_rows};
  encode(fn, m, CU_TENSOR_MAP_DATA_TYPE_BFLOAT16, ptr, 2, dims, st, box, swizzle, promo);
}
void map_w(EncodeFn fn, CUtensorMap* m, const void* ptr, int rows, int cols, int panels) {
  const cuuint64_t dims[3] = {64, (cuuint64_t)rows, (cuuint64_t)cols / 64}, st[2] = {(cuuint64_t)cols * 2, 128};
  const cuuint32_t box[3] = {64, 64, (cuuint32_t)panels};
  encode(fn, m, CU_TENSOR_MAP_DATA_TYPE_BFLOAT16, ptr, 3, dims, st, box, CU_TENSOR_MAP_SWIZZLE_128B);
}

}

extern "C" void kernel_launch(void* const* d_in, const int* in_sizes, int n_in, void* d_out, int out_size) {
  (void)in_sizes; (void)n_in; (void)out_size;
  const bf16* q = (const bf16*)d_in[0];
  const bf16* k = (const bf16*)d_in[1];
  const bf16* v = (const bf16*)d_in[2];
  const bf16* shift_k = (const bf16*)d_in[3];
  const bf16* ssm_k = (const bf16*)d_in[4];
  const bf16* ssm_d = (const bf16*)d_in[5];
  const bf16* w1 = (const bf16*)d_in[7];
  const bf16* w2 = (const bf16*)d_in[8];
  const bf16* w3 = (const bf16*)d_in[9];
  const bf16* w4 = (const bf16*)d_in[10];

  static EncodeFn fn = nullptr;
  static void *p_x3, *p_h, *p_x1, *p_hid, *p_y;
  if (!fn) {
    void* p = nullptr;
    cudaDriverEntryPointQueryResult qr;
    cudaGetDriverEntryPoint("cuTensorMapEncodeTiled", &p, cudaEnableDefault, &qr);
    fn = (EncodeFn)p;
    cudaGetSymbolAddress(&p_x3, g_x3);
    cudaGetSymbolAddress(&p_h, g_h);
    cudaGetSymbolAddress(&p_x1, g_x1);
    cudaGetSymbolAddress(&p_hid, g_hid);
    cudaGetSymbolAddress(&p_y, g_y);
    cudaFuncSetAttribute(fused_kernel, cudaFuncAttributeMaxDynamicSharedMemorySize, MEGA_SMEM);
  }
  Params maps;
  map_act(fn, &maps.m[M_X3B], (const bf16*)p_x3 + SEQ * DM, DM);
  map_act(fn, &maps.m[M_X3S], p_x3, DM, 68);
  map_act(fn, &maps.m[M_H], p_h, DM);
  map_act(fn, &maps.m[M_HS], p_h, DM, 68);
  map_act(fn, &maps.m[M_X1], p_x1, DM);
  map_act(fn, &maps.m[M_HID], p_hid, FF);
  map_act(fn, &maps.m[M_Y], p_y, DM);
  map_rows(fn, &maps.m[M_OUT], d_out, SEQ, DM, 16, 64, CU_TENSOR_MAP_SWIZZLE_128B, CU_TENSOR_MAP_L2_PROMOTION_L2_128B);
  map_w(fn, &maps.m[M_W1], w1, DM, DM, 2);
  map_w(fn, &maps.m[M_W2], w2, DM, DM, 2);
  map_w(fn, &maps.m[M_W3A], w3, DM, FF, 4);
  map_w(fn, &maps.m[M_W3B], w3, DM, FF, 3);
  map_w(fn, &maps.m[M_W4], w4, FF, DM, 2);

  map_rows(fn, &maps.m[M_K], k, SEQ, DM, 256, 8, CU_TENSOR_MAP_SWIZZLE_NONE, KV_PROMO);
  map_rows(fn, &maps.m[M_V], v, SEQ, DM, 256, 8, CU_TENSOR_MAP_SWIZZLE_NONE, KV_PROMO);
  map_rows(fn, &maps.m[M_Q], q, SEQ, DM, 256, 8, CU_TENSOR_MAP_SWIZZLE_NONE, KV_PROMO);
  map_rows(fn, &maps.m[M_W1C], w1, DM, DM, 256, 32, CU_TENSOR_MAP_SWIZZLE_64B, CU_TENSOR_MAP_L2_PROMOTION_L2_128B);
  map_rows(fn, &maps.m[M_W3C], w3, DM, FF, 256, 32, CU_TENSOR_MAP_SWIZZLE_64B, CU_TENSOR_MAP_L2_PROMOTION_L2_128B);
  maps.q = q; maps.shift_k = shift_k; maps.ssm_k = ssm_k; maps.ssm_d = ssm_d; maps.w2 = w2;
  fused_kernel<<<128, 384, MEGA_SMEM, cudaStreamPerThread>>>(maps);
}
```

```cpp
#include <cuda_runtime.h>
#include <cuda_bf16.h>
#include <cuda.h>
#include <stdint.h>

namespace {

typedef __nv_bfloat16 bf16;
constexpr int SEQ = 2048, DM = 1024, FF = 3584;
constexpr float LN_EPS = 1e-5f;

constexpr int CB_BYTES = SEQ * 16;
__device__ __align__(1024) bf16 g_x3[2][SEQ * DM];
__device__ __align__(1024) bf16 g_h[SEQ * DM];
__device__ __align__(1024) bf16 g_x1[SEQ * DM];
__device__ __align__(1024) bf16 g_hid[SEQ * FF];
__device__ __align__(1024) bf16 g_y[SEQ * DM];
__device__ __align__(128) float g_cs1[4][DM];
__device__ __align__(128) float g_cs3[FF];
__device__ __align__(128) uint32_t g_epoch;
__device__ __align__(128) float2 g_part[5][8][SEQ];
__device__ __align__(128) float2 g_qstat[SEQ];
__device__ __align__(128) uint32_t g_qcnt;
__device__ __align__(128) uint32_t g_xcnt[48];
constexpr int FS = 8;
__device__ __align__(128) uint32_t g_flag[32 * 8 * FS];
__device__ __align__(128) uint32_t g_role[4];

__device__ __forceinline__ uint32_t smem_u32(const void* p) { return (uint32_t)__cvta_generic_to_shared(p); }
__device__ __forceinline__ uint32_t opaque(uint32_t x) { uint32_t y; asm volatile("mov.u32 %0, %1;" : "=r"(y) : "r"(x)); return y; }
__device__ __forceinline__ void mbar_init(uint32_t bar, uint32_t cnt) { asm volatile("mbarrier.init.shared::cta.b64 [%0], %1;" :: "r"(bar), "r"(cnt)); }
__device__ __forceinline__ void mbar_expect_tx(uint32_t bar, uint32_t bytes) {
  asm volatile("mbarrier.arrive.expect_tx.shared::cta.b64 _, [%0], %1;" :: "r"(bar), "r"(bytes) : "memory");
}
__device__ __forceinline__ void mbar_expect_tx_cluster(uint32_t bar, uint32_t bytes) {
  asm volatile("mbarrier.arrive.expect_tx.shared::cluster.b64 _, [%0], %1;" :: "r"(bar), "r"(bytes) : "memory");
}
__device__ __forceinline__ void mbar_arrive_cluster(uint32_t bar) { asm volatile("mbarrier.arrive.shared::cluster.b64 _, [%0];" :: "r"(bar) : "memory"); }
__device__ __forceinline__ void mbar_arrive(uint32_t bar) { asm volatile("mbarrier.arrive.shared::cta.b64 _, [%0];" :: "r"(bar) : "memory"); }
__device__ __forceinline__ void mbar_arrive_if(uint32_t bar, bool cond) {
  asm volatile("{\n.reg .pred p;\nsetp.ne.b32 p, %1, 0;\n@p mbarrier.arrive.shared::cta.b64 _, [%0];\n}" :: "r"(bar), "r"((uint32_t)cond) : "memory");
}
constexpr int SPIN_LIMIT = 1 << 16;
__device__ __forceinline__ bool mbar_try(uint32_t bar, uint32_t parity) {
  uint32_t done;
  asm volatile("{\n.reg .pred p;\nmbarrier.try_wait.parity.shared::cta.b64 p, [%1], %2;\nselp.b32 %0, 1, 0, p;\n}"
               : "=r"(done) : "r"(bar), "r"(parity) : "memory");
  return done != 0;
}
__device__ __forceinline__ void mbar_wait(uint32_t bar, uint32_t parity, int& budget) {
#pragma unroll 1
  while (!mbar_try(bar, parity)) { if (--budget <= 0) break; }
}
__device__ __forceinline__ bool elect_one() {
  uint32_t p;
  asm volatile("{\n.reg .pred P;\nelect.sync _|P, 0xffffffff;\nselp.b32 %0, 1, 0, P;\n}" : "=r"(p));
  return p != 0;
}
__device__ __forceinline__ void fence_async_smem() { asm volatile("fence.proxy.async.shared::cta;" ::: "memory"); }
__device__ __forceinline__ void fence_async_global() { asm volatile("fence.proxy.async.global;" ::: "memory"); }
__device__ __forceinline__ void named_bar(int id, int n) { asm volatile("bar.sync %0, %1;" :: "r"(id), "r"(n) : "memory"); }
__device__ __forceinline__ uint4 ld_nc_u4(const void* p) {
  uint4 v; asm volatile("ld.global.nc.L1::no_allocate.v4.u32 {%0,%1,%2,%3}, [%4];" : "=r"(v.x), "=r"(v.y), "=r"(v.z), "=r"(v.w) : "l"(p)); return v;
}
__device__ __forceinline__ void tma_2d_mc(uint32_t dst, const CUtensorMap* m, uint32_t bar, int c0, int c1, uint16_t mask) {
  asm volatile("cp.async.bulk.tensor.2d.shared::cluster.global.mbarrier::complete_tx::bytes.multicast::cluster [%0], [%1, {%3, %4}], [%2], %5;"
               :: "r"(dst), "l"(m), "r"(bar), "r"(c0), "r"(c1), "h"(mask) : "memory");
}
__device__ __forceinline__ void tma_2d(uint32_t dst, const CUtensorMap* m, uint32_t bar, int c0, int c1) {
  asm volatile("cp.async.bulk.tensor.2d.shared::cluster.global.mbarrier::complete_tx::bytes [%0], [%1, {%3, %4}], [%2];"
               :: "r"(dst), "l"(m), "r"(bar), "r"(c0), "r"(c1) : "memory");
}
__device__ __forceinline__ void bulk_copy_cluster(uint32_t dst, uint32_t src, uint32_t bytes, uint32_t bar) {
  asm volatile("cp.async.bulk.shared::cluster.shared::cta.mbarrier::complete_tx::bytes [%0], [%1], %2, [%3];"
               :: "r"(dst), "r"(src), "r"(bytes), "r"(bar) : "memory");
}
__device__ __forceinline__ uint32_t mapa(uint32_t addr, uint32_t cta) {
  uint32_t r; asm volatile("mapa.shared::cluster.u32 %0, %1, %2;" : "=r"(r) : "r"(addr), "r"(cta)); return r;
}
__device__ __forceinline__ void bulk_store(void* dst, uint32_t src, uint32_t bytes) {
  asm volatile("cp.async.bulk.global.shared::cta.bulk_group [%0], [%1], %2;" :: "l"(dst), "r"(src), "r"(bytes) : "memory");
}
__device__ __forceinline__ void tma_3d(uint32_t dst, const CUtensorMap* m, uint32_t bar, int c0, int c1, int c2) {
  asm volatile("cp.async.bulk.tensor.3d.shared::cluster.global.mbarrier::complete_tx::bytes [%0], [%1, {%3, %4, %5}], [%2];"
               :: "r"(dst), "l"(m), "r"(bar), "r"(c0), "r"(c1), "r"(c2) : "memory");
}
__device__ __forceinline__ void tma_store_2d(const CUtensorMap* m, uint32_t src, int c0, int c1) {
  asm volatile("cp.async.bulk.tensor.2d.global.shared::cta.bulk_group [%0, {%2, %3}], [%1];" :: "l"(m), "r"(src), "r"(c0), "r"(c1) : "memory");
}
__device__ __forceinline__ void bulk_commit() { asm volatile("cp.async.bulk.commit_group;" ::: "memory"); }
__device__ __forceinline__ void bulk_wait_all() { asm volatile("cp.async.bulk.wait_group 0;" ::: "memory"); }
__device__ __forceinline__ void prefetch_l2(const void* p, uint32_t bytes) { asm volatile("cp.async.bulk.prefetch.L2.global [%0], %1;" :: "l"(p), "r"(bytes) : "memory"); }
__device__ __forceinline__ void cluster_exit_barrier() {
  __syncwarp();
  asm volatile("barrier.cluster.arrive.relaxed;\nbarrier.cluster.wait;" ::: "memory");
}
__device__ __forceinline__ void wg_fence() { asm volatile("wgmma.fence.sync.aligned;" ::: "memory"); }
__device__ __forceinline__ void wg_commit() { asm volatile("wgmma.commit_group.sync.aligned;" ::: "memory"); }
template <int N> __device__ __forceinline__ void wg_wait() { asm volatile("wgmma.wait_group.sync.aligned %0;" :: "n"(N) : "memory"); }
template <int R> __device__ __forceinline__ void reg_alloc() { asm volatile("setmaxnreg.inc.sync.aligned.u32 %0;" :: "n"(R)); }
template <int R> __device__ __forceinline__ void reg_dealloc() { asm volatile("setmaxnreg.dec.sync.aligned.u32 %0;" :: "n"(R)); }
__device__ __forceinline__ void ldsm_x4(uint32_t addr, uint32_t& r0, uint32_t& r1, uint32_t& r2, uint32_t& r3) {
  asm volatile("ldmatrix.sync.aligned.m8n8.x4.shared.b16 {%0,%1,%2,%3}, [%4];" : "=r"(r0), "=r"(r1), "=r"(r2), "=r"(r3) : "r"(addr));
}
__device__ __forceinline__ void ldsm_x4_t(uint32_t addr, uint32_t& r0, uint32_t& r1, uint32_t& r2, uint32_t& r3) {
  asm volatile("ldmatrix.sync.aligned.m8n8.x4.trans.shared.b16 {%0,%1,%2,%3}, [%4];" : "=r"(r0), "=r"(r1), "=r"(r2), "=r"(r3) : "r"(addr));
}
__device__ __forceinline__ void stsm_x4(uint32_t addr, uint32_t r0, uint32_t r1, uint32_t r2, uint32_t r3) {
  asm volatile("stmatrix.sync.aligned.m8n8.x4.shared.b16 [%0], {%1,%2,%3,%4};" :: "r"(addr), "r"(r0), "r"(r1), "r"(r2), "r"(r3) : "memory");
}
__device__ __forceinline__ float2 lds_f2(uint32_t addr) { float2 v; asm volatile("ld.shared.v2.f32 {%0,%1}, [%2];" : "=f"(v.x), "=f"(v.y) : "r"(addr)); return v; }
__device__ __forceinline__ void sts16(uint32_t addr, uint16_t v) { asm volatile("st.shared.u16 [%0], %1;" :: "r"(addr), "h"(v) : "memory"); }
__device__ __forceinline__ void sts32(uint32_t addr, uint32_t v) { asm volatile("st.shared.u32 [%0], %1;" :: "r"(addr), "r"(v) : "memory"); }
__device__ __forceinline__ void sts128(uint32_t addr, uint4 v) {
  asm volatile("st.shared.v4.u32 [%0], {%1,%2,%3,%4};" :: "r"(addr), "r"(v.x), "r"(v.y), "r"(v.z), "r"(v.w) : "memory");
}
__device__ __forceinline__ void mma16816(float (&d)[4], uint32_t a0, uint32_t a1, uint32_t a2, uint32_t a3, uint32_t b0, uint32_t b1) {
  asm("mma.sync.aligned.m16n8k16.row.col.f32.bf16.bf16.f32 {%0,%1,%2,%3}, {%4,%5,%6,%7}, {%8,%9}, {%0,%1,%2,%3};"
               : "+f"(d[0]), "+f"(d[1]), "+f"(d[2]), "+f"(d[3]) : "r"(a0), "r"(a1), "r"(a2), "r"(a3), "r"(b0), "r"(b1));
}
__device__ __forceinline__ uint32_t pack_bf16(float lo, float hi) {
  uint32_t r; asm("cvt.rn.bf16x2.f32 %0, %1, %2;" : "=r"(r) : "f"(hi), "f"(lo)); return r;
}
__device__ __forceinline__ float bf_lo(uint32_t v) { return __uint_as_float(v << 16); }
__device__ __forceinline__ float bf_hi(uint32_t v) { return __uint_as_float(v & 0xffff0000u); }
__device__ __forceinline__ uint32_t bmul2(uint32_t a, uint32_t b) { uint32_t r; asm("mul.rn.bf16x2 %0, %1, %2;" : "=r"(r) : "r"(a), "r"(b)); return r; }
__device__ __forceinline__ uint32_t badd2(uint32_t a, uint32_t b) { uint32_t r; asm("add.rn.bf16x2 %0, %1, %2;" : "=r"(r) : "r"(a), "r"(b)); return r; }
#define STAMP(idx) do {} while (0)
#define MSTAMP(idx) do {} while (0)
#define BSTAMP(idx, saddr) do {} while (0)

__device__ __forceinline__ uint32_t pack_f16(float lo, float hi) {
  uint32_t r; asm("cvt.rn.satfinite.f16x2.f32 %0, %1, %2;" : "=r"(r) : "f"(hi), "f"(lo)); return r;
}
__device__ __forceinline__ uint32_t hfma2(uint32_t a, uint32_t b, uint32_t c) { uint32_t r; asm("fma.rn.f16x2 %0, %1, %2, %3;" : "=r"(r) : "r"(a), "r"(b), "r"(c)); return r; }
__device__ __forceinline__ uint32_t gelu_pair_f16(uint32_t h) {
  const uint32_t c0 = 0x3e623e62u, c1 = 0x34913491u;
  uint32_t u, p, z, t, r, o;
  asm("mul.rn.f16x2 %0, %1, %1;" : "=r"(u) : "r"(h));
  asm("fma.rn.f16x2 %0, %1, %2, %3;" : "=r"(p) : "r"(u), "r"(c1), "r"(c0));
  asm("mul.rn.f16x2 %0, %1, %2;" : "=r"(z) : "r"(h), "r"(p));
  asm("tanh.approx.f16x2 %0, %1;" : "=r"(t) : "r"(z));
  asm("fma.rn.f16x2 %0, %1, %2, %1;" : "=r"(r) : "r"(h), "r"(t));
  float lo, hi;
  asm("{\n.reg .f16 a, b;\nmov.b32 {a, b}, %2;\ncvt.f32.f16 %0, a;\ncvt.f32.f16 %1, b;\n}" : "=f"(lo), "=f"(hi) : "r"(r));
  asm("cvt.rn.bf16x2.f32 %0, %1, %2;" : "=r"(o) : "f"(hi), "f"(lo));
  return o;
}
__device__ __forceinline__ float gelu_from_half(float h) {
  const float c0 = 2.f * 0.7978845608028654f, c1 = 8.f * 0.7978845608028654f * 0.044715f;
  float z = h * fmaf(h * h, c1, c0);
  float t; asm("tanh.approx.f32 %0, %1;" : "=f"(t) : "f"(z));
  return fmaf(h, t, h);
}
__device__ __forceinline__ void wgmma_ss_n128(float (&d)[64], uint32_t a_lo, uint32_t b_lo) {
  asm volatile(
    "{\n.reg .b64 da, db;\nmov.b64 da, {%64, 8};\nmov.b64 db, {%65, 0x40000040};\n"
    "wgmma.mma_async.sync.aligned.m64n128k16.f32.bf16.bf16 "
    "{%0, %1, %2, %3, %4, %5, %6, %7, %8, %9, %10, %11, %12, %13, %14, %15, "
    "%16, %17, %18, %19, %20, %21, %22, %23, %24, %25, %26, %27, %28, %29, %30, %31, "
    "%32, %33, %34, %35, %36, %37, %38, %39, %40, %41, %42, %43, %44, %45, %46, %47, "
    "%48, %49, %50, %51, %52, %53, %54, %55, %56, %57, %58, %59, %60, %61, %62, %63}, "
    "da, db, 1, 1, 1, 0, 1;\n}\n"
    : "+f"(d[0]), "+f"(d[1]), "+f"(d[2]), "+f"(d[3]), "+f"(d[4]), "+f"(d[5]), "+f"(d[6]), "+f"(d[7]),
      "+f"(d[8]), "+f"(d[9]), "+f"(d[10]), "+f"(d[11]), "+f"(d[12]), "+f"(d[13]), "+f"(d[14]), "+f"(d[15]),
      "+f"(d[16]), "+f"(d[17]), "+f"(d[18]), "+f"(d[19]), "+f"(d[20]), "+f"(d[21]), "+f"(d[22]), "+f"(d[23]),
      "+f"(d[24]), "+f"(d[25]), "+f"(d[26]), "+f"(d[27]), "+f"(d[28]), "+f"(d[29]), "+f"(d[30]), "+f"(d[31]),
      "+f"(d[32]), "+f"(d[33]), "+f"(d[34]), "+f"(d[35]), "+f"(d[36]), "+f"(d[37]), "+f"(d[38]), "+f"(d[39]),
      "+f"(d[40]), "+f"(d[41]), "+f"(d[42]), "+f"(d[43]), "+f"(d[44]), "+f"(d[45]), "+f"(d[46]), "+f"(d[47]),
      "+f"(d[48]), "+f"(d[49]), "+f"(d[50]), "+f"(d[51]), "+f"(d[52]), "+f"(d[53]), "+f"(d[54]), "+f"(d[55]),
      "+f"(d[56]), "+f"(d[57]), "+f"(d[58]), "+f"(d[59]), "+f"(d[60]), "+f"(d[61]), "+f"(d[62]), "+f"(d[63])
    : "r"(a_lo), "r"(b_lo));
}
__device__ __forceinline__ void wgmma_ss_n192(float (&d)[96], uint32_t a_lo, uint32_t b_lo) {
  asm volatile(
    "{\n.reg .b64 da, db;\nmov.b64 da, {%96, 8};\nmov.b64 db, {%97, 0x40000040};\n"
    "wgmma.mma_async.sync.aligned.m64n192k16.f32.bf16.bf16 "
    "{%0, %1, %2, %3, %4, %5, %6, %7, %8, %9, %10, %11, %12, %13, %14, %15, "
    "%16, %17, %18, %19, %20, %21, %22, %23, %24, %25, %26, %27, %28, %29, %30, %31, "
    "%32, %33, %34, %35, %36, %37, %38, %39, %40, %41, %42, %43, %44, %45, %46, %47, "
    "%48, %49, %50, %51, %52, %53, %54, %55, %56, %57, %58, %59, %60, %61, %62, %63, "
    "%64, %65, %66, %67, %68, %69, %70, %71, %72, %73, %74, %75, %76, %77, %78, %79, "
    "%80, %81, %82, %83, %84, %85, %86, %87, %88, %89, %90, %91, %92, %93, %94, %95}, "
    "da, db, 1, 1, 1, 0, 1;\n}\n"
    : "+f"(d[0]), "+f"(d[1]), "+f"(d[2]), "+f"(d[3]), "+f"(d[4]), "+f"(d[5]), "+f"(d[6]), "+f"(d[7]),
      "+f"(d[8]), "+f"(d[9]), "+f"(d[10]), "+f"(d[11]), "+f"(d[12]), "+f"(d[13]), "+f"(d[14]), "+f"(d[15]),
      "+f"(d[16]), "+f"(d[17]), "+f"(d[18]), "+f"(d[19]), "+f"(d[20]), "+f"(d[21]), "+f"(d[22]), "+f"(d[23]),
      "+f"(d[24]), "+f"(d[25]), "+f"(d[26]), "+f"(d[27]), "+f"(d[28]), "+f"(d[29]), "+f"(d[30]), "+f"(d[31]),
      "+f"(d[32]), "+f"(d[33]), "+f"(d[34]), "+f"(d[35]), "+f"(d[36]), "+f"(d[37]), "+f"(d[38]), "+f"(d[39]),
      "+f"(d[40]), "+f"(d[41]), "+f"(d[42]), "+f"(d[43]), "+f"(d[44]), "+f"(d[45]), "+f"(d[46]), "+f"(d[47]),
      "+f"(d[48]), "+f"(d[49]), "+f"(d[50]), "+f"(d[51]), "+f"(d[52]), "+f"(d[53]), "+f"(d[54]), "+f"(d[55]),
      "+f"(d[56]), "+f"(d[57]), "+f"(d[58]), "+f"(d[59]), "+f"(d[60]), "+f"(d[61]), "+f"(d[62]), "+f"(d[63]),
      "+f"(d[64]), "+f"(d[65]), "+f"(d[66]), "+f"(d[67]), "+f"(d[68]), "+f"(d[69]), "+f"(d[70]), "+f"(d[71]),
      "+f"(d[72]), "+f"(d[73]), "+f"(d[74]), "+f"(d[75]), "+f"(d[76]), "+f"(d[77]), "+f"(d[78]), "+f"(d[79]),
      "+f"(d[80]), "+f"(d[81]), "+f"(d[82]), "+f"(d[83]), "+f"(d[84]), "+f"(d[85]), "+f"(d[86]), "+f"(d[87]),
      "+f"(d[88]), "+f"(d[89]), "+f"(d[90]), "+f"(d[91]), "+f"(d[92]), "+f"(d[93]), "+f"(d[94]), "+f"(d[95])
    : "r"(a_lo), "r"(b_lo));
}
__device__ __forceinline__ void wgmma_ss_n256(float (&d)[128], uint32_t a_lo, uint32_t b_lo) {
  asm volatile(
    "{\n.reg .b64 da, db;\nmov.b64 da, {%128, 8};\nmov.b64 db, {%129, 0x40000040};\n"
    "wgmma.mma_async.sync.aligned.m64n256k16.f32.bf16.bf16 "
    "{%0, %1, %2, %3, %4, %5, %6, %7, %8, %9, %10, %11, %12, %13, %14, %15, "
    "%16, %17, %18, %19, %20, %21, %22, %23, %24, %25, %26, %27, %28, %29, %30, %31, "
    "%32, %33, %34, %35, %36, %37, %38, %39, %40, %41, %42, %43, %44, %45, %46, %47, "
    "%48, %49, %50, %51, %52, %53, %54, %55, %56, %57, %58, %59, %60, %61, %62, %63, "
    "%64, %65, %66, %67, %68, %69, %70, %71, %72, %73, %74, %75, %76, %77, %78, %79, "
    "%80, %81, %82, %83, %84, %85, %86, %87, %88, %89, %90, %91, %92, %93, %94, %95, "
    "%96, %97, %98, %99, %100, %101, %102, %103, %104, %105, %106, %107, %108, %109, %110, %111, "
    "%112, %113, %114, %115, %116, %117, %118, %119, %120, %121, %122, %123, %124, %125, %126, %127}, "
    "da, db, 1, 1, 1, 0, 1;\n}\n"
    : "+f"(d[0]), "+f"(d[1]), "+f"(d[2]), "+f"(d[3]), "+f"(d[4]), "+f"(d[5]), "+f"(d[6]), "+f"(d[7]),
      "+f"(d[8]), "+f"(d[9]), "+f"(d[10]), "+f"(d[11]), "+f"(d[12]), "+f"(d[13]), "+f"(d[14]), "+f"(d[15]),
      "+f"(d[16]), "+f"(d[17]), "+f"(d[18]), "+f"(d[19]), "+f"(d[20]), "+f"(d[21]), "+f"(d[22]), "+f"(d[23]),
      "+f"(d[24]), "+f"(d[25]), "+f"(d[26]), "+f"(d[27]), "+f"(d[28]), "+f"(d[29]), "+f"(d[30]), "+f"(d[31]),
      "+f"(d[32]), "+f"(d[33]), "+f"(d[34]), "+f"(d[35]), "+f"(d[36]), "+f"(d[37]), "+f"(d[38]), "+f"(d[39]),
      "+f"(d[40]), "+f"(d[41]), "+f"(d[42]), "+f"(d[43]), "+f"(d[44]), "+f"(d[45]), "+f"(d[46]), "+f"(d[47]),
      "+f"(d[48]), "+f"(d[49]), "+f"(d[50]), "+f"(d[51]), "+f"(d[52]), "+f"(d[53]), "+f"(d[54]), "+f"(d[55]),
      "+f"(d[56]), "+f"(d[57]), "+f"(d[58]), "+f"(d[59]), "+f"(d[60]), "+f"(d[61]), "+f"(d[62]), "+f"(d[63]),
      "+f"(d[64]), "+f"(d[65]), "+f"(d[66]), "+f"(d[67]), "+f"(d[68]), "+f"(d[69]), "+f"(d[70]), "+f"(d[71]),
      "+f"(d[72]), "+f"(d[73]), "+f"(d[74]), "+f"(d[75]), "+f"(d[76]), "+f"(d[77]), "+f"(d[78]), "+f"(d[79]),
      "+f"(d[80]), "+f"(d[81]), "+f"(d[82]), "+f"(d[83]), "+f"(d[84]), "+f"(d[85]), "+f"(d[86]), "+f"(d[87]),
      "+f"(d[88]), "+f"(d[89]), "+f"(d[90]), "+f"(d[91]), "+f"(d[92]), "+f"(d[93]), "+f"(d[94]), "+f"(d[95]),
      "+f"(d[96]), "+f"(d[97]), "+f"(d[98]), "+f"(d[99]), "+f"(d[100]), "+f"(d[101]), "+f"(d[102]), "+f"(d[103]),
      "+f"(d[104]), "+f"(d[105]), "+f"(d[106]), "+f"(d[107]), "+f"(d[108]), "+f"(d[109]), "+f"(d[110]), "+f"(d[111]),
      "+f"(d[112]), "+f"(d[113]), "+f"(d[114]), "+f"(d[115]), "+f"(d[116]), "+f"(d[117]), "+f"(d[118]), "+f"(d[119]),
      "+f"(d[120]), "+f"(d[121]), "+f"(d[122]), "+f"(d[123]), "+f"(d[124]), "+f"(d[125]), "+f"(d[126]), "+f"(d[127])
    : "r"(a_lo), "r"(b_lo));
}
__device__ __forceinline__ void wgmma_ss_n128_p(float (&d)[64], uint32_t a_lo, uint32_t b_lo, uint32_t keep) {
  asm volatile(
    "{\n.reg .pred p;\nsetp.ne.b32 p, %66, 0;\n"
    "{\n.reg .b64 da, db;\nmov.b64 da, {%64, 8};\nmov.b64 db, {%65, 0x40000040};\n"
    "wgmma.mma_async.sync.aligned.m64n128k16.f32.bf16.bf16 "
    "{%0, %1, %2, %3, %4, %5, %6, %7, %8, %9, %10, %11, %12, %13, %14, %15, "
    "%16, %17, %18, %19, %20, %21, %22, %23, %24, %25, %26, %27, %28, %29, %30, %31, "
    "%32, %33, %34, %35, %36, %37, %38, %39, %40, %41, %42, %43, %44, %45, %46, %47, "
    "%48, %49, %50, %51, %52, %53, %54, %55, %56, %57, %58, %59, %60, %61, %62, %63}, "
    "da, db, p, 1, 1, 0, 1;\n}\n}\n"
    : "+f"(d[0]), "+f"(d[1]), "+f"(d[2]), "+f"(d[3]), "+f"(d[4]), "+f"(d[5]), "+f"(d[6]), "+f"(d[7]),
      "+f"(d[8]), "+f"(d[9]), "+f"(d[10]), "+f"(d[11]), "+f"(d[12]), "+f"(d[13]), "+f"(d[14]), "+f"(d[15]),
      "+f"(d[16]), "+f"(d[17]), "+f"(d[18]), "+f"(d[19]), "+f"(d[20]), "+f"(d[21]), "+f"(d[22]), "+f"(d[23]),
      "+f"(d[24]), "+f"(d[25]), "+f"(d[26]), "+f"(d[27]), "+f"(d[28]), "+f"(d[29]), "+f"(d[30]), "+f"(d[31]),
      "+f"(d[32]), "+f"(d[33]), "+f"(d[34]), "+f"(d[35]), "+f"(d[36]), "+f"(d[37]), "+f"(d[38]), "+f"(d[39]),
      "+f"(d[40]), "+f"(d[41]), "+f"(d[42]), "+f"(d[43]), "+f"(d[44]), "+f"(d[45]), "+f"(d[46]), "+f"(d[47]),
      "+f"(d[48]), "+f"(d[49]), "+f"(d[50]), "+f"(d[51]), "+f"(d[52]), "+f"(d[53]), "+f"(d[54]), "+f"(d[55]),
      "+f"(d[56]), "+f"(d[57]), "+f"(d[58]), "+f"(d[59]), "+f"(d[60]), "+f"(d[61]), "+f"(d[62]), "+f"(d[63])
    : "r"(a_lo), "r"(b_lo), "r"(keep));
}
__device__ __forceinline__ void wgmma_ss_n256_first(float (&d)[128], uint32_t a_lo, uint32_t b_lo) {
  asm volatile(
    "{\n.reg .b64 da, db;\nmov.b64 da, {%128, 8};\nmov.b64 db, {%129, 0x40000040};\n"
    "mov.b32 %0, 0; mov.b32 %1, 0; mov.b32 %2, 0; mov.b32 %3, 0; mov.b32 %4, 0; mov.b32 %5, 0; mov.b32 %6, 0; mov.b32 %7, 0;\n"
    "mov.b32 %8, 0; mov.b32 %9, 0; mov.b32 %10, 0; mov.b32 %11, 0; mov.b32 %12, 0; mov.b32 %13, 0; mov.b32 %14, 0; mov.b32 %15, 0;\n"
    "mov.b32 %16, 0; mov.b32 %17, 0; mov.b32 %18, 0; mov.b32 %19, 0; mov.b32 %20, 0; mov.b32 %21, 0; mov.b32 %22, 0; mov.b32 %23, 0;\n"
    "mov.b32 %24, 0; mov.b32 %25, 0; mov.b32 %26, 0; mov.b32 %27, 0; mov.b32 %28, 0; mov.b32 %29, 0; mov.b32 %30, 0; mov.b32 %31, 0;\n"
    "mov.b32 %32, 0; mov.b32 %33, 0; mov.b32 %34, 0; mov.b32 %35, 0; mov.b32 %36, 0; mov.b32 %37, 0; mov.b32 %38, 0; mov.b32 %39, 0;\n"
    "mov.b32 %40, 0; mov.b32 %41, 0; mov.b32 %42, 0; mov.b32 %43, 0; mov.b32 %44, 0; mov.b32 %45, 0; mov.b32 %46, 0; mov.b32 %47, 0;\n"
    "mov.b32 %48, 0; mov.b32 %49, 0; mov.b32 %50, 0; mov.b32 %51, 0; mov.b32 %52, 0; mov.b32 %53, 0; mov.b32 %54, 0; mov.b32 %55, 0;\n"
    "mov.b32 %56, 0; mov.b32 %57, 0; mov.b32 %58, 0; mov.b32 %59, 0; mov.b32 %60, 0; mov.b32 %61, 0; mov.b32 %62, 0; mov.b32 %63, 0;\n"
    "mov.b32 %64, 0; mov.b32 %65, 0; mov.b32 %66, 0; mov.b32 %67, 0; mov.b32 %68, 0; mov.b32 %69, 0; mov.b32 %70, 0; mov.b32 %71, 0;\n"
    "mov.b32 %72, 0; mov.b32 %73, 0; mov.b32 %74, 0; mov.b32 %75, 0; mov.b32 %76, 0; mov.b32 %77, 0; mov.b32 %78, 0; mov.b32 %79, 0;\n"
    "mov.b32 %80, 0; mov.b32 %81, 0; mov.b32 %82, 0; mov.b32 %83, 0; mov.b32 %84, 0; mov.b32 %85, 0; mov.b32 %86, 0; mov.b32 %87, 0;\n"
    "mov.b32 %88, 0; mov.b32 %89, 0; mov.b32 %90, 0; mov.b32 %91, 0; mov.b32 %92, 0; mov.b32 %93, 0; mov.b32 %94, 0; mov.b32 %95, 0;\n"
    "mov.b32 %96, 0; mov.b32 %97, 0; mov.b32 %98, 0; mov.b32 %99, 0; mov.b32 %100, 0; mov.b32 %101, 0; mov.b32 %102, 0; mov.b32 %103, 0;\n"
    "mov.b32 %104, 0; mov.b32 %105, 0; mov.b32 %106, 0; mov.b32 %107, 0; mov.b32 %108, 0; mov.b32 %109, 0; mov.b32 %110, 0; mov.b32 %111, 0;\n"
    "mov.b32 %112, 0; mov.b32 %113, 0; mov.b32 %114, 0; mov.b32 %115, 0; mov.b32 %116, 0; mov.b32 %117, 0; mov.b32 %118, 0; mov.b32 %119, 0;\n"
    "mov.b32 %120, 0; mov.b32 %121, 0; mov.b32 %122, 0; mov.b32 %123, 0; mov.b32 %124, 0; mov.b32 %125, 0; mov.b32 %126, 0; mov.b32 %127, 0;\n"
    "wgmma.mma_async.sync.aligned.m64n256k16.f32.bf16.bf16 "
    "{%0, %1, %2, %3, %4, %5, %6, %7, %8, %9, %10, %11, %12, %13, %14, %15, "
    "%16, %17, %18, %19, %20, %21, %22, %23, %24, %25, %26, %27, %28, %29, %30, %31, "
    "%32, %33, %34, %35, %36, %37, %38, %39, %40, %41, %42, %43, %44, %45, %46, %47, "
    "%48, %49, %50, %51, %52, %53, %54, %55, %56, %57, %58, %59, %60, %61, %62, %63, "
    "%64, %65, %66, %67, %68, %69, %70, %71, %72, %73, %74, %75, %76, %77, %78, %79, "
    "%80, %81, %82, %83, %84, %85, %86, %87, %88, %89, %90, %91, %92, %93, %94, %95, "
    "%96, %97, %98, %99, %100, %101, %102, %103, %104, %105, %106, %107, %108, %109, %110, %111, "
    "%112, %113, %114, %115, %116, %117, %118, %119, %120, %121, %122, %123, %124, %125, %126, %127}, "
    "da, db, 1, 1, 1, 0, 1;\n}\n"
    : "=f"(d[0]), "=f"(d[1]), "=f"(d[2]), "=f"(d[3]), "=f"(d[4]), "=f"(d[5]), "=f"(d[6]), "=f"(d[7]),
      "=f"(d[8]), "=f"(d[9]), "=f"(d[10]), "=f"(d[11]), "=f"(d[12]), "=f"(d[13]), "=f"(d[14]), "=f"(d[15]),
      "=f"(d[16]), "=f"(d[17]), "=f"(d[18]), "=f"(d[19]), "=f"(d[20]), "=f"(d[21]), "=f"(d[22]), "=f"(d[23]),
      "=f"(d[24]), "=f"(d[25]), "=f"(d[26]), "=f"(d[27]), "=f"(d[28]), "=f"(d[29]), "=f"(d[30]), "=f"(d[31]),
      "=f"(d[32]), "=f"(d[33]), "=f"(d[34]), "=f"(d[35]), "=f"(d[36]), "=f"(d[37]), "=f"(d[38]), "=f"(d[39]),
      "=f"(d[40]), "=f"(d[41]), "=f"(d[42]), "=f"(d[43]), "=f"(d[44]), "=f"(d[45]), "=f"(d[46]), "=f"(d[47]),
      "=f"(d[48]), "=f"(d[49]), "=f"(d[50]), "=f"(d[51]), "=f"(d[52]), "=f"(d[53]), "=f"(d[54]), "=f"(d[55]),
      "=f"(d[56]), "=f"(d[57]), "=f"(d[58]), "=f"(d[59]), "=f"(d[60]), "=f"(d[61]), "=f"(d[62]), "=f"(d[63]),
      "=f"(d[64]), "=f"(d[65]), "=f"(d[66]), "=f"(d[67]), "=f"(d[68]), "=f"(d[69]), "=f"(d[70]), "=f"(d[71]),
      "=f"(d[72]), "=f"(d[73]), "=f"(d[74]), "=f"(d[75]), "=f"(d[76]), "=f"(d[77]), "=f"(d[78]), "=f"(d[79]),
      "=f"(d[80]), "=f"(d[81]), "=f"(d[82]), "=f"(d[83]), "=f"(d[84]), "=f"(d[85]), "=f"(d[86]), "=f"(d[87]),
      "=f"(d[88]), "=f"(d[89]), "=f"(d[90]), "=f"(d[91]), "=f"(d[92]), "=f"(d[93]), "=f"(d[94]), "=f"(d[95]),
      "=f"(d[96]), "=f"(d[97]), "=f"(d[98]), "=f"(d[99]), "=f"(d[100]), "=f"(d[101]), "=f"(d[102]), "=f"(d[103]),
      "=f"(d[104]), "=f"(d[105]), "=f"(d[106]), "=f"(d[107]), "=f"(d[108]), "=f"(d[109]), "=f"(d[110]), "=f"(d[111]),
      "=f"(d[112]), "=f"(d[113]), "=f"(d[114]), "=f"(d[115]), "=f"(d[116]), "=f"(d[117]), "=f"(d[118]), "=f"(d[119]),
      "=f"(d[120]), "=f"(d[121]), "=f"(d[122]), "=f"(d[123]), "=f"(d[124]), "=f"(d[125]), "=f"(d[126]), "=f"(d[127])
    : "r"(a_lo), "r"(b_lo));
}

template <int N> struct Mma;
template <> struct Mma<128> {
  static __device__ __forceinline__ void ss(float (&d)[64], uint32_t a, uint32_t b) { wgmma_ss_n128(d, a, b); }
  static __device__ __forceinline__ void ss(float (&d)[64], uint32_t a, uint32_t b, uint32_t keep) { wgmma_ss_n128_p(d, a, b, keep); }
};
template <> struct Mma<192> {
  static __device__ __forceinline__ void ss(float (&d)[96], uint32_t a, uint32_t b) { wgmma_ss_n192(d, a, b); }
};
template <> struct Mma<256> {
  static __device__ __forceinline__ void ss(float (&d)[128], uint32_t a, uint32_t b) { wgmma_ss_n256(d, a, b); }
  static __device__ __forceinline__ void ss(float (&d)[128], uint32_t a, uint32_t b, uint32_t) { wgmma_ss_n256_first(d, a, b); }
};
template <int R> __device__ __forceinline__ void pin(float (&d)[R]) {
#pragma unroll
  for (int x = 0; x < R; x++) asm volatile("" : "+f"(d[x]));
}

__device__ __forceinline__ uint32_t ld_relaxed(const uint32_t* p) {
  uint32_t v; asm volatile("ld.relaxed.gpu.global.u32 %0, [%1];" : "=r"(v) : "l"(p) : "memory"); return v;
}
__device__ __forceinline__ void red_release(uint32_t* p) { asm volatile("red.release.gpu.global.add.u32 [%0], 1;" :: "l"(p) : "memory"); }
__device__ __forceinline__ uint32_t both_valid(uint32_t a, uint32_t b, uint32_t ep) {
  uint32_t r; asm("lop3.b32 %0, %1, %2, %3, 0x42;" : "=r"(r) : "r"(a), "r"(b), "r"(ep)); return r;
}
__device__ __forceinline__ uint32_t tagged(float v, uint32_t ep) { return (__float_as_uint(v) | 1u) ^ (ep & 1u); }
__device__ __forceinline__ void st_release(uint32_t* p, uint32_t v) { asm volatile("st.release.gpu.global.u32 [%0], %1;" :: "l"(p), "r"(v) : "memory"); }
__device__ __forceinline__ void stg32(void* p, uint32_t v) { asm volatile("st.global.u32 [%0], %1;" :: "l"(p), "r"(v) : "memory"); }
__device__ __forceinline__ float rsqrt_fast(float x) { float r; asm("rsqrt.approx.ftz.f32 %0, %1;" : "=f"(r) : "f"(x)); return r; }
__device__ __forceinline__ uint32_t gate_pair(uint32_t x, uint32_t y, uint32_t r, uint32_t nb) {
  uint32_t o;
  asm("{\n.reg .b16 l, h;\n.reg .b32 ll, hh, t;\nmov.b32 {l, h}, %3;\nmov.b32 ll, {l, l};\nmov.b32 hh, {h, h};\n"
      "fma.rn.bf16x2 t, %1, ll, %4;\nfma.rn.bf16x2 t, %1, hh, t;\nfma.rn.bf16x2 %0, t, %2, %1;\n}" : "=r"(o) : "r"(x), "r"(y), "r"(r), "r"(nb));
  return o;
}

constexpr int CV_KT_O = 4144;
constexpr int CV_KT_CH = 8336;
constexpr int CV_KH = 2064;
constexpr int CV_U_PLANE = 2240;
constexpr int CV_U_CH = 4496;
constexpr int CV_VQ = 8320, CV_Y_CH = 1040, CV_XROW = 2064;
constexpr int SM_BAR = 0;
constexpr int CV_K = 896;
constexpr int CV_X = CV_K + 128 + 32768;
constexpr int CV_ST0 = CV_X + 16 * CV_XROW;
constexpr int CV_KT = CV_ST0 + 8192;
constexpr int CV_QS = CV_KT + 8 * CV_KT_CH;
constexpr int CV_U = 142848;
constexpr int CV_V = CV_U + 8 * CV_U_CH;
constexpr int CV_ST1 = CV_V + 4 * CV_VQ;
constexpr int SM_ZERO = CV_ST1 + 8192, SM_ROLE = SM_ZERO + 4, SM_EPOCH = SM_ZERO + 8;
constexpr int CV_END = SM_ZERO + 16;
static_assert(CV_QS + 1024 <= CV_U && CV_X % 1024 == 0 && CV_V % 128 == 0, "layout");
constexpr int CV_BAR = SM_BAR + 8 * 84, BAR_REL = 25;
enum { CB_K0, CB_QA, CB_Q0, CB_Q1, CB_Q2, CB_Q3, CB_K1, CB_X0, CB_X1, CB_QC0, CB_QC1, CB_QS, CB_U1, CB_U2,
       CB_ST0, CB_ST1, CB_O1, CB_P1, CB_Y1, CB_Y2, CB_P2, CB_EARLY, CB_LATE, CB_YOUT, CB_STAT, CB_XFREE = CB_STAT + 2, CB_COUNT };
static_assert(CV_BAR + 8 * CB_COUNT <= CV_K, "layout");

__device__ __forceinline__ uint32_t lds32_nv(uint32_t addr) { uint32_t v; asm("ld.shared.u32 %0, [%1];" : "=r"(v) : "r"(addr)); return v; }
__device__ __forceinline__ void ldsm_x4_nv(uint32_t addr, uint32_t& r0, uint32_t& r1, uint32_t& r2, uint32_t& r3) {
  asm("ldmatrix.sync.aligned.m8n8.x4.shared.b16 {%0,%1,%2,%3}, [%4];" : "=r"(r0), "=r"(r1), "=r"(r2), "=r"(r3) : "r"(addr));
}
__device__ __forceinline__ void stsm_x4_t(uint32_t addr, uint32_t r0, uint32_t r1, uint32_t r2, uint32_t r3) {
  asm volatile("stmatrix.sync.aligned.m8n8.x4.trans.shared.b16 [%0], {%1,%2,%3,%4};" :: "r"(addr), "r"(r0), "r"(r1), "r"(r2), "r"(r3) : "memory");
}
__device__ __forceinline__ void bulk_load(uint32_t dst, const void* src, uint32_t bytes, uint32_t bar) {
  asm volatile("cp.async.bulk.shared::cluster.global.mbarrier::complete_tx::bytes [%0], [%1], %2, [%3];" :: "r"(dst), "l"(src), "r"(bytes), "r"(bar) : "memory");
}
__device__ __forceinline__ void mbar_wait_plain(uint32_t bar, uint32_t parity) {
#pragma unroll 1
  for (int spins = 0; spins < SPIN_LIMIT && !mbar_try(bar, parity); spins++) {}
}

__device__ __forceinline__ void shift_chunk(uint32_t src) {
  uint4 e;
  uint32_t nx;
  asm volatile("ld.shared.v4.u32 {%0,%1,%2,%3}, [%4];" : "=r"(e.x), "=r"(e.y), "=r"(e.z), "=r"(e.w) : "r"(src));
  asm volatile("ld.shared.u32 %0, [%1];" : "=r"(nx) : "r"(src + 16));
  sts128(src + CV_KT_O, make_uint4(__byte_perm(e.x, e.y, 0x5432), __byte_perm(e.y, e.z, 0x5432), __byte_perm(e.z, e.w, 0x5432), __byte_perm(e.w, nx, 0x5432)));
}
__device__ __forceinline__ void kv_block(uint32_t sm, int t0, const uint32_t (&wp)[4], int lane) {
  const int mi = lane >> 3, rev = 7 - (lane & 7);
  uint32_t vv[4], res[4];
  ldsm_x4(sm + CV_V + (t0 >> 9) * (CV_VQ - 8192) + (t0 + 8 * mi + rev) * 16, vv[0], vv[1], vv[2], vv[3]);
#pragma unroll
  for (int i = 0; i < 4; i++) {
    uint32_t k0, k1, k2, k3;
    ldsm_x4(sm + CV_K + (8 + t0 + 8 * i + rev - mi) * 16, k0, k1, k2, k3);
    res[i] = bmul2(badd2(badd2(badd2(bmul2(k3, wp[3]), bmul2(k2, wp[2])), bmul2(k1, wp[1])), bmul2(k0, wp[0])), vv[i]);
  }
  stsm_x4_t(sm + CV_U + (lane & 7) * CV_U_CH + (1 - (mi & 1)) * CV_U_PLANE + (8 + (t0 >> 4) + (mi >> 1)) * 16, res[0], res[1], res[2], res[3]);
}
template <int T0, int NT, int D0, int D1, int J0, int J1>
__device__ __forceinline__ void conv_phase(float (&acc)[16][4], uint32_t abase, uint32_t bbase, uint32_t zero) {
  abase += zero; bbase += zero;
#pragma unroll 1
  for (int dl = 0; dl < 8; dl++) {
    uint32_t bf[NT][2];
#pragma unroll
    for (int j = 0; j < NT; j += 2) ldsm_x4_nv(bbase + (T0 + j) * 128 - dl * 16, bf[j][0], bf[j][1], bf[j + 1][0], bf[j + 1][1]);
    const uint32_t ap = abase + dl * 32;
#pragma unroll
    for (int dh = D0; dh < D1; dh++) {
      const uint32_t a0 = lds32_nv(ap + dh * 256), a1 = lds32_nv(ap + dh * 256 - 16), a2 = lds32_nv(ap + dh * 256 + 16);
      const uint32_t a3 = a0 + zero;
#pragma unroll
      for (int j = 0; j < NT; j++)
        if (dh + T0 + j >= J0 && dh + T0 + j < J1) mma16816(acc[dh + T0 + j], a0, a1, a2, a3, bf[j][0], bf[j][1]);
    }
  }
}
__device__ __forceinline__ uint32_t hidden_zero(uint32_t addr) {
  uint32_t z; asm volatile("ld.volatile.shared.u32 %0, [%1];" : "=r"(z) : "r"(addr) : "memory"); return z;
}
template <int J0, int J1>
__device__ __forceinline__ void stage_y(const float (&acc)[16][4], uint32_t ys, uint32_t bar) {
#pragma unroll
  for (int j = J0; j < J1; j += 2)
    stsm_x4_t(ys + (j >> 2) * CV_VQ + (j & 3) * 128, pack_bf16(acc[j][0], acc[j][1]), pack_bf16(acc[j][2], acc[j][3]),
              pack_bf16(acc[j + 1][0], acc[j + 1][1]), pack_bf16(acc[j + 1][2], acc[j + 1][3]));
  if (J0) {
    __syncwarp();
    mbar_arrive_if(bar, (threadIdx.x & 31) == 0);
  }
}

#define KV_PROMO CU_TENSOR_MAP_L2_PROMOTION_L2_128B
#define STATS_EARLY 0
#define QC1_AT 2
#define QROW_AT 3
constexpr int CV_JS = 8;
enum { M_K, M_V, M_Q, M_W1C, M_W3C, M_X3S, M_X3B, M_H, M_HS, M_X1, M_HID, M_W1, M_W2, M_W3A, M_W3B, M_W4, M_OUT, M_Y, M_COUNT };
struct alignas(64) Params {
  const bf16 *q, *shift_k, *ssm_k, *ssm_d, *w2;
  CUtensorMap m[M_COUNT];
};
__device__ __forceinline__ void prefetch_line(const void* p) { asm volatile("prefetch.global.L2 [%0];" :: "l"(p) : "memory"); }

__device__ __forceinline__ uint32_t pick_role() {
  uint32_t smid;
  asm volatile("mov.u32 %0, %%smid;" : "=r"(smid));
  const uint32_t t = smid >> 1;
  const uint32_t gpc = t < 32 ? t & 7 : t < 60 ? 1 + (t - 32) % 7 : t < 62 ? t - 54 : 0;
#pragma unroll 1
  for (uint32_t k = 0; k < 4; k++) {
    const uint32_t p = (gpc + k) & 3, ticket = atomicAdd(&g_role[p], 1u);
    if (ticket < 16) return ticket * 4 + p;
  }
  return 0;
}

__device__ __forceinline__ void load_k(const Params& pr, uint32_t sm, int x) {
  const uint32_t bar = sm + CV_BAR + 8 * (x ? CB_K1 : CB_K0), bytes = x ? 4096 - CV_KH : CV_KH;
  mbar_expect_tx(bar, 8 * bytes);
#pragma unroll 1
  for (int ch = 0; ch < 8; ch++)
    bulk_load(sm + CV_KT + ch * CV_KT_CH + 32 + x * CV_KH, reinterpret_cast<const char*>(pr.ssm_k) + (blockIdx.x * 8 + ch) * 4096 + x * CV_KH, bytes, bar);
}
__device__ __forceinline__ void load_kv(const Params& pr, uint32_t sm, int y, int barrier) {
  tma_2d(sm + CV_K + 128 + y * 4096, &pr.m[M_K], sm + CV_BAR + 8 * barrier, blockIdx.x * 8, y * 256);
  tma_2d(sm + CV_V + (y >> 1) * CV_VQ + (y & 1) * 4096, &pr.m[M_V], sm + CV_BAR + 8 * barrier, blockIdx.x * 8, y * 256);
}

__device__ __forceinline__ void conv_part(const Params& pr, uint32_t sm, int warp) {
  const int tid = threadIdx.x, lane = tid & 31;
  const int b = blockIdx.x, d0 = b * 8;
  const uint32_t kt = sm + CV_KT, ub = sm + CV_U, bar = sm + CV_BAR;
  const int g = lane >> 2, qd = lane & 3, mi = lane >> 3;
  if (warp == 8) {
    asm volatile("bar.arrive 1, 384;" ::: "memory");
    const uint32_t ep = ld_relaxed(&g_epoch);
    if (elect_one()) {
      load_k(pr, sm, 1);
#pragma unroll 1
      for (int y = 2; y < 8; y++) {
        if (y == 2 * QROW_AT) {
          mbar_expect_tx(bar + 8 * CB_X0, 32768);
#pragma unroll 1
          for (int r = 0; r < 16; r++) bulk_load(sm + CV_X + r * CV_XROW, pr.q + (size_t)(b * 16 + r) * DM, 2048, bar + 8 * CB_X0);
        }
        if (!(y & 1)) mbar_expect_tx(bar + 8 * (CB_Q0 + (y >> 1)), 16384);
        load_kv(pr, sm, y, CB_Q0 + (y >> 1));
      }
#pragma unroll 1
      for (int x = M_Q; x < M_COUNT; x++) asm volatile("prefetch.tensormap [%0];" :: "l"(&pr.m[x]) : "memory");
      sts32(sm + SM_EPOCH, ep);
      if ((b & 1) == 0) sts32(sm + SM_ROLE, pick_role());
      asm volatile("fence.release.sync_restrict::shared::cta.cluster;" ::: "memory");
    }
    __syncwarp();
    asm volatile("barrier.cluster.arrive.relaxed.aligned;" ::: "memory");
    auto load_q = [&](int x) {
      mbar_wait_plain(bar + 8 * (CB_U1 + x), 0);
      fence_async_smem();
      if (elect_one()) {
        mbar_expect_tx(bar + 8 * (CB_QC0 + x), 16384);
#pragma unroll 1
        for (int y = 4 * x; y < 4 * x + 4; y++) tma_2d(sm + CV_K + 128 + y * 4096, &pr.m[M_Q], bar + 8 * (CB_QC0 + x), d0, y * 256);
      }
    };
    const int npieces = b < 112 ? 5 : 1;
    const int xr = (mi >> 1) * 8 + (lane & 7);
    const uint32_t xa = sm + CV_X + xr * 64 + (((mi & 1) ^ ((xr >> 1) & 3)) << 4);
    float cs[8][4] = {};
    auto q_stats = [&]() {
      mbar_wait_plain(bar + 8 * CB_QS, 0);
      float sum = 0.f, sq = 0.f;
#pragma unroll
      for (int x = 0; x < 8; x++) { const float2 v = lds_f2(sm + CV_QS + x * 128 + (lane & 15) * 8); sum += v.x; sq += v.y; }
      const float mean = sum * (1.f / DM), rs = rsqrt_fast(fmaxf(fmaf(-mean, mean, sq * (1.f / DM)), 0.f) + LN_EPS);
      const uint32_t rh = pack_bf16(0.f, rs);
      if (lane < 16)
        asm volatile("st.relaxed.gpu.global.v2.b32 [%0], {%1,%2};" :: "l"(g_qstat + b * 16 + lane), "r"(tagged(__uint_as_float(pack_bf16(rs - bf_hi(rh), bf_hi(rh))), ep)),
                     "r"(pack_bf16(-mean * rs, -mean * rs)) : "memory");
      if (lane == 0) { STAMP(47); asm volatile("red.relaxed.gpu.global.add.u32 [%0], 1;" :: "l"(&g_qcnt) : "memory"); }
    };
#pragma unroll 1
    for (int pc = -3; pc < npieces; pc++) {
      if (pc == -2) q_stats();
      if (pc >= 0) {
        mbar_wait_plain(bar + 8 * (CB_X0 + ((pc + 1) & 1)), ((pc + 1) >> 1) & 1);
#pragma unroll 1
        for (int r = 0; r < 16; r += 4) {
#pragma unroll
          for (int x = 0; x < 8; x++) {
            uint32_t a0, a1, a2, a3;
            ldsm_x4_t((xa ^ ((x & 1) << 5)) + ((pc + 1) & 1) * 16384 + (r + (x >> 1)) * 1024, a0, a1, a2, a3);
            mma16816(cs[x], a0, a1, a2, a3, 0x3f803f80u, 0x3f803f80u);
          }
        }
        if (pc == 0 || pc == 4) {
          float t = 0.f;
#pragma unroll
          for (int x = 0; x < 8; x += 2) {
            t += qd & 2 ? (qd & 1 ? cs[x + 1][2] : cs[x + 1][0]) : (qd & 1 ? cs[x][2] : cs[x][0]);
            cs[x][0] = cs[x][2] = cs[x + 1][0] = cs[x + 1][2] = 0.f;
          }
          (pc ? g_cs3 + 32 * b : g_cs1[b & 3] + 32 * (b >> 2))[8 * qd + g] = t;
        }
        __syncwarp();
      }
      if (pc > -3 && pc + 2 < npieces && elect_one()) {
        const uint32_t bx = bar + 8 * (CB_X0 + ((pc + 1) & 1));
        mbar_expect_tx(bx, 16384);
        tma_2d(sm + CV_X + ((pc + 1) & 1) * 16384, &pr.m[pc == -2 ? M_W1C : M_W3C], bx, 32 * (pc == -2 ? b >> 2 : b), 256 * (pc == -2 ? b & 3 : pc + 1));
      }
      if (pc == -3 || pc == min(QC1_AT, npieces - 1)) load_q(pc >= 0);
    }
#pragma unroll 1
    for (int x = 0; x < 4; x++) prefetch_line(reinterpret_cast<const char*>(pr.w2) + (b * 128 + x * 32 + lane) * 128);
    if (lane == 0) STAMP(52);
    return;
  }

  const uint32_t dpair = __ldg(reinterpret_cast<const uint32_t*>(pr.ssm_d + d0 + 2 * qd));
  const int wi = warp - (warp > 8), ti = 32 * wi + lane;
  {
    if (tid < 160) {
      const int x = tid - 128, y = x & 3;
      sts128(tid < 128 ? ub + (tid >> 4) * CV_U_CH + ((tid >> 3) & 1) * CV_U_PLANE + (tid & 7) * 16
                       : y == 3 ? sm + CV_K + (x >> 2) * 16 : kt + (x >> 2) * CV_KT_CH + (y == 2 ? 4128 : y * 16), make_uint4(0, 0, 0, 0));
    }
    uint32_t wp[4];
    {
      const uint4 a = ld_nc_u4(pr.shift_k + (d0 + 2 * qd) * 4);
      wp[0] = __byte_perm(a.x, a.z, 0x5410); wp[1] = __byte_perm(a.x, a.z, 0x7632);
      wp[2] = __byte_perm(a.y, a.w, 0x5410); wp[3] = __byte_perm(a.y, a.w, 0x7632);
    }
    const uint32_t kc = kt + (lane & 7) * CV_KT_CH;
    named_bar(1, 384);
#pragma unroll 1
    for (int x = 0; x < 2; x++) {
      mbar_wait_plain(bar + 8 * (x ? CB_K1 : CB_K0), 0);
#pragma unroll 1
      for (uint32_t a = kc + ((ti >> 3) + (x ? 130 - 32 : 0)) * 16; a < kc + (x ? 258 : 130) * 16; a += x ? 192 : 704) shift_chunk(a);
      __syncwarp();
      mbar_arrive_if(bar + 8 * CB_O1, x && lane == 0);
      if (tid == 0) BSTAMP(54, kt);
#pragma unroll 1
      for (int t0 = warp < 8 ? 32 * wi : 32 * wi + 256; t0 < (x ? SEQ : 512); t0 += x ? 96 : 256) {
        mbar_wait_plain(bar + 8 * (t0 < 256 ? CB_QA : CB_Q0 + (t0 >> 9)), 0);
        if (tid == 0) BSTAMP(56, kt);
        kv_block(sm, t0, wp, lane);
        constexpr int T1 = 128 * CV_JS + 32;
        __syncwarp();
        mbar_arrive_if(bar + 8 * (CB_U1 + (t0 >= T1)), t0 + 96 >= (t0 < T1 ? T1 : SEQ) && lane == 0);
      }
      if (x == 0) named_bar(4, 352);
      if (warp < 8) break;
    }
  }

  if (warp < 8) {
    const int o = 2 * qd - g;
    const uint32_t abase = kt + warp * CV_KT_CH + 32 + ((g & 1) ? CV_KT_O + (o - 1) * 2 : o * 2);
    const uint32_t bbase = ub + warp * CV_U_CH + (mi & 1) * CV_U_PLANE + (8 + (lane >> 4) * 8 + (lane & 7)) * 16;
    const uint32_t ys = sm + CV_V + warp * CV_Y_CH + (mi & 1) * 512 + ((lane >> 4) * 8 + (lane & 7)) * 16;
    auto q_sums = [&]() {
      mbar_wait_plain(bar + 8 * CB_X0, 0);
      float sum[4] = {0.f, 0.f, 0.f, 0.f}, lo[4] = {0.f, 0.f, 0.f, 0.f}, hi[4] = {0.f, 0.f, 0.f, 0.f};
#pragma unroll
      for (int x = 0; x < 8; x++) {
        uint32_t a0, a1, a2, a3;
        ldsm_x4(sm + CV_X + (lane & 15) * CV_XROW + warp * 256 + (lane >> 4) * 16 + x * 32, a0, a1, a2, a3);
        mma16816(sum, a0, a1, a2, a3, 0x3f803f80u, 0x3f803f80u);
        mma16816(lo, a0, a1, a2, a3, a0, a2);
        mma16816(hi, a0, a1, a2, a3, a1, a3);
      }
      if (qd == (g >> 1)) {
        asm volatile("st.shared.v2.f32 [%0], {%1,%2};" :: "r"(sm + CV_QS + warp * 128 + g * 8), "f"(sum[0]), "f"((g & 1) ? lo[1] : lo[0]) : "memory");
        asm volatile("st.shared.v2.f32 [%0], {%1,%2};" :: "r"(sm + CV_QS + warp * 128 + g * 8 + 64), "f"(sum[2]), "f"((g & 1) ? hi[3] : hi[2]) : "memory");
      }
      __syncwarp();
      mbar_arrive_if(bar + 8 * CB_QS, lane == 0);
    };
    if (tid == 0) STAMP(49);
    float acc[16][4];
#pragma unroll
    for (int j = 0; j < 16; j++) { acc[j][0] = acc[j][1] = acc[j][2] = acc[j][3] = 0.f; }
    conv_phase<0, 4, 0, 8, 0, 16>(acc, abase, bbase, hidden_zero(ub));
    stage_y<0, 4>(acc, ys, 0);
    if (tid == 0) STAMP(57);
    if (STATS_EARLY) q_sums();
    mbar_wait_plain(bar + 8 * CB_K1, 0);
    mbar_wait_plain(bar + 8 * CB_O1, 0);
    conv_phase<0, 4, 8, 16, 0, 16>(acc, abase, bbase, hidden_zero(ub));
    if (tid == 0) STAMP(58);
    if (!STATS_EARLY) q_sums();
    mbar_wait_plain(bar + 8 * CB_U1, 0);
    conv_phase<4, CV_JS - 4, 0, CV_JS - 4, 0, CV_JS>(acc, abase, bbase, hidden_zero(ub));
    stage_y<4, CV_JS>(acc, ys, bar + 8 * CB_Y1);
    if (tid == 0) STAMP(59);
    mbar_wait_plain(bar + 8 * CB_U2, 0);
    if (tid == 0) BSTAMP(55, kt);
    conv_phase<4, 12, 0, 12, CV_JS, 16>(acc, abase, bbase, hidden_zero(ub));
    stage_y<CV_JS, 16>(acc, ys, bar + 8 * CB_Y2);
    if (tid == 0) STAMP(50);
    if (tid == 32) STAMP(62);
  }
  {
    const int ch = lane & 7;
    const uint32_t ya = sm + CV_V + ch * CV_Y_CH + (mi & 1) * 512 + (mi >> 1) * 16;
    const uint32_t ua = ub + ch * CV_U_CH + (mi & 1) * CV_U_PLANE + (8 + (mi >> 1)) * 16;
    const uint32_t qa = sm + CV_K + 128 + (16 * (mi >> 1) + 15 - 8 * (mi & 1) - ch) * 16;
    char* xo = reinterpret_cast<char*>(g_x3[0]) + (size_t)b * CB_BYTES + (15 - g) * 16 + qd * 4;
    const uint32_t yo = sm + CV_K + 128 + ((7 - g) * 4 + qd) * 8;
    int budget = SPIN_LIMIT;
    uint32_t ep = 0;
    if (warp > 9) {
      if (tid == 320) STAMP(53);
      ep = ld_relaxed(&g_epoch);
#pragma unroll 1
      while (ld_relaxed(&g_qcnt) - 128 * ep < 128 && --budget > 0) __nanosleep(100);
      if (tid == 320) STAMP(43);
    }
#pragma unroll 1
    for (int part = warp < 8; part < 2; part++) {
      if (warp == 9 && part) break;
      if (warp > 9) {
        uint4 v[8];
#pragma unroll 1
        do {
          uint32_t ok = 1;
#pragma unroll
          for (int y = 0; y < 8; y++) {
            asm volatile("ld.relaxed.gpu.global.v4.u32 {%0,%1,%2,%3}, [%4];" : "=r"(v[y].x), "=r"(v[y].y), "=r"(v[y].z), "=r"(v[y].w)
                         : "l"(g_qstat + 1024 * part + 2 * (tid & 63) + 128 * y) : "memory");
            ok &= both_valid(v[y].x, v[y].z, ep);
          }
          if (__all_sync(0xffffffffu, ok)) break;
        } while (--budget > 0);
#pragma unroll
        for (int y = 0; y < 8; y++) sts128(sm + (part ? CV_ST1 : CV_ST0) + (tid & 63) * 16 + 1024 * y, make_uint4(v[y].x | 1u, v[y].y, v[y].z | 1u, v[y].w));
        __syncwarp();
        mbar_arrive_if(bar + 8 * (CB_ST0 + part), lane == 0);
      }
      mbar_wait_plain(bar + 8 * (CB_ST0 + part), 0);
      mbar_wait_plain(bar + 8 * (CB_QC0 + part), 0);
      if (tid == 288) STAMP(63);
      mbar_wait_plain(bar + 8 * (CB_Y1 + part), 0);
      const uint32_t sa = sm + (part ? CV_ST1 - 8192 : CV_ST0) + (15 - g) * 8;
#pragma unroll 1
      for (int u = part ? 4 * CV_JS + warp - 2 * (warp > 8) : warp - 9; u < (part ? 64 : 4 * CV_JS); u += part ? 10 : 3) {
        uint32_t y[4], uu[4], qq[4];
        ldsm_x4_t(ya + ((u >> 4) * (CV_VQ - 512) + u * 32), y[0], y[1], y[2], y[3]);
        ldsm_x4_t(ua + u * 32, uu[0], uu[1], uu[2], uu[3]);
        ldsm_x4(qa + u * 512, qq[0], qq[1], qq[2], qq[3]);
#pragma unroll
        for (int i = 0; i < 4; i++) {
          const int off = 16 * (i >> 1) - 8 * (i & 1);
          const float2 s = lds_f2(sa + (u * 256 + off * 8));
          y[i] = badd2(y[i], bmul2(uu[i], dpair));
          stg32(xo + (uint32_t)u * 512 + off * 16, gate_pair(qq[i], y[i], __float_as_uint(s.x), __float_as_uint(s.y)));
        }
        asm volatile("st.shared.v2.u32 [%0], {%1,%2};" :: "r"(yo + u * 512), "r"(y[1]), "r"(y[0]) : "memory");
        asm volatile("st.shared.v2.u32 [%0], {%1,%2};" :: "r"(yo + u * 512 + 256), "r"(y[3]), "r"(y[2]) : "memory");
      }
      __syncwarp();
      mbar_arrive_if(bar + 8 * (part ? CB_P2 : CB_P1), lane == 0);
    }
  }
  if (warp == 9) {
    mbar_wait_plain(bar + 8 * CB_P1, 0);
    if (elect_one()) {
      STAMP(61);
      red_release(&g_xcnt[b >> 3]);
      fence_async_smem();
      bulk_store(reinterpret_cast<char*>(g_y) + (size_t)b * CB_BYTES, sm + CV_K + 128, 16384);
      bulk_commit();
      bulk_wait_all();
      mbar_arrive(bar + 8 * CB_YOUT);
    }
  }
  if (tid == 0) STAMP(51);
}

constexpr int NA = 5, A_SLOT = 68 * 128;
constexpr int SM_B = 1024;
constexpr int SM_A = SM_B + 98304;
constexpr int SM_X = SM_A + 2 * NA * A_SLOT;
constexpr int SM_CS1 = CV_END;
constexpr int SM_CS3 = SM_CS1 + 512;
static_assert(SM_X % 1024 == 0 && SM_X + 32768 <= SM_CS1 && SM_B + 2 * 16384 == CV_X && SM_A + NA * A_SLOT == CV_U, "layout");
constexpr int BAR_FULLA = 0, BAR_FULLB = 16, BAR_TURN = 24, BAR_OWN = 26;
constexpr int BAR_EMPTYA = 28, BAR_EMPTYB = BAR_EMPTYA + 18, BAR_CS = BAR_EMPTYB + 9;
constexpr int BAR_PUB = 56;
constexpr int BAR_END = 84;
constexpr int SM_RS = SM_CS3 + 1792;
constexpr int MEGA_SMEM = SM_RS + 2 * 68 * 8;
static_assert(MEGA_SMEM <= 232448, "shared memory");
#define LEADS 0x444444
#define LEAD3 2

template <int N> struct BGeo;
template <> struct BGeo<128> { static constexpr int SLOTS = 6, BYTES = 16384; };
template <> struct BGeo<256> { static constexpr int SLOTS = 3, BYTES = 32768; };
template <> struct BGeo<192> { static constexpr int SLOTS = 4, BYTES = 24576; };
__host__ __device__ constexpr int first_slot(int s) { return s == 0 || s == 2 ? 2 : 0; }
__device__ __forceinline__ bool starts_local(int l, int s) { return s == 2 || s == 1 - l; }
__device__ __forceinline__ int token_shift(int j) { return ((j >> 1) & 1 ? 1 : -1) * (1 + (j >> 2)); }

struct Ctx {
  uint32_t sm;
  uint32_t bar;
  int i, j, r;
  int bid;
  uint32_t ep;
};

struct Pipe {
  uint32_t ko, kp;
  uint32_t po;
  uint32_t a0, a1, ar;
  uint32_t b;
  uint32_t keep;
  uint32_t sh, wide;
  uint32_t turn;
  int budget;
  uint32_t rel;
  bool signals;
  __device__ __forceinline__ void release() const {
    asm volatile("{\n.reg .pred p;\nsetp.ne.b32 p, %1, 0;\n@p mbarrier.arrive.shared::cluster.b64 _, [%0];\n}" :: "r"(rel + po), "r"((uint32_t)signals) : "memory");
  }
  __device__ __forceinline__ void drain() { wg_wait<0>(); release(); po = 64; }
};
__device__ __forceinline__ uint32_t desc_a(const Ctx& c, int off) { return ((c.sm & 0x3FFFFu) >> 4) + 0x400000u + (off >> 4); }
__device__ __forceinline__ uint32_t desc_b(const Ctx& c, int off) { return ((c.sm & 0x3FFFFu) >> 4) + 0x2000000u + ((SM_B + off) >> 4); }

template <int N, bool PRED, bool SHIFT = false, class Extra>
__device__ __forceinline__ void gemm_step(float (&acc)[N / 2], const Ctx& c, int wg, Pipe& p, Extra&& extra) {
  using G = BGeo<N>;
  const uint32_t fa = c.bar + 8 * BAR_FULLA + 64 * wg + p.ko, fb = c.bar + 8 * BAR_FULLB + p.ko;
#pragma unroll 1
  while (true) {
    uint32_t ready;
    asm volatile("{\n.reg .pred p, q;\nmbarrier.try_wait.parity.shared::cta.b64 p, [%1], %3;\nmbarrier.try_wait.parity.shared::cta.b64 q, [%2], %3;\n"
                 "and.pred p, p, q;\nselp.b32 %0, 1, 0, p;\n}" : "=r"(ready) : "r"(fa), "r"(fb), "r"(p.kp) : "memory");
    if (ready || --p.budget <= 0) break;
  }
  wg_fence();
  const uint32_t a = SHIFT ? p.a0 + (p.sh & 3) + (p.wide << 16) : p.a0, ak = SHIFT ? 128 + 2 * p.wide : 128;
  if constexpr (SHIFT) p.sh >>= 2;
  if constexpr (PRED) { Mma<N>::ss(acc, a, p.b, p.keep); p.keep = 1; } else Mma<N>::ss(acc, a, p.b);
#pragma unroll
  for (int kk = 1; kk < 4; kk++) Mma<N>::ss(acc, a + kk * ak, p.b + kk * 128);
  wg_commit();
  extra();
  wg_wait<1>();
  p.release();
  p.po = p.ko;
  p.ko = (p.ko + 8) & 63;
  p.kp ^= p.ko == 0;
  p.a0 = p.a1; p.a1 = p.ar;
  p.ar = p.ar == desc_a(c, SM_A + (NA - 1) * A_SLOT) + wg * NA * (A_SLOT >> 4) ? p.ar - (NA - 1) * (A_SLOT >> 4) : p.ar + (A_SLOT >> 4);
  p.b = p.b == desc_b(c, (G::SLOTS - 1) * G::BYTES) ? desc_b(c, 0) : p.b + (G::BYTES >> 4);
}
template <int N>
__device__ __forceinline__ void gemm_begin(const Ctx& c, int wg, int wq, Pipe& p, int s, bool local) {
  if (local) {
    fence_async_smem();
    named_bar(2 + wg, 128);
    mbar_arrive_if(c.bar + 8 * BAR_FULLA + 64 * wg + 8 * (threadIdx.x & 1), (threadIdx.x & 126) == 96);
    if (wq < 2) {
      mbar_wait(c.bar + 8 * (BAR_EMPTYA + 9 * wg + 8 - NA + wq), p.kp ^ 1, p.budget);
      if (elect_one()) {
        const uint32_t peer = mapa(c.sm, c.r ^ 1), bar = peer + SM_BAR + 8 * (BAR_FULLA + 8 * wg + 2 + wq);
        mbar_expect_tx_cluster(bar, 8192);
        bulk_copy_cluster(peer + (((wq ? p.a1 : p.a0) - desc_a(c, 0)) << 4), c.sm + SM_X + (2 * wg + wq) * 8192, 8192, bar);
      }
      __syncwarp();
    }
  }
  asm volatile("{\n.reg .pred p;\nsetp.ne.b32 p, %3, 0;\nselp.b32 %2, %0, %2, p;\nselp.b32 %0, %4, %0, p;\nselp.b32 %1, %5, %1, p;\n}"
               : "+r"(p.a0), "+r"(p.a1), "+r"(p.ar) : "r"((uint32_t)local), "r"(desc_a(c, SM_X) + wg * 1024), "r"(desc_a(c, SM_X + 8192) + wg * 1024));
  p.b = desc_b(c, first_slot(s) * BGeo<N>::BYTES);
}
template <class Hook>
__device__ __forceinline__ void yield_turn(const Ctx& c, int wg, Pipe& p, Hook&& hook) {
  if (wg == 1) p.drain();
  hook();
  if (wg == 1) mbar_wait(c.bar + 8 * BAR_TURN, p.turn, p.budget);
  p.turn ^= 1;
}
__device__ __forceinline__ void pass_turn(const Ctx& c, bool now) { mbar_arrive_if(c.bar + 8 * BAR_TURN, now && threadIdx.x == 96); }
struct Nop { __device__ __forceinline__ void operator()() const {} };
template <int N, bool PRED, bool SHIFT = false, class Hook, class Tail>
__device__ __forceinline__ void gemm_steps(float (&acc)[N / 2], const Ctx& c, int wg, Pipe& p, int count, int lead, Hook&& hook, Tail&& tail) {
#pragma unroll 1
  for (int n = count - lead; n > 0; n--) gemm_step<N, PRED, SHIFT>(acc, c, wg, p, Nop());
  yield_turn(c, wg, p, hook);
#pragma unroll 1
  for (int n = lead - 1; n >= 0; n--) {
    gemm_step<N, false, SHIFT>(acc, c, wg, p, Nop());
    pass_turn(c, n == 1);
  }
  tail();
  p.drain();
}

__device__ __forceinline__ void put_stat(float2* gdst, float s, float q, bool cond, uint32_t ep) {
  const float m = s * (1.f / 128), v = fmaxf(fmaf(-m, s, q), 0.f);
  asm volatile("{\n.reg .pred p;\nsetp.ne.b32 p, %3, 0;\n@p st.relaxed.gpu.global.v2.b32 [%0], {%1,%2};\n}"
               :: "l"(gdst), "r"(__float_as_uint(m)), "r"(tagged(v, ep)), "r"((uint32_t)cond) : "memory");
}
__device__ __forceinline__ void put_partial(const float (&v)[64], float2* gdst, uint32_t ep) {
  float s[4] = {v[0], v[1], v[2], v[3]}, q[4] = {v[0] * v[0], v[1] * v[1], v[2] * v[2], v[3] * v[3]};
#pragma unroll
  for (int x = 4; x < 64; x++) { s[x & 3] += v[x]; q[x & 3] = fmaf(v[x], v[x], q[x & 3]); }
  const bool odd = threadIdx.x & 1;
  const float s0 = s[0] + s[1], s1 = s[2] + s[3], q0 = q[0] + q[1], q1 = q[2] + q[3];
  float ss = (odd ? s1 : s0) + __shfl_xor_sync(0xffffffffu, odd ? s0 : s1, 1);
  float qq = (odd ? q1 : q0) + __shfl_xor_sync(0xffffffffu, odd ? q0 : q1, 1);
  ss += __shfl_xor_sync(0xffffffffu, ss, 2);
  qq += __shfl_xor_sync(0xffffffffu, qq, 2);
  put_stat(gdst + (odd ? 8 : 0), ss, qq, !(threadIdx.x & 2), ep);
}
struct RowStats {
  float2 p[4];
  __device__ __forceinline__ void load(const float2* r0, const float2* r1) {
#pragma unroll
    for (int x = 0; x < 4; x++)
      asm volatile("ld.relaxed.gpu.global.v2.f32 {%0,%1}, [%2];" : "=f"(p[x].x), "=f"(p[x].y) : "l"((x & 2 ? r1 : r0) + (x & 1) * SEQ) : "memory");
  }
  __device__ __forceinline__ void finish(const float2* r0, const float2* r1, int& budget, float2& s0, float2& s1) {
#pragma unroll 1
    while (!__all_sync(0xffffffffu, both_valid(__float_as_uint(p[0].y), __float_as_uint(p[1].y), 0) & both_valid(__float_as_uint(p[2].y), __float_as_uint(p[3].y), 0) & 1)) {
      if (--budget <= 0) break;
      load(r0, r1);
    }
#pragma unroll
    for (int h = 0; h < 2; h++) {
      const float2 a = p[2 * h], b = p[2 * h + 1];
      float m = a.x + b.x;
      m += __shfl_xor_sync(0xffffffffu, m, 1);
      m += __shfl_xor_sync(0xffffffffu, m, 2);
      m *= 0.125f;
      const float ea = a.x - m, eb = b.x - m;
      float t = fmaf(fmaf(ea, ea, eb * eb), 128.f, a.y + b.y);
      t += __shfl_xor_sync(0xffffffffu, t, 1);
      t += __shfl_xor_sync(0xffffffffu, t, 2);
      (h ? s1 : s0) = make_float2(m, rsqrt_fast(fmaf(t, 1.f / DM, LN_EPS)));
    }
  }
};

__device__ __forceinline__ void emit_panel(const uint32_t* v, char* gp, uint32_t pub) {
#pragma unroll
  for (int t = 0; t < 8; t++) { stg32(gp + t * CB_BYTES, v[2 * t]); stg32(gp + t * CB_BYTES + 128, v[2 * t + 1]); }
  __syncwarp();
  mbar_arrive_if(pub, (threadIdx.x & 31) == 0);
}
template <int NT>
__device__ __forceinline__ void stage_tiles(const uint32_t* v, uint32_t sp) {
#pragma unroll
  for (int t = 0; t < NT; t += 2) stsm_x4(sp + t * 1024, v[2 * t], v[2 * t + 1], v[2 * t + 2], v[2 * t + 3]);
}

__device__ __forceinline__ float late_zero(uint32_t addr) {
  float z; asm volatile("ld.volatile.shared.f32 %0, [%1];" : "=f"(z) : "r"(addr) : "memory"); return z;
}

template <int NT>
__device__ __forceinline__ void fold_tiles(uint32_t* v, const float* acc, const float2* cs_ptr, float2 st0, float2 st1) {
  const float n0 = -st0.x * st0.y, n1 = -st1.x * st1.y;
#pragma unroll
  for (int tile = 0; tile < NT; tile++) {
    const float2 cs = cs_ptr[tile * 4];
    float a = fmaf(acc[4 * tile + 0], st0.y, n0 * cs.x), b = fmaf(acc[4 * tile + 1], st0.y, n0 * cs.y);
    float cc = fmaf(acc[4 * tile + 2], st1.y, n1 * cs.x), d = fmaf(acc[4 * tile + 3], st1.y, n1 * cs.y);
    v[2 * tile] = pack_bf16(gelu_from_half(a), gelu_from_half(b));
    v[2 * tile + 1] = pack_bf16(gelu_from_half(cc), gelu_from_half(d));
  }
}

__device__ __forceinline__ void move_reg(uint32_t& d, uint32_t s) { asm volatile("mov.b32 %0, %1;" : "=r"(d) : "r"(s)); }
__device__ __forceinline__ void move_reg(float& d, float s) { asm volatile("mov.f32 %0, %1;" : "=f"(d) : "f"(s)); }
template <int CH, int LO, int HI, class T, int NR>
__device__ __forceinline__ void pick_group(T (&held)[NR], int idx) {
  if constexpr (HI - LO == 1) {
#pragma unroll
    for (int x = 0; x < CH; x++) move_reg(held[x], held[CH * LO + x]);
  } else {
    constexpr int MID = (LO + HI) / 2;
    if (idx < MID) pick_group<CH, LO, MID>(held, idx); else pick_group<CH, MID, HI>(held, idx);
  }
}
template <int CH>
__device__ __forceinline__ void gelu_chunk(const uint32_t* t, char* gp) {
#pragma unroll
  for (int x = 0; x < CH; x++) stg32(gp + (x >> 1) * CB_BYTES + (x & 1) * 128, gelu_pair_f16(t[x]));
}

#define REG_CONS 216
#define REG_PROD 72
__global__ void __cluster_dims__(2, 1, 1) __launch_bounds__(384, 1)
fused_kernel(const __grid_constant__ Params maps) {
  extern __shared__ __align__(1024) char smem[];
  const int tid = threadIdx.x, lane = tid & 31;
  const int warp = __shfl_sync(0xffffffffu, tid >> 5, 0), wg = warp >> 2;
  if (tid == 0) STAMP(48);
  const uint32_t sm0 = opaque(smem_u32(smem));
  if (elect_one()) {
    if (warp == 8) {
#pragma unroll
      for (int x = 0; x < CB_Q1; x++) mbar_init(sm0 + CV_BAR + 8 * x, 1);
      asm volatile("fence.mbarrier_init.release.cluster;" ::: "memory");
      load_k(maps, sm0, 0);
#pragma unroll
      for (int y = 0; y < 2; y++) {
        mbar_expect_tx(sm0 + CV_BAR + 8 * (CB_QA + y), 8192);
        load_kv(maps, sm0, y, CB_QA + y);
      }
#pragma unroll
      for (int x = CB_Q1; x < CB_ST0; x++) mbar_init(sm0 + CV_BAR + 8 * x, x < CB_QS ? 1 : x == CB_QS ? 8 : 3);
    } else if (warp == 9) {
#pragma unroll
      for (int x = CB_ST0; x < CB_COUNT; x++) mbar_init(sm0 + CV_BAR + 8 * x, x < CB_O1 ? 2 : x < CB_Y1 ? 3 : x < CB_P2 ? 8 : x == CB_P2 ? 10 : x == CB_YOUT ? 5 : x < CB_STAT ? 2 : 1);
    } else if (warp < 2) {
      asm volatile("prefetch.tensormap [%0];" :: "l"(&maps.m[M_K + warp]) : "memory");
    }
#pragma unroll
    for (int x = 0; x < 7; x++) mbar_init(sm0 + SM_BAR + 56 * warp + 8 * x, 1 << wg);
    asm volatile("fence.mbarrier_init.release.cluster;" ::: "memory");
    if (warp == 11) sts32(sm0 + SM_ZERO, 0);
  }
  static_assert(BAR_END == 84, "start-up work of 12 warps");
  __syncwarp();
  if (warp != 8) asm volatile("barrier.cluster.arrive.relaxed.aligned;" ::: "memory");
  conv_part(maps, sm0, warp);
  __syncwarp();
  asm volatile("barrier.cluster.wait.acquire.aligned;" ::: "memory");
  Ctx c;
  c.sm = sm0;
  c.bar = c.sm + SM_BAR;
  c.r = blockIdx.x & 1;
  {
    uint32_t role;
    asm volatile("ld.shared::cluster.u32 %0, [%1];" : "=r"(role) : "r"(mapa(sm0 + SM_ROLE, 0)) : "memory");
    role = __shfl_sync(0xffffffffu, role, 0);
    c.i = role >> 2; c.j = (role & 3) * 2 + c.r;
    c.bid = c.i * 8 + c.j;
    asm volatile("ld.shared.u32 %0, [%1];" : "=r"(c.ep) : "r"(c.sm + SM_EPOCH) : "memory");
  }

  if (tid == 0) MSTAMP(45);
  if (wg == 2) {
    reg_dealloc<REG_PROD>();
    int budget = SPIN_LIMIT;
    if (warp == 8) {
      const int hh = 16 * c.r + c.i;
      const uint32_t full0 = c.bar + 8 * (BAR_FULLA + c.r * 8), empty0 = c.bar + 8 * (BAR_EMPTYA + c.r * 9), full_peer = mapa(full0, c.r ^ 1);
      const uint32_t ring0 = c.sm + SM_A + c.r * NA * A_SLOT;
      const int nb = hh + (lane & 8 ? (lane & 2) - 1 : 0);
      const uint32_t* lf = g_flag + ((nb >= 0 && nb < 32 ? nb : hh) * 8 + (lane & 7)) * FS;
      const uint32_t* xf = g_xcnt + (hh + ((c.j >> 1) & 1) >= 16 ? 16 : 0) + (lane & 15);
      const uint32_t cb = c.sm + CV_BAR;
      if (lane == 0) mbar_arrive(cb + 8 * CB_XFREE);
      mbar_wait(cb + 8 * CB_Y2, 0, budget);
      if (lane == 0) STAMP(60);
      mbar_wait(cb + 8 * CB_P1, 0, budget);
      fence_async_smem();
      if (lane < 2) mbar_arrive_cluster(mapa(cb + 8 * CB_EARLY, lane));
      int seen = ld_relaxed(xf) - 8 * c.ep;
      mbar_wait(cb + 8 * (CB_EARLY + c.r), 0, budget);
      fence_async_global();
      if (lane == 0) MSTAMP(46);
      uint32_t slot = ring0;
      int k = 0;
#pragma unroll 1
      for (int ph = 0; ph < 10; ph++) {
        const int l = ph >= 5, s = ph - 5 * l;
        const CUtensorMap* m = &maps.m[s == 0 ? M_X3S + l : s == 1 ? M_H + l : s == 4 ? M_HID : M_X1];
        const uint32_t bytes = s == l ? A_SLOT : 8192;
        const bool local = starts_local(l, s);
        const int np = ph == 0 ? 1 : s == 4 ? 7 : 2, cnt = ph == 0 ? 16 : local ? 6 : 8, e0 = ph == 0 ? 2 * (c.j & 6) : (c.j & 6) + (local ? 2 : 0);
        const int need0 = ph == 0 ? 8 : 13 * l + (s == 0 ? 1 : s == 1 ? 3 : s == 4 ? 7 : 5);
        const uint32_t up = ph == 0 ? (c.j & 2 ? 0u : 0xffffu) : ph == 6 ? 0x33u : 0u;
        const uint32_t* fp = ph == 0 ? xf : lf;
        const uint32_t base = ph == 0 ? 8 * c.ep : 32 * c.ep;
        const bool polls = lane < (s == l ? 16 : 8);
        if (ph == 1) seen = 0;
        if (local) {
          k += 4;
          slot += slot >= ring0 + (NA - 2) * A_SLOT ? (2 - NA) * A_SLOT : 2 * A_SLOT;
        }
#pragma unroll 1
        for (int p = 0; p < np; p++) {
          uint32_t ready = __ballot_sync(0xffffffffu, seen >= need0 + p);
          if (ph == 6) ready &= ready >> 8;
#pragma unroll 1
          for (int x = 0; x < cnt; x++) {
            const int e = (e0 + x) & (ph == 0 ? 15 : 7);
            const uint32_t off = 8 * (k & 7);
            mbar_wait(empty0 + 8 * ((k - NA) & 7), ((k - NA) >> 3) & 1, budget);
            if (elect_one()) {
              mbar_expect_tx(full0 + off, bytes);
              mbar_expect_tx_cluster(full_peer + off, bytes);
            }
            if (!((ready >> e) & 1)) {
#pragma unroll 1
              do {
                if (polls) seen = ld_relaxed(fp) - base;
                ready = __ballot_sync(0xffffffffu, seen >= need0 + p);
                if (ph == 6) ready &= ready >> 8;
              } while (!((ready >> e) & 1) && --budget > 0);
              fence_async_global();
            }
            if (elect_one()) tma_2d_mc(slot, m, full0 + off, 128 * hh - 8 * ((up >> e) & 1), (np * e + p) * 8, (uint16_t)3);
            slot += slot == ring0 + (NA - 1) * A_SLOT ? (1 - NA) * A_SLOT : A_SLOT;
            k++;
          }
        }
      }
    } else if (warp == 9) {
      const uint32_t e8 = __funnelshift_r(0x76543210u, 0x76543210u, 4 * (c.j & 6));
      int k = 0;
#pragma unroll 1
      for (int ph = 0; ph < 10; ph++) {
        const int l = ph >= 5, s = ph - 5 * l;
        const uint32_t bytes = s == 2 ? 32768 : s == 3 ? 24576 : 16384, slots = s == 2 ? 3 : s == 3 ? 4 : 6;
        uint32_t dist = s == 2 ? 0x33333345u : s == 3 ? 0x44444333u : s == 4 ? 0x66655544u : 0x66666666u;
        const CUtensorMap* m = &maps.m[M_W1 + s];
        const int np = s == 4 ? 7 : 2;
        const int panel0 = s == 2 ? 7 * c.j : s == 3 ? 7 * c.j + 4 : 2 * c.j;
        const bool local = starts_local(l, s), direct = local || ph == 0;
        uint32_t slot = c.sm + SM_B + first_slot(s) * bytes;
#pragma unroll 1
        for (int o = 0; o < np; o++) {
          uint32_t tab = e8;
          if (local) tab = o ? (e8 >> 24 << 1) | ((e8 << 1) & 0xffffff00u) | 0x11111100u : (0x3210u ^ (c.j * 0x2222u)) | (e8 >> 8 << 17);
          if (ph == 0) tab = (c.j & 2 ? 0xba987654u : 0x76543210u) ^ (((c.j >> 2) ^ o) * 0x88888888u);
          const int mul = direct ? 64 : 64 * np, add = direct ? 0 : 64 * o;
#pragma unroll 1
          for (uint32_t bar = c.bar + 8 * BAR_FULLB; bar < c.bar + 8 * BAR_FULLB + 64; bar += 8) {
            const int last = k - (dist & 15), row = (tab & 15) * mul + add;
            if (last < 0) {
              mbar_wait(c.sm + CV_BAR + 8 * (k < 2 ? CB_XFREE : k < 5 ? CB_EARLY : CB_YOUT), 0, budget);
              fence_async_smem();
            }
            mbar_wait(c.bar + 8 * (BAR_EMPTYB + (last & 7)), (last >> 3) & 1, budget);
            if (elect_one()) {
              mbar_expect_tx(bar, bytes);
              tma_3d(slot, m, bar, 0, row, panel0);
            }
            slot += bytes;
            if (slot == c.sm + SM_B + 98304) slot = c.sm + SM_B;
            dist = __funnelshift_r(dist, slots, 4);
            tab >>= 4;
            k++;
          }
        }
      }
    } else {
      const int w = warp - 10;
      const int row0 = 64 * (16 * w + c.i);
      mbar_wait(c.sm + CV_BAR + 8 * CB_P2, 0, budget);
      if (w == 0) {
        fence_async_smem();
        if (lane < 2) mbar_arrive_cluster(mapa(c.sm + CV_BAR + 8 * CB_LATE, lane));
      } else if (elect_one()) {
        red_release(&g_xcnt[16 + (blockIdx.x >> 3)]);
        mbar_arrive(c.bar + 8 * BAR_REL);
        MSTAMP(44);
      }
      __syncwarp();
      uint32_t* my_flag = g_flag + ((16 * w + c.i) * 8 + c.j) * FS;
#pragma unroll 1
      for (int pc = 1; pc < 26; pc++) {
        const int l = pc >= 13, u = pc - 13 * l;
        if (pc > 1) {
          if (pc == 8) { reinterpret_cast<uint4*>(&g_part[2][c.j][row0])[lane] = make_uint4(0, 0, 0, 0); __syncwarp(); }
          mbar_wait(c.bar + 8 * (BAR_PUB + 13 * w + u), u < 2 ? 0 : l, budget);
          st_release(my_flag, 32 * c.ep + pc + 1);
        }
        if (pc == 12 && elect_one()) {
          const uint32_t bar = c.bar + 8 * (BAR_OWN + w);
          fence_async_global();
          mbar_expect_tx(bar, 16384);
          tma_2d(c.sm + SM_X + w * 16384, &maps.m[M_Y], bar, 2 * row0, 16 * c.j);
          tma_2d(c.sm + SM_X + w * 16384 + 8192, &maps.m[M_Y], bar, 2 * row0, 16 * c.j + 8);
        }
        __syncwarp();
        float2* part = &g_part[3 * l + (u == 5)][0][0];
#pragma unroll 1
        for (uint32_t jobs = pc == 1 ? 0x453u : u == 5 ? 0x421u : u == 1 ? 4u : 0u; jobs; jobs >>= 4) {
          const int job = jobs & 15;
          if (job < 3) {
            const int r = 32 * (job - 1) + lane;
            float s0 = 0.f, s1 = 0.f, q0 = 0.f, q1 = 0.f;
#pragma unroll 2
            for (int x = 0; x < 16; x++) {
              uint32_t v[4];
              asm volatile("ld.shared.v4.u32 {%0,%1,%2,%3}, [%4];" : "=r"(v[0]), "=r"(v[1]), "=r"(v[2]), "=r"(v[3])
                           : "r"(c.sm + SM_X + w * 16384 + x * 1024 + r * 16) : "memory");
#pragma unroll
              for (int y = 0; y < 4; y++) {
                const float a = bf_lo(v[y]), b = bf_hi(v[y]);
                s0 += a; s1 += b; q0 = fmaf(a, a, q0); q1 = fmaf(b, b, q1);
              }
            }
            put_stat(part + c.j * SEQ + row0 + r, s0 + s1, q0 + q1, true, c.ep);
          } else if (job == 3) {
            if (w == 1) {
              mbar_wait(c.sm + CV_BAR + 8 * CB_YOUT, 0, budget);
              mbar_wait(c.sm + CV_BAR + 8 * CB_EARLY, 0, budget);
              if (lane == 0) red_release(&g_xcnt[32 + (blockIdx.x >> 3)]);
              __syncwarp();
            }
            uint32_t xseen;
#pragma unroll 1
            do {
              asm volatile("ld.acquire.gpu.global.u32 %0, [%1];" : "=r"(xseen) : "l"(g_xcnt + 32 + (lane & 15)) : "memory");
            } while (!__all_sync(0xffffffffu, (int)(xseen - 8 * c.ep) >= 8) && --budget > 0);
            if (w == 0) {
              float4 s = make_float4(0.f, 0.f, 0.f, 0.f);
#pragma unroll
              for (int x = 0; x < 4; x++) {
                const float4 v = __ldcg(reinterpret_cast<const float4*>(&g_cs1[x][c.j * 128]) + lane);
                s.x += v.x; s.y += v.y; s.z += v.z; s.w += v.w;
              }
              reinterpret_cast<float4*>(smem + SM_CS1)[lane] = s;
            } else {
#pragma unroll
              for (int x = 0; x < 4; x++) {
                const int y = min(32 * x + lane, 111);
                const float4 v = __ldcg(reinterpret_cast<const float4*>(g_cs3 + c.j * 448) + y);
                if (x < 2) {
                  uint32_t* d = reinterpret_cast<uint32_t*>(smem + SM_CS3) + (y >> 2) * 8 + (y & 1) * 4 + ((y >> 1) & 1);
                  d[0] = pack_f16(v.x, v.y); d[2] = pack_f16(v.z, v.w);
                } else {
                  reinterpret_cast<float4*>(smem + SM_CS3)[y] = v;
                }
              }
            }
            __syncwarp();
            if (lane == 0) {
              mbar_arrive(c.bar + 8 * BAR_CS);
              if (c.bid == 0 && w == 0) { g_epoch = c.ep + 1; *reinterpret_cast<uint4*>(g_role) = make_uint4(0, 0, 0, 0); }
            }
          } else {
            const int r = job == 4 ? 2 * lane : token_shift(c.j) > 0 ? 64 : -2;
            const float2* src = part + min(max(row0 + r, 0), SEQ - 2);
            float4 v[8];
#pragma unroll 1
            do {
              uint32_t ok = 1;
#pragma unroll
              for (int x = 0; x < 8; x++) {
                asm volatile("ld.relaxed.gpu.global.v4.f32 {%0,%1,%2,%3}, [%4];" : "=f"(v[x].x), "=f"(v[x].y), "=f"(v[x].z), "=f"(v[x].w) : "l"(src + x * SEQ) : "memory");
                ok &= both_valid(__float_as_uint(v[x].y), __float_as_uint(v[x].w), c.ep);
              }
              if (__all_sync(0xffffffffu, ok)) break;
            } while (--budget > 0);
            float ma = 0.f, mb = 0.f, ta = 0.f, tb = 0.f;
#pragma unroll
            for (int x = 0; x < 8; x++) { ma += v[x].x; mb += v[x].z; }
            ma *= 0.125f; mb *= 0.125f;
#pragma unroll
            for (int x = 0; x < 8; x++) {
              const float ea = v[x].x - ma, eb = v[x].z - mb;
              ta += fmaf(128.f * ea, ea, __uint_as_float(__float_as_uint(v[x].y) | 1u));
              tb += fmaf(128.f * eb, eb, __uint_as_float(__float_as_uint(v[x].w) | 1u));
            }
            *reinterpret_cast<float4*>(smem + SM_RS + (68 * w + 2 + r) * 8) =
                make_float4(ma, rsqrt_fast(fmaf(ta, 1.f / DM, LN_EPS)), mb, rsqrt_fast(fmaf(tb, 1.f / DM, LN_EPS)));
            __syncwarp();
            if (job == 4 && lane == 0) mbar_arrive(c.sm + CV_BAR + 8 * (CB_STAT + w));
          }
        }
      }
    }
    cluster_exit_barrier();
  } else {
    reg_alloc<REG_CONS>();
#define WSTAMP(idx) do {} while (0)
    const int t = tid & 127, g = lane >> 2, qd = lane & 3;
    const int wrow = 64 * (16 * wg + c.i) + (t >> 5) * 16, row = wrow + g;
    const uint32_t frag = row * 16 + qd * 4 + c.j * 16 * CB_BYTES;
    const uint32_t stage = c.sm + SM_X + wg * 16384 + (lane >> 4) * 1024 + ((t >> 5) * 16 + (lane & 15)) * 16;
    const uint32_t pub = c.bar + 8 * (BAR_PUB + 13 * wg);
    const uint32_t rstat = c.sm + SM_RS + (68 * wg + 2 + (t >> 5) * 16 + g) * 8;
    Pipe p;
    p.ko = 0; p.kp = 0; p.po = 64; p.turn = 0; p.budget = SPIN_LIMIT;
    p.a0 = desc_a(c, SM_A) + wg * NA * (A_SLOT >> 4); p.a1 = p.a0 + (A_SLOT >> 4); p.ar = p.a1 + (A_SLOT >> 4);
    p.signals = t == 0 || t == 32 || t == 64;
    p.rel = mapa(c.bar + 8 * (t == 64 ? BAR_EMPTYB : BAR_EMPTYA + wg * 9), t == 32 ? c.r ^ 1 : c.r);
    auto fence_sched = [&]() { mbar_wait(c.bar + 8 * BAR_CS, 0, p.budget); };
    uint32_t x3[32];
    float acc[64];
#pragma unroll
    for (int x = 0; x < 64; x++) acc[x] = 0.f;
    WSTAMP(0);
    if (wg == 1) {
      mbar_wait(c.bar + 8 * BAR_REL, 0, p.budget);
#pragma unroll 2
      for (int x = 0; x < 8; x++)
        reinterpret_cast<uint4*>(g_y)[blockIdx.x * 2048 + 1024 + x * 128 + t] = reinterpret_cast<const uint4*>(smem + CV_K + 128 + 16384)[x * 128 + t];
      __syncwarp();
      mbar_arrive_if(c.sm + CV_BAR + 8 * CB_YOUT, lane == 0);
    }
    {
      mbar_wait(c.bar + 8 * (BAR_FULLA + 8 * wg + 2 * c.r), 0, p.budget);
      mbar_wait(c.bar + 8 * (BAR_FULLA + 8 * wg + 2 * c.r + 1), 0, p.budget);
      const uint32_t own = c.sm + SM_A + (wg * NA + 2 * c.r) * A_SLOT + (lane >> 4) * 1088 + ((token_shift(c.j) < 0 ? 4 : 0) + (t >> 5) * 16 + (lane & 15)) * 16;
#pragma unroll
      for (int x = 0; x < 32; x += 4) ldsm_x4(own + x * 544, x3[x], x3[x + 1], x3[x + 2], x3[x + 3]);
    }
#pragma unroll 1
    for (int ph = 0; ph < 6; ph++) {
      const int l = ph >= 3, s = ph - 3 * l;
      if (s < 2) {
        gemm_begin<128>(c, wg, warp & 3, p, s, s != l);
        p.keep = s;
        if (s == 0) {
          float sum[4] = {0.f, 0.f, 0.f, 0.f}, lo[4] = {0.f, 0.f, 0.f, 0.f}, hi[4] = {0.f, 0.f, 0.f, 0.f};
#pragma unroll
          for (int x = 0; x < 32; x += 4) {
            mma16816(sum, x3[x], x3[x + 1], x3[x + 2], x3[x + 3], 0x3f803f80u, 0x3f803f80u);
            mma16816(lo, x3[x], x3[x + 1], x3[x + 2], x3[x + 3], x3[x], x3[x + 2]);
            mma16816(hi, x3[x], x3[x + 1], x3[x + 2], x3[x + 3], x3[x + 1], x3[x + 3]);
          }
          put_stat(&g_part[3 * l][c.j][row], sum[0], (g & 1) ? lo[1] : lo[0], qd == (g >> 1), c.ep);
          put_stat(&g_part[3 * l][c.j][row + 8], sum[2], (g & 1) ? hi[3] : hi[2], qd == (g >> 1), c.ep);
          WSTAMP(1 + 16 * l);
        }
      } else {
        const uint32_t park = c.sm + SM_X + wg * 16384 + t * 16;
        char* hp = reinterpret_cast<char*>(g_hid) + frag + c.j * 40 * CB_BYTES;
        uint32_t held[64];
        float acc3[128];
        gemm_step<256, true>(acc3, c, wg, p, Nop());
        float2 s0 = make_float2(0.f, 0.f), s1 = s0;
        gemm_steps<256, false>(acc3, c, wg, p, 15, LEAD3, [&]() {
          mbar_wait(c.sm + CV_BAR + 8 * (CB_STAT + wg), 1, p.budget);
          s0 = lds_f2(rstat); s1 = lds_f2(rstat + 64);
          s0.y *= 0.5f; s1.y *= 0.5f;
#pragma unroll
          for (int x = 0; x < 8; x++) sts128(park + x * 2048, make_uint4(x3[4 * x], x3[4 * x + 1], x3[4 * x + 2], x3[4 * x + 3]));
        }, Nop());
        WSTAMP(6 + 16 * l);
#pragma unroll
        for (int x = 0; x < 64; x++) held[x] = pack_f16(acc3[2 * x] * ((x & 1) ? s1.y : s0.y), acc3[2 * x + 1] * ((x & 1) ? s1.y : s0.y));
        const uint32_t n0 = pack_f16(-s0.x * s0.y, -s0.x * s0.y), n1 = pack_f16(-s1.x * s1.y, -s1.x * s1.y);
        float accb[96];
#pragma unroll
        for (int x = 0; x < 24; x++) {
          const float2 cs = (reinterpret_cast<const float2*>(smem + SM_CS3 + 1024) + qd)[4 * x];
          accb[4 * x] = -s0.x * cs.x; accb[4 * x + 1] = -s0.x * cs.y; accb[4 * x + 2] = -s1.x * cs.x; accb[4 * x + 3] = -s1.x * cs.y;
        }
        pin(accb);
        WSTAMP(7 + 16 * l);
        gemm_begin<192>(c, wg, warp & 3, p, 3, false);
#pragma unroll 1
        for (int pn = 0; pn < 4; pn++) {
#pragma unroll
          for (int u = 0; u < 4; u++)
            gemm_step<192, false>(accb, c, wg, p, [&]() {
              const uint2 cs = reinterpret_cast<const uint2*>(smem + SM_CS3)[16 * pn + 4 * u + qd];
              const uint32_t h[4] = {hfma2(cs.x, n0, held[4 * u]), hfma2(cs.x, n1, held[4 * u + 1]), hfma2(cs.y, n0, held[4 * u + 2]), hfma2(cs.y, n1, held[4 * u + 3])};
              gelu_chunk<4>(h, hp + 2 * u * CB_BYTES);
            });
          hp += 8 * CB_BYTES;
          __syncwarp();
          mbar_arrive_if(pub + 8 * (6 + pn), lane == 0);
          pick_group<16, 1, 4>(held, pn + 1);
        }
        WSTAMP(8 + 16 * l);
#pragma unroll
        for (int x = 0; x < 8; x++) {
          uint4 v;
          asm volatile("ld.shared.v4.u32 {%0,%1,%2,%3}, [%4];" : "=r"(v.x), "=r"(v.y), "=r"(v.z), "=r"(v.w) : "r"(park + x * 2048) : "memory");
          acc[8 * x] = bf_lo(v.x); acc[8 * x + 1] = bf_hi(v.x); acc[8 * x + 2] = bf_lo(v.y); acc[8 * x + 3] = bf_hi(v.y);
          acc[8 * x + 4] = bf_lo(v.z); acc[8 * x + 5] = bf_hi(v.z); acc[8 * x + 6] = bf_lo(v.w); acc[8 * x + 7] = bf_hi(v.w);
        }
        pin(acc);
        WSTAMP(9 + 16 * l);
        gemm_begin<128>(c, wg, warp & 3, p, 4, false);
        gemm_step<128, false>(acc, c, wg, p, Nop());
        pin(accb);
#pragma unroll 1
        for (int hpn = 0; hpn < 6; hpn++) {
#pragma unroll
          for (int u = 0; u < 4; u++)
            gemm_step<128, false>(acc, c, wg, p, [&]() {
              const uint32_t h[2] = {pack_f16(accb[4 * u] * s0.y, accb[4 * u + 1] * s0.y), pack_f16(accb[4 * u + 2] * s1.y, accb[4 * u + 3] * s1.y)};
              gelu_chunk<2>(h, hp + u * CB_BYTES);
            });
          hp += 4 * CB_BYTES;
          __syncwarp();
          mbar_arrive_if(pub + 8 * (10 + (hpn >> 1)), (hpn & 1) && lane == 0);
          pick_group<16, 1, 6>(accb, hpn + 1);
        }
        WSTAMP(12 + 16 * l);
        p.keep = 1;
#pragma unroll
        for (int x = 0; x < 32; x++) x3[x] = 0;
      }
      p.sh = ph == 0 ? (token_shift(c.j) & 3) * 0x55555555u : ph == 4 ? __funnelshift_r(0xaa5faa5fu, 0xaa5faa5fu, 2 * (c.j & 6)) : 0;
      p.wide = s == l ? 4 : 0;
      float2 s0 = make_float2(0.f, 0.f), s1 = s0;
      gemm_steps<128, true, true>(acc, c, wg, p, s == 2 ? 31 : 16, (LEADS >> (4 * ph)) & 15, Nop(), [&]() {
        if (s == 0) {
          const int sh = l == 0 ? token_shift(c.j) : 0;
          mbar_wait(c.sm + CV_BAR + 8 * (CB_STAT + wg), 0, p.budget);
          s0 = lds_f2(rstat + 8 * sh); s1 = lds_f2(rstat + 8 * sh + 64);
          s0.y *= (row + sh < 0 ? 0.f : 0.5f) * rsqrt_fast(fmaxf(fmaf(-LN_EPS * s0.y, s0.y, 1.f), 0.f) + LN_EPS);
          s1.y *= (row + sh + 8 >= SEQ ? 0.f : 0.5f) * rsqrt_fast(fmaxf(fmaf(-LN_EPS * s1.y, s1.y, 1.f), 0.f) + LN_EPS);
          fence_sched();
        }
      });
      WSTAMP((s == 2 ? 10 : 2 + 2 * s) + 16 * l);
      if (s == 0) {
#pragma unroll
        for (int pn = 0; pn < 2; pn++) {
          uint32_t v[16];
          if (pn == 0) {
            fold_tiles<4>(v, acc, reinterpret_cast<const float2*>(smem + SM_CS1) + qd, s0, s1);
#pragma unroll
            for (int x = 0; x < 8; x++) stg32(reinterpret_cast<char*>(g_h) + frag + (x >> 1) * CB_BYTES + (x & 1) * 128, v[x]);
            fence_sched();
            fold_tiles<4>(v + 8, acc + 16, reinterpret_cast<const float2*>(smem + SM_CS1) + qd + 16, s0, s1);
#pragma unroll
            for (int x = 8; x < 16; x++) stg32(reinterpret_cast<char*>(g_h) + frag + (x >> 1) * CB_BYTES + (x & 1) * 128, v[x]);
            __syncwarp();
            mbar_arrive_if(pub + 8 * 2, lane == 0);
          } else {
            fold_tiles<8>(v, acc + 32, reinterpret_cast<const float2*>(smem + SM_CS1) + qd + 32, s0, s1);
            emit_panel(v, reinterpret_cast<char*>(g_h) + frag + 8 * CB_BYTES, pub + 8 * 3);
          }
          if (l == 0) stage_tiles<8>(v, stage + pn * 8192);
        }
        s0 = lds_f2(rstat); s1 = lds_f2(rstat + 64);
        const float nb0 = -s0.x * s0.y, nb1 = -s1.x * s1.y;
#pragma unroll
        for (int x = 0; x < 32; x++) {
          acc[2 * x] = fmaf(bf_lo(x3[x]), (x & 1) ? s1.y : s0.y, (x & 1) ? nb1 : nb0);
          acc[2 * x + 1] = fmaf(bf_hi(x3[x]), (x & 1) ? s1.y : s0.y, (x & 1) ? nb1 : nb0);
        }
        WSTAMP(3 + 16 * l);
      } else if (s == 1) {
        uint32_t v[32];
#pragma unroll
        for (int x = 0; x < 32; x++) v[x] = pack_bf16(acc[2 * x], acc[2 * x + 1]);
        emit_panel(v, reinterpret_cast<char*>(g_x1) + frag, pub + 8 * 4);
        stage_tiles<16>(v, stage);
        gemm_begin<256>(c, wg, warp & 3, p, 2, true);
        emit_panel(v + 16, reinterpret_cast<char*>(g_x1) + frag + 8 * CB_BYTES, pub + 8 * 5);
#pragma unroll
        for (int x = 0; x < 32; x++) x3[x] = badd2(x3[x], v[x]);
        WSTAMP(5 + 16 * l);
      } else if (l == 0) {
        put_partial(acc, &g_part[2][c.j][row], 0);
        WSTAMP(11);
        const float2* sp = &g_part[2][2 * qd][row];
        RowStats rs;
        rs.load(sp, sp + 8);
        float yf[64];
        mbar_wait(c.bar + 8 * (BAR_OWN + wg), 0, p.budget);
#pragma unroll
        for (int x = 0; x < 16; x++) {
          uint32_t y0, y1;
          asm volatile("ld.shared.v2.u32 {%0,%1}, [%2];" : "=r"(y0), "=r"(y1) : "r"(c.sm + SM_X + wg * 16384 + x * 1024 + t * 8) : "memory");
          yf[4 * x] = bf_lo(y0); yf[4 * x + 1] = bf_hi(y0); yf[4 * x + 2] = bf_lo(y1); yf[4 * x + 3] = bf_hi(y1);
        }
        pin(yf);
        rs.finish(sp, sp + 8, p.budget, s0, s1);
        WSTAMP(13);
        float nb0 = -s0.x * s0.y, nb1 = -s1.x * s1.y;
#pragma unroll
        for (int pn = 0; pn < 2; pn++) {
          if (pn == 1) { const float z = late_zero(c.sm + SM_ZERO); nb0 += z; nb1 += z; }
#pragma unroll
          for (int x = 16 * pn; x < 16 * pn + 16; x++) {
            const float r = (x & 1) ? s1.y : s0.y, nb = (x & 1) ? nb1 : nb0;
            x3[x] = pack_bf16(fmaf(fmaf(acc[2 * x], r, nb), yf[2 * x], acc[2 * x]), fmaf(fmaf(acc[2 * x + 1], r, nb), yf[2 * x + 1], acc[2 * x + 1]));
          }
          if (pn == 1) stage_tiles<16>(x3, stage);
          emit_panel(x3 + 16 * pn, reinterpret_cast<char*>(g_x3[1]) + frag + pn * 8 * CB_BYTES, pub + 8 * pn);
        }
      }
    }
    {
      const uint32_t ob = c.sm + SM_X + warp * 4096, oa = ob + (lane & 15) * 128 + (((lane >> 4) ^ (lane & 7)) << 4);
#pragma unroll
      for (int pn = 0; pn < 2; pn++) {
#pragma unroll
        for (int x = 0; x < 8; x += 2) {
          const float* a = acc + 32 * pn + 4 * x;
          stsm_x4((oa ^ (x << 4)) + pn * 2048, pack_bf16(a[0], a[1]), pack_bf16(a[2], a[3]), pack_bf16(a[4], a[5]), pack_bf16(a[6], a[7]));
        }
        fence_async_smem();
        __syncwarp();
        if (elect_one()) {
          tma_store_2d(&maps.m[M_OUT], ob + pn * 2048, c.j * 128 + 64 * pn, 64 * (16 * wg + c.i) + 16 * (warp & 3));
          if (pn == 1) {
            bulk_commit();
            asm volatile("cp.async.bulk.wait_group.read 0;" ::: "memory");
          }
        }
      }
    }
    WSTAMP(27);
    cluster_exit_barrier();
    WSTAMP(30);
  }
}

typedef CUresult (*EncodeFn)(CUtensorMap*, CUtensorMapDataType, cuuint32_t, void*, const cuuint64_t*, const cuuint64_t*, const cuuint32_t*,
                             const cuuint32_t*, CUtensorMapInterleave, CUtensorMapSwizzle, CUtensorMapL2promotion, CUtensorMapFloatOOBfill);

void encode(EncodeFn fn, CUtensorMap* m, CUtensorMapDataType type, const void* ptr, int rank, const cuuint64_t* dims, const cuuint64_t* strides,
            const cuuint32_t* box, CUtensorMapSwizzle swizzle, CUtensorMapL2promotion promo = CU_TENSOR_MAP_L2_PROMOTION_L2_128B) {
  const cuuint32_t es[3] = {1, 1, 1};
  fn(m, type, rank, const_cast<void*>(ptr), dims, strides, box, es, CU_TENSOR_MAP_INTERLEAVE_NONE, swizzle, promo, CU_TENSOR_MAP_FLOAT_OOB_FILL_NONE);
}
void map_act(EncodeFn fn, CUtensorMap* m, const void* ptr, int cols, int rows = 64) {
  const cuuint64_t dims[2] = {(cuuint64_t)SEQ * 2, (cuuint64_t)cols / 8}, st[1] = {(cuuint64_t)CB_BYTES};
  const cuuint32_t box[2] = {(cuuint32_t)rows * 2, 8};
  encode(fn, m, CU_TENSOR_MAP_DATA_TYPE_UINT64, ptr, 2, dims, st, box, CU_TENSOR_MAP_SWIZZLE_NONE);
}
void map_rows(EncodeFn fn, CUtensorMap* m, const void* ptr, int rows, int cols, int box_rows, int box_cols, CUtensorMapSwizzle swizzle,
              CUtensorMapL2promotion promo) {
  const cuuint64_t dims[2] = {(cuuint64_t)cols, (cuuint64_t)rows}, st[1] = {(cuuint64_t)cols * 2};
  const cuuint32_t box[2] = {(cuuint32_t)box_cols, (cuuint32_t)box_rows};
  encode(fn, m, CU_TENSOR_MAP_DATA_TYPE_BFLOAT16, ptr, 2, dims, st, box, swizzle, promo);
}
void map_w(EncodeFn fn, CUtensorMap* m, const void* ptr, int rows, int cols, int panels) {
  const cuuint64_t dims[3] = {64, (cuuint64_t)rows, (cuuint64_t)cols / 64}, st[2] = {(cuuint64_t)cols * 2, 128};
  const cuuint32_t box[3] = {64, 64, (cuuint32_t)panels};
  encode(fn, m, CU_TENSOR_MAP_DATA_TYPE_BFLOAT16, ptr, 3, dims, st, box, CU_TENSOR_MAP_SWIZZLE_128B);
}

}

extern "C" void kernel_launch(void* const* d_in, const int* in_sizes, int n_in, void* d_out, int out_size) {
  (void)in_sizes; (void)n_in; (void)out_size;
  const bf16* q = (const bf16*)d_in[0];
  const bf16* k = (const bf16*)d_in[1];
  const bf16* v = (const bf16*)d_in[2];
  const bf16* shift_k = (const bf16*)d_in[3];
  const bf16* ssm_k = (const bf16*)d_in[4];
  const bf16* ssm_d = (const bf16*)d_in[5];
  const bf16* w1 = (const bf16*)d_in[7];
  const bf16* w2 = (const bf16*)d_in[8];
  const bf16* w3 = (const bf16*)d_in[9];
  const bf16* w4 = (const bf16*)d_in[10];

  static EncodeFn fn = nullptr;
  static void *p_x3, *p_h, *p_x1, *p_hid, *p_y;
  if (!fn) {
    void* p = nullptr;
    cudaDriverEntryPointQueryResult qr;
    cudaGetDriverEntryPoint("cuTensorMapEncodeTiled", &p, cudaEnableDefault, &qr);
    fn = (EncodeFn)p;
    cudaGetSymbolAddress(&p_x3, g_x3);
    cudaGetSymbolAddress(&p_h, g_h);
    cudaGetSymbolAddress(&p_x1, g_x1);
    cudaGetSymbolAddress(&p_hid, g_hid);
    cudaGetSymbolAddress(&p_y, g_y);
    cudaFuncSetAttribute(fused_kernel, cudaFuncAttributeMaxDynamicSharedMemorySize, MEGA_SMEM);
  }
  Params maps;
  map_act(fn, &maps.m[M_X3B], (const bf16*)p_x3 + SEQ * DM, DM);
  map_act(fn, &maps.m[M_X3S], p_x3, DM, 68);
  map_act(fn, &maps.m[M_H], p_h, DM);
  map_act(fn, &maps.m[M_HS], p_h, DM, 68);
  map_act(fn, &maps.m[M_X1], p_x1, DM);
  map_act(fn, &maps.m[M_HID], p_hid, FF);
  map_act(fn, &maps.m[M_Y], p_y, DM);
  map_rows(fn, &maps.m[M_OUT], d_out, SEQ, DM, 16, 64, CU_TENSOR_MAP_SWIZZLE_128B, CU_TENSOR_MAP_L2_PROMOTION_L2_128B);
  map_w(fn, &maps.m[M_W1], w1, DM, DM, 2);
  map_w(fn, &maps.m[M_W2], w2, DM, DM, 2);
  map_w(fn, &maps.m[M_W3A], w3, DM, FF, 4);
  map_w(fn, &maps.m[M_W3B], w3, DM, FF, 3);
  map_w(fn, &maps.m[M_W4], w4, FF, DM, 2);

  map_rows(fn, &maps.m[M_K], k, SEQ, DM, 256, 8, CU_TENSOR_MAP_SWIZZLE_NONE, KV_PROMO);
  map_rows(fn, &maps.m[M_V], v, SEQ, DM, 256, 8, CU_TENSOR_MAP_SWIZZLE_NONE, KV_PROMO);
  map_rows(fn, &maps.m[M_Q], q, SEQ, DM, 256, 8, CU_TENSOR_MAP_SWIZZLE_NONE, KV_PROMO);
  map_rows(fn, &maps.m[M_W1C], w1, DM, DM, 256, 32, CU_TENSOR_MAP_SWIZZLE_64B, CU_TENSOR_MAP_L2_PROMOTION_L2_128B);
  map_rows(fn, &maps.m[M_W3C], w3, DM, FF, 256, 32, CU_TENSOR_MAP_SWIZZLE_64B, CU_TENSOR_MAP_L2_PROMOTION_L2_128B);
  maps.q = q; maps.shift_k = shift_k; maps.ssm_k = ssm_k; maps.ssm_d = ssm_d; maps.w2 = w2;
  fused_kernel<<<128, 384, MEGA_SMEM, cudaStreamPerThread>>>(maps);
}
```

```cpp
#include <cuda_runtime.h>
#include <cuda_bf16.h>
#include <cuda.h>
#include <stdint.h>

namespace {

typedef __nv_bfloat16 bf16;
constexpr int SEQ = 2048, DM = 1024, FF = 3584;
constexpr float LN_EPS = 1e-5f;

constexpr int CB_BYTES = SEQ * 16;
__device__ __align__(1024) bf16 g_x3[2][SEQ * DM];
__device__ __align__(1024) bf16 g_h[SEQ * DM];
__device__ __align__(1024) bf16 g_x1[SEQ * DM];
__device__ __align__(1024) bf16 g_hid[SEQ * FF];
__device__ __align__(1024) bf16 g_y[SEQ * DM];
__device__ __align__(128) float g_cs1[4][DM];
__device__ __align__(128) float g_cs3[FF];
__device__ __align__(128) uint32_t g_epoch;
__device__ __align__(128) float2 g_part[5][8][SEQ];
__device__ __align__(128) float2 g_qstat[SEQ];
__device__ __align__(128) uint32_t g_qcnt;
__device__ __align__(128) uint32_t g_xcnt[48];
constexpr int FS = 8;
__device__ __align__(128) uint32_t g_flag[32 * 8 * FS];
__device__ __align__(128) uint32_t g_role[4];

__device__ __forceinline__ uint32_t smem_u32(const void* p) { return (uint32_t)__cvta_generic_to_shared(p); }
__device__ __forceinline__ uint32_t opaque(uint32_t x) { uint32_t y; asm volatile("mov.u32 %0, %1;" : "=r"(y) : "r"(x)); return y; }
__device__ __forceinline__ void mbar_init(uint32_t bar, uint32_t cnt) { asm volatile("mbarrier.init.shared::cta.b64 [%0], %1;" :: "r"(bar), "r"(cnt)); }
__device__ __forceinline__ void mbar_expect_tx(uint32_t bar, uint32_t bytes) {
  asm volatile("mbarrier.arrive.expect_tx.shared::cta.b64 _, [%0], %1;" :: "r"(bar), "r"(bytes) : "memory");
}
__device__ __forceinline__ void mbar_expect_tx_cluster(uint32_t bar, uint32_t bytes) {
  asm volatile("mbarrier.arrive.expect_tx.shared::cluster.b64 _, [%0], %1;" :: "r"(bar), "r"(bytes) : "memory");
}
__device__ __forceinline__ void mbar_arrive_cluster(uint32_t bar) { asm volatile("mbarrier.arrive.shared::cluster.b64 _, [%0];" :: "r"(bar) : "memory"); }
__device__ __forceinline__ void mbar_arrive(uint32_t bar) { asm volatile("mbarrier.arrive.shared::cta.b64 _, [%0];" :: "r"(bar) : "memory"); }
__device__ __forceinline__ void mbar_arrive_if(uint32_t bar, bool cond) {
  asm volatile("{\n.reg .pred p;\nsetp.ne.b32 p, %1, 0;\n@p mbarrier.arrive.shared::cta.b64 _, [%0];\n}" :: "r"(bar), "r"((uint32_t)cond) : "memory");
}
constexpr int SPIN_LIMIT = 1 << 16;
__device__ __forceinline__ bool mbar_try(uint32_t bar, uint32_t parity) {
  uint32_t done;
  asm volatile("{\n.reg .pred p;\nmbarrier.try_wait.parity.shared::cta.b64 p, [%1], %2;\nselp.b32 %0, 1, 0, p;\n}"
               : "=r"(done) : "r"(bar), "r"(parity) : "memory");
  return done != 0;
}
__device__ __forceinline__ void mbar_wait(uint32_t bar, uint32_t parity, int& budget) {
#pragma unroll 1
  while (!mbar_try(bar, parity)) { if (--budget <= 0) break; }
}
__device__ __forceinline__ bool elect_one() {
  uint32_t p;
  asm volatile("{\n.reg .pred P;\nelect.sync _|P, 0xffffffff;\nselp.b32 %0, 1, 0, P;\n}" : "=r"(p));
  return p != 0;
}
__device__ __forceinline__ void fence_async_smem() { asm volatile("fence.proxy.async.shared::cta;" ::: "memory"); }
__device__ __forceinline__ void fence_async_global() { asm volatile("fence.proxy.async.global;" ::: "memory"); }
__device__ __forceinline__ void named_bar(int id, int n) { asm volatile("bar.sync %0, %1;" :: "r"(id), "r"(n) : "memory"); }
__device__ __forceinline__ uint4 ld_nc_u4(const void* p) {
  uint4 v; asm volatile("ld.global.nc.L1::no_allocate.v4.u32 {%0,%1,%2,%3}, [%4];" : "=r"(v.x), "=r"(v.y), "=r"(v.z), "=r"(v.w) : "l"(p)); return v;
}
__device__ __forceinline__ void tma_2d_mc(uint32_t dst, const CUtensorMap* m, uint32_t bar, int c0, int c1, uint16_t mask) {
  asm volatile("cp.async.bulk.tensor.2d.shared::cluster.global.mbarrier::complete_tx::bytes.multicast::cluster [%0], [%1, {%3, %4}], [%2], %5;"
               :: "r"(dst), "l"(m), "r"(bar), "r"(c0), "r"(c1), "h"(mask) : "memory");
}
__device__ __forceinline__ void tma_2d(uint32_t dst, const CUtensorMap* m, uint32_t bar, int c0, int c1) {
  asm volatile("cp.async.bulk.tensor.2d.shared::cluster.global.mbarrier::complete_tx::bytes [%0], [%1, {%3, %4}], [%2];"
               :: "r"(dst), "l"(m), "r"(bar), "r"(c0), "r"(c1) : "memory");
}
__device__ __forceinline__ void bulk_copy_cluster(uint32_t dst, uint32_t src, uint32_t bytes, uint32_t bar) {
  asm volatile("cp.async.bulk.shared::cluster.shared::cta.mbarrier::complete_tx::bytes [%0], [%1], %2, [%3];"
               :: "r"(dst), "r"(src), "r"(bytes), "r"(bar) : "memory");
}
__device__ __forceinline__ uint32_t mapa(uint32_t addr, uint32_t cta) {
  uint32_t r; asm volatile("mapa.shared::cluster.u32 %0, %1, %2;" : "=r"(r) : "r"(addr), "r"(cta)); return r;
}
__device__ __forceinline__ void bulk_store(void* dst, uint32_t src, uint32_t bytes) {
  asm volatile("cp.async.bulk.global.shared::cta.bulk_group [%0], [%1], %2;" :: "l"(dst), "r"(src), "r"(bytes) : "memory");
}
__device__ __forceinline__ void tma_3d(uint32_t dst, const CUtensorMap* m, uint32_t bar, int c0, int c1, int c2) {
  asm volatile("cp.async.bulk.tensor.3d.shared::cluster.global.mbarrier::complete_tx::bytes [%0], [%1, {%3, %4, %5}], [%2];"
               :: "r"(dst), "l"(m), "r"(bar), "r"(c0), "r"(c1), "r"(c2) : "memory");
}
__device__ __forceinline__ void tma_store_2d(const CUtensorMap* m, uint32_t src, int c0, int c1) {
  asm volatile("cp.async.bulk.tensor.2d.global.shared::cta.bulk_group [%0, {%2, %3}], [%1];" :: "l"(m), "r"(src), "r"(c0), "r"(c1) : "memory");
}
__device__ __forceinline__ void bulk_commit() { asm volatile("cp.async.bulk.commit_group;" ::: "memory"); }
__device__ __forceinline__ void bulk_wait_all() { asm volatile("cp.async.bulk.wait_group 0;" ::: "memory"); }
__device__ __forceinline__ void prefetch_l2(const void* p, uint32_t bytes) { asm volatile("cp.async.bulk.prefetch.L2.global [%0], %1;" :: "l"(p), "r"(bytes) : "memory"); }
__device__ __forceinline__ void cluster_exit_barrier() {
  __syncwarp();
  asm volatile("barrier.cluster.arrive.relaxed;\nbarrier.cluster.wait;" ::: "memory");
}
__device__ __forceinline__ void wg_fence() { asm volatile("wgmma.fence.sync.aligned;" ::: "memory"); }
__device__ __forceinline__ void wg_commit() { asm volatile("wgmma.commit_group.sync.aligned;" ::: "memory"); }
template <int N> __device__ __forceinline__ void wg_wait() { asm volatile("wgmma.wait_group.sync.aligned %0;" :: "n"(N) : "memory"); }
template <int R> __device__ __forceinline__ void reg_alloc() { asm volatile("setmaxnreg.inc.sync.aligned.u32 %0;" :: "n"(R)); }
template <int R> __device__ __forceinline__ void reg_dealloc() { asm volatile("setmaxnreg.dec.sync.aligned.u32 %0;" :: "n"(R)); }
__device__ __forceinline__ void ldsm_x4(uint32_t addr, uint32_t& r0, uint32_t& r1, uint32_t& r2, uint32_t& r3) {
  asm volatile("ldmatrix.sync.aligned.m8n8.x4.shared.b16 {%0,%1,%2,%3}, [%4];" : "=r"(r0), "=r"(r1), "=r"(r2), "=r"(r3) : "r"(addr));
}
__device__ __forceinline__ void ldsm_x4_t(uint32_t addr, uint32_t& r0, uint32_t& r1, uint32_t& r2, uint32_t& r3) {
  asm volatile("ldmatrix.sync.aligned.m8n8.x4.trans.shared.b16 {%0,%1,%2,%3}, [%4];" : "=r"(r0), "=r"(r1), "=r"(r2), "=r"(r3) : "r"(addr));
}
__device__ __forceinline__ void stsm_x4(uint32_t addr, uint32_t r0, uint32_t r1, uint32_t r2, uint32_t r3) {
  asm volatile("stmatrix.sync.aligned.m8n8.x4.shared.b16 [%0], {%1,%2,%3,%4};" :: "r"(addr), "r"(r0), "r"(r1), "r"(r2), "r"(r3) : "memory");
}
__device__ __forceinline__ float2 lds_f2(uint32_t addr) { float2 v; asm volatile("ld.shared.v2.f32 {%0,%1}, [%2];" : "=f"(v.x), "=f"(v.y) : "r"(addr)); return v; }
__device__ __forceinline__ void sts16(uint32_t addr, uint16_t v) { asm volatile("st.shared.u16 [%0], %1;" :: "r"(addr), "h"(v) : "memory"); }
__device__ __forceinline__ void sts32(uint32_t addr, uint32_t v) { asm volatile("st.shared.u32 [%0], %1;" :: "r"(addr), "r"(v) : "memory"); }
__device__ __forceinline__ void sts128(uint32_t addr, uint4 v) {
  asm volatile("st.shared.v4.u32 [%0], {%1,%2,%3,%4};" :: "r"(addr), "r"(v.x), "r"(v.y), "r"(v.z), "r"(v.w) : "memory");
}
__device__ __forceinline__ void mma16816(float (&d)[4], uint32_t a0, uint32_t a1, uint32_t a2, uint32_t a3, uint32_t b0, uint32_t b1) {
  asm("mma.sync.aligned.m16n8k16.row.col.f32.bf16.bf16.f32 {%0,%1,%2,%3}, {%4,%5,%6,%7}, {%8,%9}, {%0,%1,%2,%3};"
               : "+f"(d[0]), "+f"(d[1]), "+f"(d[2]), "+f"(d[3]) : "r"(a0), "r"(a1), "r"(a2), "r"(a3), "r"(b0), "r"(b1));
}
__device__ __forceinline__ uint32_t pack_bf16(float lo, float hi) {
  uint32_t r; asm("cvt.rn.bf16x2.f32 %0, %1, %2;" : "=r"(r) : "f"(hi), "f"(lo)); return r;
}
__device__ __forceinline__ float bf_lo(uint32_t v) { return __uint_as_float(v << 16); }
__device__ __forceinline__ float bf_hi(uint32_t v) { return __uint_as_float(v & 0xffff0000u); }
__device__ __forceinline__ uint32_t bmul2(uint32_t a, uint32_t b) { uint32_t r; asm("mul.rn.bf16x2 %0, %1, %2;" : "=r"(r) : "r"(a), "r"(b)); return r; }
__device__ __forceinline__ uint32_t badd2(uint32_t a, uint32_t b) { uint32_t r; asm("add.rn.bf16x2 %0, %1, %2;" : "=r"(r) : "r"(a), "r"(b)); return r; }
#define STAMP(idx) do {} while (0)
#define MSTAMP(idx) do {} while (0)
#define BSTAMP(idx, saddr) do {} while (0)

__device__ __forceinline__ uint32_t pack_f16(float lo, float hi) {
  uint32_t r; asm("cvt.rn.satfinite.f16x2.f32 %0, %1, %2;" : "=r"(r) : "f"(hi), "f"(lo)); return r;
}
__device__ __forceinline__ uint32_t hfma2(uint32_t a, uint32_t b, uint32_t c) { uint32_t r; asm("fma.rn.f16x2 %0, %1, %2, %3;" : "=r"(r) : "r"(a), "r"(b), "r"(c)); return r; }
__device__ __forceinline__ uint32_t gelu_pair_f16(uint32_t h) {
  const uint32_t c0 = 0x3e623e62u, c1 = 0x34913491u;
  uint32_t u, p, z, t, r, o;
  asm("mul.rn.f16x2 %0, %1, %1;" : "=r"(u) : "r"(h));
  asm("fma.rn.f16x2 %0, %1, %2, %3;" : "=r"(p) : "r"(u), "r"(c1), "r"(c0));
  asm("mul.rn.f16x2 %0, %1, %2;" : "=r"(z) : "r"(h), "r"(p));
  asm("tanh.approx.f16x2 %0, %1;" : "=r"(t) : "r"(z));
  asm("fma.rn.f16x2 %0, %1, %2, %1;" : "=r"(r) : "r"(h), "r"(t));
  float lo, hi;
  asm("{\n.reg .f16 a, b;\nmov.b32 {a, b}, %2;\ncvt.f32.f16 %0, a;\ncvt.f32.f16 %1, b;\n}" : "=f"(lo), "=f"(hi) : "r"(r));
  asm("cvt.rn.bf16x2.f32 %0, %1, %2;" : "=r"(o) : "f"(hi), "f"(lo));
  return o;
}
__device__ __forceinline__ float gelu_from_half(float h) {
  const float c0 = 2.f * 0.7978845608028654f, c1 = 8.f * 0.7978845608028654f * 0.044715f;
  float z = h * fmaf(h * h, c1, c0);
  float t; asm("tanh.approx.f32 %0, %1;" : "=f"(t) : "f"(z));
  return fmaf(h, t, h);
}
__device__ __forceinline__ void wgmma_ss_n128(float (&d)[64], uint32_t a_lo, uint32_t b_lo) {
  asm volatile(
    "{\n.reg .b64 da, db;\nmov.b64 da, {%64, 8};\nmov.b64 db, {%65, 0x40000040};\n"
    "wgmma.mma_async.sync.aligned.m64n128k16.f32.bf16.bf16 "
    "{%0, %1, %2, %3, %4, %5, %6, %7, %8, %9, %10, %11, %12, %13, %14, %15, "
    "%16, %17, %18, %19, %20, %21, %22, %23, %24, %25, %26, %27, %28, %29, %30, %31, "
    "%32, %33, %34, %35, %36, %37, %38, %39, %40, %41, %42, %43, %44, %45, %46, %47, "
    "%48, %49, %50, %51, %52, %53, %54, %55, %56, %57, %58, %59, %60, %61, %62, %63}, "
    "da, db, 1, 1, 1, 0, 1;\n}\n"
    : "+f"(d[0]), "+f"(d[1]), "+f"(d[2]), "+f"(d[3]), "+f"(d[4]), "+f"(d[5]), "+f"(d[6]), "+f"(d[7]),
      "+f"(d[8]), "+f"(d[9]), "+f"(d[10]), "+f"(d[11]), "+f"(d[12]), "+f"(d[13]), "+f"(d[14]), "+f"(d[15]),
      "+f"(d[16]), "+f"(d[17]), "+f"(d[18]), "+f"(d[19]), "+f"(d[20]), "+f"(d[21]), "+f"(d[22]), "+f"(d[23]),
      "+f"(d[24]), "+f"(d[25]), "+f"(d[26]), "+f"(d[27]), "+f"(d[28]), "+f"(d[29]), "+f"(d[30]), "+f"(d[31]),
      "+f"(d[32]), "+f"(d[33]), "+f"(d[34]), "+f"(d[35]), "+f"(d[36]), "+f"(d[37]), "+f"(d[38]), "+f"(d[39]),
      "+f"(d[40]), "+f"(d[41]), "+f"(d[42]), "+f"(d[43]), "+f"(d[44]), "+f"(d[45]), "+f"(d[46]), "+f"(d[47]),
      "+f"(d[48]), "+f"(d[49]), "+f"(d[50]), "+f"(d[51]), "+f"(d[52]), "+f"(d[53]), "+f"(d[54]), "+f"(d[55]),
      "+f"(d[56]), "+f"(d[57]), "+f"(d[58]), "+f"(d[59]), "+f"(d[60]), "+f"(d[61]), "+f"(d[62]), "+f"(d[63])
    : "r"(a_lo), "r"(b_lo));
}
__device__ __forceinline__ void wgmma_ss_n192(float (&d)[96], uint32_t a_lo, uint32_t b_lo) {
  asm volatile(
    "{\n.reg .b64 da, db;\nmov.b64 da, {%96, 8};\nmov.b64 db, {%97, 0x40000040};\n"
    "wgmma.mma_async.sync.aligned.m64n192k16.f32.bf16.bf16 "
    "{%0, %1, %2, %3, %4, %5, %6, %7, %8, %9, %10, %11, %12, %13, %14, %15, "
    "%16, %17, %18, %19, %20, %21, %22, %23, %24, %25, %26, %27, %28, %29, %30, %31, "
    "%32, %33, %34, %35, %36, %37, %38, %39, %40, %41, %42, %43, %44, %45, %46, %47, "
    "%48, %49, %50, %51, %52, %53, %54, %55, %56, %57, %58, %59, %60, %61, %62, %63, "
    "%64, %65, %66, %67, %68, %69, %70, %71, %72, %73, %74, %75, %76, %77, %78, %79, "
    "%80, %81, %82, %83, %84, %85, %86, %87, %88, %89, %90, %91, %92, %93, %94, %95}, "
    "da, db, 1, 1, 1, 0, 1;\n}\n"
    : "+f"(d[0]), "+f"(d[1]), "+f"(d[2]), "+f"(d[3]), "+f"(d[4]), "+f"(d[5]), "+f"(d[6]), "+f"(d[7]),
      "+f"(d[8]), "+f"(d[9]), "+f"(d[10]), "+f"(d[11]), "+f"(d[12]), "+f"(d[13]), "+f"(d[14]), "+f"(d[15]),
      "+f"(d[16]), "+f"(d[17]), "+f"(d[18]), "+f"(d[19]), "+f"(d[20]), "+f"(d[21]), "+f"(d[22]), "+f"(d[23]),
      "+f"(d[24]), "+f"(d[25]), "+f"(d[26]), "+f"(d[27]), "+f"(d[28]), "+f"(d[29]), "+f"(d[30]), "+f"(d[31]),
      "+f"(d[32]), "+f"(d[33]), "+f"(d[34]), "+f"(d[35]), "+f"(d[36]), "+f"(d[37]), "+f"(d[38]), "+f"(d[39]),
      "+f"(d[40]), "+f"(d[41]), "+f"(d[42]), "+f"(d[43]), "+f"(d[44]), "+f"(d[45]), "+f"(d[46]), "+f"(d[47]),
      "+f"(d[48]), "+f"(d[49]), "+f"(d[50]), "+f"(d[51]), "+f"(d[52]), "+f"(d[53]), "+f"(d[54]), "+f"(d[55]),
      "+f"(d[56]), "+f"(d[57]), "+f"(d[58]), "+f"(d[59]), "+f"(d[60]), "+f"(d[61]), "+f"(d[62]), "+f"(d[63]),
      "+f"(d[64]), "+f"(d[65]), "+f"(d[66]), "+f"(d[67]), "+f"(d[68]), "+f"(d[69]), "+f"(d[70]), "+f"(d[71]),
      "+f"(d[72]), "+f"(d[73]), "+f"(d[74]), "+f"(d[75]), "+f"(d[76]), "+f"(d[77]), "+f"(d[78]), "+f"(d[79]),
      "+f"(d[80]), "+f"(d[81]), "+f"(d[82]), "+f"(d[83]), "+f"(d[84]), "+f"(d[85]), "+f"(d[86]), "+f"(d[87]),
      "+f"(d[88]), "+f"(d[89]), "+f"(d[90]), "+f"(d[91]), "+f"(d[92]), "+f"(d[93]), "+f"(d[94]), "+f"(d[95])
    : "r"(a_lo), "r"(b_lo));
}
__device__ __forceinline__ void wgmma_ss_n256(float (&d)[128], uint32_t a_lo, uint32_t b_lo) {
  asm volatile(
    "{\n.reg .b64 da, db;\nmov.b64 da, {%128, 8};\nmov.b64 db, {%129, 0x40000040};\n"
    "wgmma.mma_async.sync.aligned.m64n256k16.f32.bf16.bf16 "
    "{%0, %1, %2, %3, %4, %5, %6, %7, %8, %9, %10, %11, %12, %13, %14, %15, "
    "%16, %17, %18, %19, %20, %21, %22, %23, %24, %25, %26, %27, %28, %29, %30, %31, "
    "%32, %33, %34, %35, %36, %37, %38, %39, %40, %41, %42, %43, %44, %45, %46, %47, "
    "%48, %49, %50, %51, %52, %53, %54, %55, %56, %57, %58, %59, %60, %61, %62, %63, "
    "%64, %65, %66, %67, %68, %69, %70, %71, %72, %73, %74, %75, %76, %77, %78, %79, "
    "%80, %81, %82, %83, %84, %85, %86, %87, %88, %89, %90, %91, %92, %93, %94, %95, "
    "%96, %97, %98, %99, %100, %101, %102, %103, %104, %105, %106, %107, %108, %109, %110, %111, "
    "%112, %113, %114, %115, %116, %117, %118, %119, %120, %121, %122, %123, %124, %125, %126, %127}, "
    "da, db, 1, 1, 1, 0, 1;\n}\n"
    : "+f"(d[0]), "+f"(d[1]), "+f"(d[2]), "+f"(d[3]), "+f"(d[4]), "+f"(d[5]), "+f"(d[6]), "+f"(d[7]),
      "+f"(d[8]), "+f"(d[9]), "+f"(d[10]), "+f"(d[11]), "+f"(d[12]), "+f"(d[13]), "+f"(d[14]), "+f"(d[15]),
      "+f"(d[16]), "+f"(d[17]), "+f"(d[18]), "+f"(d[19]), "+f"(d[20]), "+f"(d[21]), "+f"(d[22]), "+f"(d[23]),
      "+f"(d[24]), "+f"(d[25]), "+f"(d[26]), "+f"(d[27]), "+f"(d[28]), "+f"(d[29]), "+f"(d[30]), "+f"(d[31]),
      "+f"(d[32]), "+f"(d[33]), "+f"(d[34]), "+f"(d[35]), "+f"(d[36]), "+f"(d[37]), "+f"(d[38]), "+f"(d[39]),
      "+f"(d[40]), "+f"(d[41]), "+f"(d[42]), "+f"(d[43]), "+f"(d[44]), "+f"(d[45]), "+f"(d[46]), "+f"(d[47]),
      "+f"(d[48]), "+f"(d[49]), "+f"(d[50]), "+f"(d[51]), "+f"(d[52]), "+f"(d[53]), "+f"(d[54]), "+f"(d[55]),
      "+f"(d[56]), "+f"(d[57]), "+f"(d[58]), "+f"(d[59]), "+f"(d[60]), "+f"(d[61]), "+f"(d[62]), "+f"(d[63]),
      "+f"(d[64]), "+f"(d[65]), "+f"(d[66]), "+f"(d[67]), "+f"(d[68]), "+f"(d[69]), "+f"(d[70]), "+f"(d[71]),
      "+f"(d[72]), "+f"(d[73]), "+f"(d[74]), "+f"(d[75]), "+f"(d[76]), "+f"(d[77]), "+f"(d[78]), "+f"(d[79]),
      "+f"(d[80]), "+f"(d[81]), "+f"(d[82]), "+f"(d[83]), "+f"(d[84]), "+f"(d[85]), "+f"(d[86]), "+f"(d[87]),
      "+f"(d[88]), "+f"(d[89]), "+f"(d[90]), "+f"(d[91]), "+f"(d[92]), "+f"(d[93]), "+f"(d[94]), "+f"(d[95]),
      "+f"(d[96]), "+f"(d[97]), "+f"(d[98]), "+f"(d[99]), "+f"(d[100]), "+f"(d[101]), "+f"(d[102]), "+f"(d[103]),
      "+f"(d[104]), "+f"(d[105]), "+f"(d[106]), "+f"(d[107]), "+f"(d[108]), "+f"(d[109]), "+f"(d[110]), "+f"(d[111]),
      "+f"(d[112]), "+f"(d[113]), "+f"(d[114]), "+f"(d[115]), "+f"(d[116]), "+f"(d[117]), "+f"(d[118]), "+f"(d[119]),
      "+f"(d[120]), "+f"(d[121]), "+f"(d[122]), "+f"(d[123]), "+f"(d[124]), "+f"(d[125]), "+f"(d[126]), "+f"(d[127])
    : "r"(a_lo), "r"(b_lo));
}
__device__ __forceinline__ void wgmma_ss_n128_p(float (&d)[64], uint32_t a_lo, uint32_t b_lo, uint32_t keep) {
  asm volatile(
    "{\n.reg .pred p;\nsetp.ne.b32 p, %66, 0;\n"
    "{\n.reg .b64 da, db;\nmov.b64 da, {%64, 8};\nmov.b64 db, {%65, 0x40000040};\n"
    "wgmma.mma_async.sync.aligned.m64n128k16.f32.bf16.bf16 "
    "{%0, %1, %2, %3, %4, %5, %6, %7, %8, %9, %10, %11, %12, %13, %14, %15, "
    "%16, %17, %18, %19, %20, %21, %22, %23, %24, %25, %26, %27, %28, %29, %30, %31, "
    "%32, %33, %34, %35, %36, %37, %38, %39, %40, %41, %42, %43, %44, %45, %46, %47, "
    "%48, %49, %50, %51, %52, %53, %54, %55, %56, %57, %58, %59, %60, %61, %62, %63}, "
    "da, db, p, 1, 1, 0, 1;\n}\n}\n"
    : "+f"(d[0]), "+f"(d[1]), "+f"(d[2]), "+f"(d[3]), "+f"(d[4]), "+f"(d[5]), "+f"(d[6]), "+f"(d[7]),
      "+f"(d[8]), "+f"(d[9]), "+f"(d[10]), "+f"(d[11]), "+f"(d[12]), "+f"(d[13]), "+f"(d[14]), "+f"(d[15]),
      "+f"(d[16]), "+f"(d[17]), "+f"(d[18]), "+f"(d[19]), "+f"(d[20]), "+f"(d[21]), "+f"(d[22]), "+f"(d[23]),
      "+f"(d[24]), "+f"(d[25]), "+f"(d[26]), "+f"(d[27]), "+f"(d[28]), "+f"(d[29]), "+f"(d[30]), "+f"(d[31]),
      "+f"(d[32]), "+f"(d[33]), "+f"(d[34]), "+f"(d[35]), "+f"(d[36]), "+f"(d[37]), "+f"(d[38]), "+f"(d[39]),
      "+f"(d[40]), "+f"(d[41]), "+f"(d[42]), "+f"(d[43]), "+f"(d[44]), "+f"(d[45]), "+f"(d[46]), "+f"(d[47]),
      "+f"(d[48]), "+f"(d[49]), "+f"(d[50]), "+f"(d[51]), "+f"(d[52]), "+f"(d[53]), "+f"(d[54]), "+f"(d[55]),
      "+f"(d[56]), "+f"(d[57]), "+f"(d[58]), "+f"(d[59]), "+f"(d[60]), "+f"(d[61]), "+f"(d[62]), "+f"(d[63])
    : "r"(a_lo), "r"(b_lo), "r"(keep));
}
__device__ __forceinline__ void wgmma_ss_n256_first(float (&d)[128], uint32_t a_lo, uint32_t b_lo) {
  asm volatile(
    "{\n.reg .b64 da, db;\nmov.b64 da, {%128, 8};\nmov.b64 db, {%129, 0x40000040};\n"
    "mov.b32 %0, 0; mov.b32 %1, 0; mov.b32 %2, 0; mov.b32 %3, 0; mov.b32 %4, 0; mov.b32 %5, 0; mov.b32 %6, 0; mov.b32 %7, 0;\n"
    "mov.b32 %8, 0; mov.b32 %9, 0; mov.b32 %10, 0; mov.b32 %11, 0; mov.b32 %12, 0; mov.b32 %13, 0; mov.b32 %14, 0; mov.b32 %15, 0;\n"
    "mov.b32 %16, 0; mov.b32 %17, 0; mov.b32 %18, 0; mov.b32 %19, 0; mov.b32 %20, 0; mov.b32 %21, 0; mov.b32 %22, 0; mov.b32 %23, 0;\n"
    "mov.b32 %24, 0; mov.b32 %25, 0; mov.b32 %26, 0; mov.b32 %27, 0; mov.b32 %28, 0; mov.b32 %29, 0; mov.b32 %30, 0; mov.b32 %31, 0;\n"
    "mov.b32 %32, 0; mov.b32 %33, 0; mov.b32 %34, 0; mov.b32 %35, 0; mov.b32 %36, 0; mov.b32 %37, 0; mov.b32 %38, 0; mov.b32 %39, 0;\n"
    "mov.b32 %40, 0; mov.b32 %41, 0; mov.b32 %42, 0; mov.b32 %43, 0; mov.b32 %44, 0; mov.b32 %45, 0; mov.b32 %46, 0; mov.b32 %47, 0;\n"
    "mov.b32 %48, 0; mov.b32 %49, 0; mov.b32 %50, 0; mov.b32 %51, 0; mov.b32 %52, 0; mov.b32 %53, 0; mov.b32 %54, 0; mov.b32 %55, 0;\n"
    "mov.b32 %56, 0; mov.b32 %57, 0; mov.b32 %58, 0; mov.b32 %59, 0; mov.b32 %60, 0; mov.b32 %61, 0; mov.b32 %62, 0; mov.b32 %63, 0;\n"
    "mov.b32 %64, 0; mov.b32 %65, 0; mov.b32 %66, 0; mov.b32 %67, 0; mov.b32 %68, 0; mov.b32 %69, 0; mov.b32 %70, 0; mov.b32 %71, 0;\n"
    "mov.b32 %72, 0; mov.b32 %73, 0; mov.b32 %74, 0; mov.b32 %75, 0; mov.b32 %76, 0; mov.b32 %77, 0; mov.b32 %78, 0; mov.b32 %79, 0;\n"
    "mov.b32 %80, 0; mov.b32 %81, 0; mov.b32 %82, 0; mov.b32 %83, 0; mov.b32 %84, 0; mov.b32 %85, 0; mov.b32 %86, 0; mov.b32 %87, 0;\n"
    "mov.b32 %88, 0; mov.b32 %89, 0; mov.b32 %90, 0; mov.b32 %91, 0; mov.b32 %92, 0; mov.b32 %93, 0; mov.b32 %94, 0; mov.b32 %95, 0;\n"
    "mov.b32 %96, 0; mov.b32 %97, 0; mov.b32 %98, 0; mov.b32 %99, 0; mov.b32 %100, 0; mov.b32 %101, 0; mov.b32 %102, 0; mov.b32 %103, 0;\n"
    "mov.b32 %104, 0; mov.b32 %105, 0; mov.b32 %106, 0; mov.b32 %107, 0; mov.b32 %108, 0; mov.b32 %109, 0; mov.b32 %110, 0; mov.b32 %111, 0;\n"
    "mov.b32 %112, 0; mov.b32 %113, 0; mov.b32 %114, 0; mov.b32 %115, 0; mov.b32 %116, 0; mov.b32 %117, 0; mov.b32 %118, 0; mov.b32 %119, 0;\n"
    "mov.b32 %120, 0; mov.b32 %121, 0; mov.b32 %122, 0; mov.b32 %123, 0; mov.b32 %124, 0; mov.b32 %125, 0; mov.b32 %126, 0; mov.b32 %127, 0;\n"
    "wgmma.mma_async.sync.aligned.m64n256k16.f32.bf16.bf16 "
    "{%0, %1, %2, %3, %4, %5, %6, %7, %8, %9, %10, %11, %12, %13, %14, %15, "
    "%16, %17, %18, %19, %20, %21, %22, %23, %24, %25, %26, %27, %28, %29, %30, %31, "
    "%32, %33, %34, %35, %36, %37, %38, %39, %40, %41, %42, %43, %44, %45, %46, %47, "
    "%48, %49, %50, %51, %52, %53, %54, %55, %56, %57, %58, %59, %60, %61, %62, %63, "
    "%64, %65, %66, %67, %68, %69, %70, %71, %72, %73, %74, %75, %76, %77, %78, %79, "
    "%80, %81, %82, %83, %84, %85, %86, %87, %88, %89, %90, %91, %92, %93, %94, %95, "
    "%96, %97, %98, %99, %100, %101, %102, %103, %104, %105, %106, %107, %108, %109, %110, %111, "
    "%112, %113, %114, %115, %116, %117, %118, %119, %120, %121, %122, %123, %124, %125, %126, %127}, "
    "da, db, 1, 1, 1, 0, 1;\n}\n"
    : "=f"(d[0]), "=f"(d[1]), "=f"(d[2]), "=f"(d[3]), "=f"(d[4]), "=f"(d[5]), "=f"(d[6]), "=f"(d[7]),
      "=f"(d[8]), "=f"(d[9]), "=f"(d[10]), "=f"(d[11]), "=f"(d[12]), "=f"(d[13]), "=f"(d[14]), "=f"(d[15]),
      "=f"(d[16]), "=f"(d[17]), "=f"(d[18]), "=f"(d[19]), "=f"(d[20]), "=f"(d[21]), "=f"(d[22]), "=f"(d[23]),
      "=f"(d[24]), "=f"(d[25]), "=f"(d[26]), "=f"(d[27]), "=f"(d[28]), "=f"(d[29]), "=f"(d[30]), "=f"(d[31]),
      "=f"(d[32]), "=f"(d[33]), "=f"(d[34]), "=f"(d[35]), "=f"(d[36]), "=f"(d[37]), "=f"(d[38]), "=f"(d[39]),
      "=f"(d[40]), "=f"(d[41]), "=f"(d[42]), "=f"(d[43]), "=f"(d[44]), "=f"(d[45]), "=f"(d[46]), "=f"(d[47]),
      "=f"(d[48]), "=f"(d[49]), "=f"(d[50]), "=f"(d[51]), "=f"(d[52]), "=f"(d[53]), "=f"(d[54]), "=f"(d[55]),
      "=f"(d[56]), "=f"(d[57]), "=f"(d[58]), "=f"(d[59]), "=f"(d[60]), "=f"(d[61]), "=f"(d[62]), "=f"(d[63]),
      "=f"(d[64]), "=f"(d[65]), "=f"(d[66]), "=f"(d[67]), "=f"(d[68]), "=f"(d[69]), "=f"(d[70]), "=f"(d[71]),
      "=f"(d[72]), "=f"(d[73]), "=f"(d[74]), "=f"(d[75]), "=f"(d[76]), "=f"(d[77]), "=f"(d[78]), "=f"(d[79]),
      "=f"(d[80]), "=f"(d[81]), "=f"(d[82]), "=f"(d[83]), "=f"(d[84]), "=f"(d[85]), "=f"(d[86]), "=f"(d[87]),
      "=f"(d[88]), "=f"(d[89]), "=f"(d[90]), "=f"(d[91]), "=f"(d[92]), "=f"(d[93]), "=f"(d[94]), "=f"(d[95]),
      "=f"(d[96]), "=f"(d[97]), "=f"(d[98]), "=f"(d[99]), "=f"(d[100]), "=f"(d[101]), "=f"(d[102]), "=f"(d[103]),
      "=f"(d[104]), "=f"(d[105]), "=f"(d[106]), "=f"(d[107]), "=f"(d[108]), "=f"(d[109]), "=f"(d[110]), "=f"(d[111]),
      "=f"(d[112]), "=f"(d[113]), "=f"(d[114]), "=f"(d[115]), "=f"(d[116]), "=f"(d[117]), "=f"(d[118]), "=f"(d[119]),
      "=f"(d[120]), "=f"(d[121]), "=f"(d[122]), "=f"(d[123]), "=f"(d[124]), "=f"(d[125]), "=f"(d[126]), "=f"(d[127])
    : "r"(a_lo), "r"(b_lo));
}

template <int N> struct Mma;
template <> struct Mma<128> {
  static __device__ __forceinline__ void ss(float (&d)[64], uint32_t a, uint32_t b) { wgmma_ss_n128(d, a, b); }
  static __device__ __forceinline__ void ss(float (&d)[64], uint32_t a, uint32_t b, uint32_t keep) { wgmma_ss_n128_p(d, a, b, keep); }
};
template <> struct Mma<192> {
  static __device__ __forceinline__ void ss(float (&d)[96], uint32_t a, uint32_t b) { wgmma_ss_n192(d, a, b); }
};
template <> struct Mma<256> {
  static __device__ __forceinline__ void ss(float (&d)[128], uint32_t a, uint32_t b) { wgmma_ss_n256(d, a, b); }
  static __device__ __forceinline__ void ss(float (&d)[128], uint32_t a, uint32_t b, uint32_t) { wgmma_ss_n256_first(d, a, b); }
};
template <int R> __device__ __forceinline__ void pin(float (&d)[R]) {
#pragma unroll
  for (int x = 0; x < R; x++) asm volatile("" : "+f"(d[x]));
}

__device__ __forceinline__ uint32_t ld_relaxed(const uint32_t* p) {
  uint32_t v; asm volatile("ld.relaxed.gpu.global.u32 %0, [%1];" : "=r"(v) : "l"(p) : "memory"); return v;
}
__device__ __forceinline__ void red_release(uint32_t* p) { asm volatile("red.release.gpu.global.add.u32 [%0], 1;" :: "l"(p) : "memory"); }
__device__ __forceinline__ uint32_t both_valid(uint32_t a, uint32_t b, uint32_t ep) {
  uint32_t r; asm("lop3.b32 %0, %1, %2, %3, 0x42;" : "=r"(r) : "r"(a), "r"(b), "r"(ep)); return r;
}
__device__ __forceinline__ uint32_t tagged(float v, uint32_t ep) { return (__float_as_uint(v) | 1u) ^ (ep & 1u); }
__device__ __forceinline__ void st_release(uint32_t* p, uint32_t v) { asm volatile("st.release.gpu.global.u32 [%0], %1;" :: "l"(p), "r"(v) : "memory"); }
__device__ __forceinline__ void stg32(void* p, uint32_t v) { asm volatile("st.global.u32 [%0], %1;" :: "l"(p), "r"(v) : "memory"); }
__device__ __forceinline__ float rsqrt_fast(float x) { float r; asm("rsqrt.approx.ftz.f32 %0, %1;" : "=f"(r) : "f"(x)); return r; }
__device__ __forceinline__ uint32_t gate_pair(uint32_t x, uint32_t y, uint32_t r, uint32_t nb) {
  uint32_t o;
  asm("{\n.reg .b16 l, h;\n.reg .b32 ll, hh, t;\nmov.b32 {l, h}, %3;\nmov.b32 ll, {l, l};\nmov.b32 hh, {h, h};\n"
      "fma.rn.bf16x2 t, %1, ll, %4;\nfma.rn.bf16x2 t, %1, hh, t;\nfma.rn.bf16x2 %0, t, %2, %1;\n}" : "=r"(o) : "r"(x), "r"(y), "r"(r), "r"(nb));
  return o;
}

constexpr int CV_KT_O = 4144;
constexpr int CV_KT_CH = 8336;
constexpr int CV_KH = 2064;
constexpr int CV_U_PLANE = 2240;
constexpr int CV_U_CH = 4496;
constexpr int CV_VQ = 8320, CV_Y_CH = 1040, CV_XROW = 2064;
constexpr int SM_BAR = 0;
constexpr int CV_K = 896;
constexpr int CV_X = CV_K + 128 + 32768;
constexpr int CV_ST0 = CV_X + 16 * CV_XROW;
constexpr int CV_KT = CV_ST0 + 8192;
constexpr int CV_QS = CV_KT + 8 * CV_KT_CH;
constexpr int CV_U = 142848;
constexpr int CV_V = CV_U + 8 * CV_U_CH;
constexpr int CV_ST1 = CV_V + 4 * CV_VQ;
constexpr int SM_ZERO = CV_ST1 + 8192, SM_ROLE = SM_ZERO + 4, SM_EPOCH = SM_ZERO + 8;
constexpr int CV_END = SM_ZERO + 16;
static_assert(CV_QS + 1024 <= CV_U && CV_X % 1024 == 0 && CV_V % 128 == 0, "layout");
constexpr int CV_BAR = SM_BAR + 8 * 84, BAR_REL = 25;
enum { CB_K0, CB_QA, CB_Q0, CB_Q1, CB_Q2, CB_Q3, CB_K1, CB_X0, CB_X1, CB_QC0, CB_QC1, CB_QS, CB_U1, CB_U2,
       CB_ST0, CB_ST1, CB_O1, CB_P1, CB_Y1, CB_Y2, CB_P2, CB_EARLY, CB_LATE, CB_YOUT, CB_STAT, CB_XFREE = CB_STAT + 2, CB_COUNT };
static_assert(CV_BAR + 8 * CB_COUNT <= CV_K, "layout");

__device__ __forceinline__ uint32_t lds32_nv(uint32_t addr) { uint32_t v; asm("ld.shared.u32 %0, [%1];" : "=r"(v) : "r"(addr)); return v; }
__device__ __forceinline__ void ldsm_x4_nv(uint32_t addr, uint32_t& r0, uint32_t& r1, uint32_t& r2, uint32_t& r3) {
  asm("ldmatrix.sync.aligned.m8n8.x4.shared.b16 {%0,%1,%2,%3}, [%4];" : "=r"(r0), "=r"(r1), "=r"(r2), "=r"(r3) : "r"(addr));
}
__device__ __forceinline__ void stsm_x4_t(uint32_t addr, uint32_t r0, uint32_t r1, uint32_t r2, uint32_t r3) {
  asm volatile("stmatrix.sync.aligned.m8n8.x4.trans.shared.b16 [%0], {%1,%2,%3,%4};" :: "r"(addr), "r"(r0), "r"(r1), "r"(r2), "r"(r3) : "memory");
}
__device__ __forceinline__ void bulk_load(uint32_t dst, const void* src, uint32_t bytes, uint32_t bar) {
  asm volatile("cp.async.bulk.shared::cluster.global.mbarrier::complete_tx::bytes [%0], [%1], %2, [%3];" :: "r"(dst), "l"(src), "r"(bytes), "r"(bar) : "memory");
}
__device__ __forceinline__ void mbar_wait_plain(uint32_t bar, uint32_t parity) {
#pragma unroll 1
  for (int spins = 0; spins < SPIN_LIMIT && !mbar_try(bar, parity); spins++) {}
}

__device__ __forceinline__ void shift_chunk(uint32_t src) {
  uint4 e;
  uint32_t nx;
  asm volatile("ld.shared.v4.u32 {%0,%1,%2,%3}, [%4];" : "=r"(e.x), "=r"(e.y), "=r"(e.z), "=r"(e.w) : "r"(src));
  asm volatile("ld.shared.u32 %0, [%1];" : "=r"(nx) : "r"(src + 16));
  sts128(src + CV_KT_O, make_uint4(__byte_perm(e.x, e.y, 0x5432), __byte_perm(e.y, e.z, 0x5432), __byte_perm(e.z, e.w, 0x5432), __byte_perm(e.w, nx, 0x5432)));
}
__device__ __forceinline__ void kv_block(uint32_t sm, int t0, const uint32_t (&wp)[4], int lane) {
  const int mi = lane >> 3, rev = 7 - (lane & 7);
  uint32_t vv[4], res[4];
  ldsm_x4(sm + CV_V + (t0 >> 9) * (CV_VQ - 8192) + (t0 + 8 * mi + rev) * 16, vv[0], vv[1], vv[2], vv[3]);
#pragma unroll
  for (int i = 0; i < 4; i++) {
    uint32_t k0, k1, k2, k3;
    ldsm_x4(sm + CV_K + (8 + t0 + 8 * i + rev - mi) * 16, k0, k1, k2, k3);
    res[i] = bmul2(badd2(badd2(badd2(bmul2(k3, wp[3]), bmul2(k2, wp[2])), bmul2(k1, wp[1])), bmul2(k0, wp[0])), vv[i]);
  }
  stsm_x4_t(sm + CV_U + (lane & 7) * CV_U_CH + (1 - (mi & 1)) * CV_U_PLANE + (8 + (t0 >> 4) + (mi >> 1)) * 16, res[0], res[1], res[2], res[3]);
}
template <int T0, int NT, int D0, int D1, int J0, int J1>
__device__ __forceinline__ void conv_phase(float (&acc)[16][4], uint32_t abase, uint32_t bbase, uint32_t zero) {
  abase += zero; bbase += zero;
#pragma unroll 1
  for (int dl = 0; dl < 8; dl++) {
    uint32_t bf[NT][2];
#pragma unroll
    for (int j = 0; j < NT; j += 2) ldsm_x4_nv(bbase + (T0 + j) * 128 - dl * 16, bf[j][0], bf[j][1], bf[j + 1][0], bf[j + 1][1]);
    const uint32_t ap = abase + dl * 32;
#pragma unroll
    for (int dh = D0; dh < D1; dh++) {
      const uint32_t a0 = lds32_nv(ap + dh * 256), a1 = lds32_nv(ap + dh * 256 - 16), a2 = lds32_nv(ap + dh * 256 + 16);
      const uint32_t a3 = a0 + zero;
#pragma unroll
      for (int j = 0; j < NT; j++)
        if (dh + T0 + j >= J0 && dh + T0 + j < J1) mma16816(acc[dh + T0 + j], a0, a1, a2, a3, bf[j][0], bf[j][1]);
    }
  }
}
__device__ __forceinline__ uint32_t hidden_zero(uint32_t addr) {
  uint32_t z; asm volatile("ld.volatile.shared.u32 %0, [%1];" : "=r"(z) : "r"(addr) : "memory"); return z;
}
template <int J0, int J1>
__device__ __forceinline__ void stage_y(const float (&acc)[16][4], uint32_t ys, uint32_t bar) {
#pragma unroll
  for (int j = J0; j < J1; j += 2)
    stsm_x4_t(ys + (j >> 2) * CV_VQ + (j & 3) * 128, pack_bf16(acc[j][0], acc[j][1]), pack_bf16(acc[j][2], acc[j][3]),
              pack_bf16(acc[j + 1][0], acc[j + 1][1]), pack_bf16(acc[j + 1][2], acc[j + 1][3]));
  if (J0) {
    __syncwarp();
    mbar_arrive_if(bar, (threadIdx.x & 31) == 0);
  }
}

#define KV_PROMO CU_TENSOR_MAP_L2_PROMOTION_L2_128B
#define STATS_EARLY 0
#define QC1_AT 2
#define QROW_AT 3
constexpr int CV_JS = 8;
enum { M_K, M_V, M_Q, M_W1C, M_W3C, M_X3S, M_X3B, M_H, M_HS, M_X1, M_HID, M_W1, M_W2, M_W3A, M_W3B, M_W4, M_OUT, M_Y, M_COUNT };
struct alignas(64) Params {
  const bf16 *q, *shift_k, *ssm_k, *ssm_d, *w2;
  CUtensorMap m[M_COUNT];
};
__device__ __forceinline__ void prefetch_line(const void* p) { asm volatile("prefetch.global.L2 [%0];" :: "l"(p) : "memory"); }

__device__ __forceinline__ uint32_t pick_role() {
  uint32_t smid;
  asm volatile("mov.u32 %0, %%smid;" : "=r"(smid));
  const uint32_t t = smid >> 1;
  const uint32_t gpc = t < 32 ? t & 7 : t < 60 ? 1 + (t - 32) % 7 : t < 62 ? t - 54 : 0;
#pragma unroll 1
  for (uint32_t k = 0; k < 4; k++) {
    const uint32_t p = (gpc + k) & 3, ticket = atomicAdd(&g_role[p], 1u);
    if (ticket < 16) return ticket * 4 + p;
  }
  return 0;
}

__device__ __forceinline__ void load_k(const Params& pr, uint32_t sm, int x) {
  const uint32_t bar = sm + CV_BAR + 8 * (x ? CB_K1 : CB_K0), bytes = x ? 4096 - CV_KH : CV_KH;
  mbar_expect_tx(bar, 8 * bytes);
#pragma unroll 1
  for (int ch = 0; ch < 8; ch++)
    bulk_load(sm + CV_KT + ch * CV_KT_CH + 32 + x * CV_KH, reinterpret_cast<const char*>(pr.ssm_k) + (blockIdx.x * 8 + ch) * 4096 + x * CV_KH, bytes, bar);
}
__device__ __forceinline__ void load_kv(const Params& pr, uint32_t sm, int y, int barrier) {
  tma_2d(sm + CV_K + 128 + y * 4096, &pr.m[M_K], sm + CV_BAR + 8 * barrier, blockIdx.x * 8, y * 256);
  tma_2d(sm + CV_V + (y >> 1) * CV_VQ + (y & 1) * 4096, &pr.m[M_V], sm + CV_BAR + 8 * barrier, blockIdx.x * 8, y * 256);
}

__device__ __forceinline__ void conv_part(const Params& pr, uint32_t sm, int warp) {
  const int tid = threadIdx.x, lane = tid & 31;
  const int b = blockIdx.x, d0 = b * 8;
  const uint32_t kt = sm + CV_KT, ub = sm + CV_U, bar = sm + CV_BAR;
  const int g = lane >> 2, qd = lane & 3, mi = lane >> 3;
  if (warp == 8) {
    asm volatile("bar.arrive 1, 384;" ::: "memory");
    const uint32_t ep = ld_relaxed(&g_epoch);
    if (elect_one()) {
      load_k(pr, sm, 1);
#pragma unroll 1
      for (int y = 2; y < 8; y++) {
        if (y == 2 * QROW_AT) {
          mbar_expect_tx(bar + 8 * CB_X0, 32768);
#pragma unroll 1
          for (int r = 0; r < 16; r++) bulk_load(sm + CV_X + r * CV_XROW, pr.q + (size_t)(b * 16 + r) * DM, 2048, bar + 8 * CB_X0);
        }
        if (!(y & 1)) mbar_expect_tx(bar + 8 * (CB_Q0 + (y >> 1)), 16384);
        load_kv(pr, sm, y, CB_Q0 + (y >> 1));
      }
#pragma unroll 1
      for (int x = M_Q; x < M_COUNT; x++) asm volatile("prefetch.tensormap [%0];" :: "l"(&pr.m[x]) : "memory");
      sts32(sm + SM_EPOCH, ep);
      if ((b & 1) == 0) sts32(sm + SM_ROLE, pick_role());
      asm volatile("fence.release.sync_restrict::shared::cta.cluster;" ::: "memory");
    }
    __syncwarp();
    asm volatile("barrier.cluster.arrive.relaxed.aligned;" ::: "memory");
    auto load_q = [&](int x) {
      mbar_wait_plain(bar + 8 * (CB_U1 + x), 0);
      fence_async_smem();
      if (elect_one()) {
        mbar_expect_tx(bar + 8 * (CB_QC0 + x), 16384);
#pragma unroll 1
        for (int y = 4 * x; y < 4 * x + 4; y++) tma_2d(sm + CV_K + 128 + y * 4096, &pr.m[M_Q], bar + 8 * (CB_QC0 + x), d0, y * 256);
      }
    };
    const int npieces = b < 112 ? 5 : 1;
    const int xr = (mi >> 1) * 8 + (lane & 7);
    const uint32_t xa = sm + CV_X + xr * 64 + (((mi & 1) ^ ((xr >> 1) & 3)) << 4);
    float cs[8][4] = {};
    auto q_stats = [&]() {
      mbar_wait_plain(bar + 8 * CB_QS, 0);
      float sum = 0.f, sq = 0.f;
#pragma unroll
      for (int x = 0; x < 8; x++) { const float2 v = lds_f2(sm + CV_QS + x * 128 + (lane & 15) * 8); sum += v.x; sq += v.y; }
      const float mean = sum * (1.f / DM), rs = rsqrt_fast(fmaxf(fmaf(-mean, mean, sq * (1.f / DM)), 0.f) + LN_EPS);
      const uint32_t rh = pack_bf16(0.f, rs);
      if (lane < 16)
        asm volatile("st.relaxed.gpu.global.v2.b32 [%0], {%1,%2};" :: "l"(g_qstat + b * 16 + lane), "r"(tagged(__uint_as_float(pack_bf16(rs - bf_hi(rh), bf_hi(rh))), ep)),
                     "r"(pack_bf16(-mean * rs, -mean * rs)) : "memory");
      if (lane == 0) { STAMP(47); asm volatile("red.relaxed.gpu.global.add.u32 [%0], 1;" :: "l"(&g_qcnt) : "memory"); }
    };
#pragma unroll 1
    for (int pc = -3; pc < npieces; pc++) {
      if (pc == -2) q_stats();
      if (pc >= 0) {
        mbar_wait_plain(bar + 8 * (CB_X0 + ((pc + 1) & 1)), ((pc + 1) >> 1) & 1);
#pragma unroll 1
        for (int r = 0; r < 16; r += 4) {
#pragma unroll
          for (int x = 0; x < 8; x++) {
            uint32_t a0, a1, a2, a3;
            ldsm_x4_t((xa ^ ((x & 1) << 5)) + ((pc + 1) & 1) * 16384 + (r + (x >> 1)) * 1024, a0, a1, a2, a3);
            mma16816(cs[x], a0, a1, a2, a3, 0x3f803f80u, 0x3f803f80u);
          }
        }
        if (pc == 0 || pc == 4) {
          float t = 0.f;
#pragma unroll
          for (int x = 0; x < 8; x += 2) {
            t += qd & 2 ? (qd & 1 ? cs[x + 1][2] : cs[x + 1][0]) : (qd & 1 ? cs[x][2] : cs[x][0]);
            cs[x][0] = cs[x][2] = cs[x + 1][0] = cs[x + 1][2] = 0.f;
          }
          (pc ? g_cs3 + 32 * b : g_cs1[b & 3] + 32 * (b >> 2))[8 * qd + g] = t;
        }
        __syncwarp();
      }
      if (pc > -3 && pc + 2 < npieces && elect_one()) {
        const uint32_t bx = bar + 8 * (CB_X0 + ((pc + 1) & 1));
        mbar_expect_tx(bx, 16384);
        tma_2d(sm + CV_X + ((pc + 1) & 1) * 16384, &pr.m[pc == -2 ? M_W1C : M_W3C], bx, 32 * (pc == -2 ? b >> 2 : b), 256 * (pc == -2 ? b & 3 : pc + 1));
      }
      if (pc == -3 || pc == min(QC1_AT, npieces - 1)) load_q(pc >= 0);
    }
#pragma unroll 1
    for (int x = 0; x < 4; x++) prefetch_line(reinterpret_cast<const char*>(pr.w2) + (b * 128 + x * 32 + lane) * 128);
    if (lane == 0) STAMP(52);
    return;
  }

  const uint32_t dpair = __ldg(reinterpret_cast<const uint32_t*>(pr.ssm_d + d0 + 2 * qd));
  const int wi = warp - (warp > 8), ti = 32 * wi + lane;
  {
    if (tid < 160) {
      const int x = tid - 128, y = x & 3;
      sts128(tid < 128 ? ub + (tid >> 4) * CV_U_CH + ((tid >> 3) & 1) * CV_U_PLANE + (tid & 7) * 16
                       : y == 3 ? sm + CV_K + (x >> 2) * 16 : kt + (x >> 2) * CV_KT_CH + (y == 2 ? 4128 : y * 16), make_uint4(0, 0, 0, 0));
    }
    uint32_t wp[4];
    {
      const uint4 a = ld_nc_u4(pr.shift_k + (d0 + 2 * qd) * 4);
      wp[0] = __byte_perm(a.x, a.z, 0x5410); wp[1] = __byte_perm(a.x, a.z, 0x7632);
      wp[2] = __byte_perm(a.y, a.w, 0x5410); wp[3] = __byte_perm(a.y, a.w, 0x7632);
    }
    const uint32_t kc = kt + (lane & 7) * CV_KT_CH;
    named_bar(1, 384);
#pragma unroll 1
    for (int x = 0; x < 2; x++) {
      mbar_wait_plain(bar + 8 * (x ? CB_K1 : CB_K0), 0);
#pragma unroll 1
      for (uint32_t a = kc + ((ti >> 3) + (x ? 130 - 32 : 0)) * 16; a < kc + (x ? 258 : 130) * 16; a += x ? 192 : 704) shift_chunk(a);
      __syncwarp();
      mbar_arrive_if(bar + 8 * CB_O1, x && lane == 0);
      if (tid == 0) BSTAMP(54, kt);
#pragma unroll 1
      for (int t0 = warp < 8 ? 32 * wi : 32 * wi + 256; t0 < (x ? SEQ : 512); t0 += x ? 96 : 256) {
        mbar_wait_plain(bar + 8 * (t0 < 256 ? CB_QA : CB_Q0 + (t0 >> 9)), 0);
        if (tid == 0) BSTAMP(56, kt);
        kv_block(sm, t0, wp, lane);
        constexpr int T1 = 128 * CV_JS + 32;
        __syncwarp();
        mbar_arrive_if(bar + 8 * (CB_U1 + (t0 >= T1)), t0 + 96 >= (t0 < T1 ? T1 : SEQ) && lane == 0);
      }
      if (x == 0) named_bar(4, 352);
      if (warp < 8) break;
    }
  }

  if (warp < 8) {
    const int o = 2 * qd - g;
    const uint32_t abase = kt + warp * CV_KT_CH + 32 + ((g & 1) ? CV_KT_O + (o - 1) * 2 : o * 2);
    const uint32_t bbase = ub + warp * CV_U_CH + (mi & 1) * CV_U_PLANE + (8 + (lane >> 4) * 8 + (lane & 7)) * 16;
    const uint32_t ys = sm + CV_V + warp * CV_Y_CH + (mi & 1) * 512 + ((lane >> 4) * 8 + (lane & 7)) * 16;
    auto q_sums = [&]() {
      mbar_wait_plain(bar + 8 * CB_X0, 0);
      float sum[4] = {0.f, 0.f, 0.f, 0.f}, lo[4] = {0.f, 0.f, 0.f, 0.f}, hi[4] = {0.f, 0.f, 0.f, 0.f};
#pragma unroll
      for (int x = 0; x < 8; x++) {
        uint32_t a0, a1, a2, a3;
        ldsm_x4(sm + CV_X + (lane & 15) * CV_XROW + warp * 256 + (lane >> 4) * 16 + x * 32, a0, a1, a2, a3);
        mma16816(sum, a0, a1, a2, a3, 0x3f803f80u, 0x3f803f80u);
        mma16816(lo, a0, a1, a2, a3, a0, a2);
        mma16816(hi, a0, a1, a2, a3, a1, a3);
      }
      if (qd == (g >> 1)) {
        asm volatile("st.shared.v2.f32 [%0], {%1,%2};" :: "r"(sm + CV_QS + warp * 128 + g * 8), "f"(sum[0]), "f"((g & 1) ? lo[1] : lo[0]) : "memory");
        asm volatile("st.shared.v2.f32 [%0], {%1,%2};" :: "r"(sm + CV_QS + warp * 128 + g * 8 + 64), "f"(sum[2]), "f"((g & 1) ? hi[3] : hi[2]) : "memory");
      }
      __syncwarp();
      mbar_arrive_if(bar + 8 * CB_QS, lane == 0);
    };
    if (tid == 0) STAMP(49);
    float acc[16][4];
#pragma unroll
    for (int j = 0; j < 16; j++) { acc[j][0] = acc[j][1] = acc[j][2] = acc[j][3] = 0.f; }
    conv_phase<0, 4, 0, 8, 0, 16>(acc, abase, bbase, hidden_zero(ub));
    stage_y<0, 4>(acc, ys, 0);
    if (tid == 0) STAMP(57);
    if (STATS_EARLY) q_sums();
    mbar_wait_plain(bar + 8 * CB_K1, 0);
    mbar_wait_plain(bar + 8 * CB_O1, 0);
    conv_phase<0, 4, 8, 16, 0, 16>(acc, abase, bbase, hidden_zero(ub));
    if (tid == 0) STAMP(58);
    if (!STATS_EARLY) q_sums();
    mbar_wait_plain(bar + 8 * CB_U1, 0);
    conv_phase<4, CV_JS - 4, 0, CV_JS - 4, 0, CV_JS>(acc, abase, bbase, hidden_zero(ub));
    stage_y<4, CV_JS>(acc, ys, bar + 8 * CB_Y1);
    if (tid == 0) STAMP(59);
    mbar_wait_plain(bar + 8 * CB_U2, 0);
    if (tid == 0) BSTAMP(55, kt);
    conv_phase<4, 12, 0, 12, CV_JS, 16>(acc, abase, bbase, hidden_zero(ub));
    stage_y<CV_JS, 16>(acc, ys, bar + 8 * CB_Y2);
    if (tid == 0) STAMP(50);
    if (tid == 32) STAMP(62);
  }
  {
    const int ch = lane & 7;
    const uint32_t ya = sm + CV_V + ch * CV_Y_CH + (mi & 1) * 512 + (mi >> 1) * 16;
    const uint32_t ua = ub + ch * CV_U_CH + (mi & 1) * CV_U_PLANE + (8 + (mi >> 1)) * 16;
    const uint32_t qa = sm + CV_K + 128 + (16 * (mi >> 1) + 15 - 8 * (mi & 1) - ch) * 16;
    char* xo = reinterpret_cast<char*>(g_x3[0]) + (size_t)b * CB_BYTES + (15 - g) * 16 + qd * 4;
    const uint32_t yo = sm + CV_K + 128 + ((7 - g) * 4 + qd) * 8;
    int budget = SPIN_LIMIT;
    uint32_t ep = 0;
    if (warp > 9) {
      if (tid == 320) STAMP(53);
      ep = ld_relaxed(&g_epoch);
#pragma unroll 1
      while (ld_relaxed(&g_qcnt) - 128 * ep < 128 && --budget > 0) __nanosleep(100);
      if (tid == 320) STAMP(43);
    }
#pragma unroll 1
    for (int part = warp < 8; part < 2; part++) {
      if (warp == 9 && part) break;
      if (warp > 9) {
        uint4 v[8];
#pragma unroll 1
        do {
          uint32_t ok = 1;
#pragma unroll
          for (int y = 0; y < 8; y++) {
            asm volatile("ld.relaxed.gpu.global.v4.u32 {%0,%1,%2,%3}, [%4];" : "=r"(v[y].x), "=r"(v[y].y), "=r"(v[y].z), "=r"(v[y].w)
                         : "l"(g_qstat + 1024 * part + 2 * (tid & 63) + 128 * y) : "memory");
            ok &= both_valid(v[y].x, v[y].z, ep);
          }
          if (__all_sync(0xffffffffu, ok)) break;
        } while (--budget > 0);
#pragma unroll
        for (int y = 0; y < 8; y++) sts128(sm + (part ? CV_ST1 : CV_ST0) + (tid & 63) * 16 + 1024 * y, make_uint4(v[y].x | 1u, v[y].y, v[y].z | 1u, v[y].w));
        __syncwarp();
        mbar_arrive_if(bar + 8 * (CB_ST0 + part), lane == 0);
      }
      mbar_wait_plain(bar + 8 * (CB_ST0 + part), 0);
      mbar_wait_plain(bar + 8 * (CB_QC0 + part), 0);
      if (tid == 288) STAMP(63);
      mbar_wait_plain(bar + 8 * (CB_Y1 + part), 0);
      const uint32_t sa = sm + (part ? CV_ST1 - 8192 : CV_ST0) + (15 - g) * 8;
#pragma unroll 1
      for (int u = part ? 4 * CV_JS + warp - 2 * (warp > 8) : warp - 9; u < (part ? 64 : 4 * CV_JS); u += part ? 10 : 3) {
        uint32_t y[4], uu[4], qq[4];
        ldsm_x4_t(ya + ((u >> 4) * (CV_VQ - 512) + u * 32), y[0], y[1], y[2], y[3]);
        ldsm_x4_t(ua + u * 32, uu[0], uu[1], uu[2], uu[3]);
        ldsm_x4(qa + u * 512, qq[0], qq[1], qq[2], qq[3]);
#pragma unroll
        for (int i = 0; i < 4; i++) {
          const int off = 16 * (i >> 1) - 8 * (i & 1);
          const float2 s = lds_f2(sa + (u * 256 + off * 8));
          y[i] = badd2(y[i], bmul2(uu[i], dpair));
          stg32(xo + (uint32_t)u * 512 + off * 16, gate_pair(qq[i], y[i], __float_as_uint(s.x), __float_as_uint(s.y)));
        }
        asm volatile("st.shared.v2.u32 [%0], {%1,%2};" :: "r"(yo + u * 512), "r"(y[1]), "r"(y[0]) : "memory");
        asm volatile("st.shared.v2.u32 [%0], {%1,%2};" :: "r"(yo + u * 512 + 256), "r"(y[3]), "r"(y[2]) : "memory");
      }
      __syncwarp();
      mbar_arrive_if(bar + 8 * (part ? CB_P2 : CB_P1), lane == 0);
    }
  }
  if (warp == 9) {
    mbar_wait_plain(bar + 8 * CB_P1, 0);
    if (elect_one()) {
      STAMP(61);
      red_release(&g_xcnt[b >> 3]);
      fence_async_smem();
      bulk_store(reinterpret_cast<char*>(g_y) + (size_t)b * CB_BYTES, sm + CV_K + 128, 16384);
      bulk_commit();
      bulk_wait_all();
      mbar_arrive(bar + 8 * CB_YOUT);
    }
  }
  if (tid == 0) STAMP(51);
}

constexpr int NA = 5, A_SLOT = 68 * 128;
constexpr int SM_B = 1024;
constexpr int SM_A = SM_B + 98304;
constexpr int SM_X = SM_A + 2 * NA * A_SLOT;
constexpr int SM_CS1 = CV_END;
constexpr int SM_CS3 = SM_CS1 + 512;
static_assert(SM_X % 1024 == 0 && SM_X + 32768 <= SM_CS1 && SM_B + 2 * 16384 == CV_X && SM_A + NA * A_SLOT == CV_U, "layout");
constexpr int BAR_FULLA = 0, BAR_FULLB = 16, BAR_TURN = 24, BAR_OWN = 26;
constexpr int BAR_EMPTYA = 28, BAR_EMPTYB = BAR_EMPTYA + 18, BAR_CS = BAR_EMPTYB + 9;
constexpr int BAR_PUB = 56;
constexpr int BAR_END = 84;
constexpr int SM_RS = SM_CS3 + 1792;
constexpr int MEGA_SMEM = SM_RS + 2 * 68 * 8;
static_assert(MEGA_SMEM <= 232448, "shared memory");
#define LEADS 0x444444
#define Y_AT 6
#define LEAD3 2

template <int N> struct BGeo;
template <> struct BGeo<128> { static constexpr int SLOTS = 6, BYTES = 16384; };
template <> struct BGeo<256> { static constexpr int SLOTS = 3, BYTES = 32768; };
template <> struct BGeo<192> { static constexpr int SLOTS = 4, BYTES = 24576; };
__host__ __device__ constexpr int first_slot(int s) { return s == 0 || s == 2 ? 2 : 0; }
__device__ __forceinline__ bool starts_local(int l, int s) { return s == 2 || s == 1 - l; }
__device__ __forceinline__ int token_shift(int j) { return ((j >> 1) & 1 ? 1 : -1) * (1 + (j >> 2)); }

struct Ctx {
  uint32_t sm;
  uint32_t bar;
  int i, j, r;
  int bid;
  uint32_t ep;
};

struct Pipe {
  uint32_t ko, kp;
  uint32_t po;
  uint32_t a0, a1, ar;
  uint32_t b;
  uint32_t keep;
  uint32_t sh, wide;
  uint32_t turn;
  int budget;
  uint32_t rel;
  bool signals;
  __device__ __forceinline__ void release() const {
    asm volatile("{\n.reg .pred p;\nsetp.ne.b32 p, %1, 0;\n@p mbarrier.arrive.shared::cluster.b64 _, [%0];\n}" :: "r"(rel + po), "r"((uint32_t)signals) : "memory");
  }
  __device__ __forceinline__ void drain() { wg_wait<0>(); release(); po = 64; }
};
__device__ __forceinline__ uint32_t desc_a(const Ctx& c, int off) { return ((c.sm & 0x3FFFFu) >> 4) + 0x400000u + (off >> 4); }
__device__ __forceinline__ uint32_t desc_b(const Ctx& c, int off) { return ((c.sm & 0x3FFFFu) >> 4) + 0x2000000u + ((SM_B + off) >> 4); }

template <int N, bool PRED, bool SHIFT = false, class Extra>
__device__ __forceinline__ void gemm_step(float (&acc)[N / 2], const Ctx& c, int wg, Pipe& p, Extra&& extra) {
  using G = BGeo<N>;
  const uint32_t fa = c.bar + 8 * BAR_FULLA + 64 * wg + p.ko, fb = c.bar + 8 * BAR_FULLB + p.ko;
#pragma unroll 1
  while (true) {
    uint32_t ready;
    asm volatile("{\n.reg .pred p, q;\nmbarrier.try_wait.parity.shared::cta.b64 p, [%1], %3;\nmbarrier.try_wait.parity.shared::cta.b64 q, [%2], %3;\n"
                 "and.pred p, p, q;\nselp.b32 %0, 1, 0, p;\n}" : "=r"(ready) : "r"(fa), "r"(fb), "r"(p.kp) : "memory");
    if (ready || --p.budget <= 0) break;
  }
  wg_fence();
  const uint32_t a = SHIFT ? p.a0 + (p.sh & 3) + (p.wide << 16) : p.a0, ak = SHIFT ? 128 + 2 * p.wide : 128;
  if constexpr (SHIFT) p.sh >>= 2;
  if constexpr (PRED) { Mma<N>::ss(acc, a, p.b, p.keep); p.keep = 1; } else Mma<N>::ss(acc, a, p.b);
#pragma unroll
  for (int kk = 1; kk < 4; kk++) Mma<N>::ss(acc, a + kk * ak, p.b + kk * 128);
  wg_commit();
  extra();
  wg_wait<1>();
  p.release();
  p.po = p.ko;
  p.ko = (p.ko + 8) & 63;
  p.kp ^= p.ko == 0;
  p.a0 = p.a1; p.a1 = p.ar;
  p.ar = p.ar == desc_a(c, SM_A + (NA - 1) * A_SLOT) + wg * NA * (A_SLOT >> 4) ? p.ar - (NA - 1) * (A_SLOT >> 4) : p.ar + (A_SLOT >> 4);
  p.b = p.b == desc_b(c, (G::SLOTS - 1) * G::BYTES) ? desc_b(c, 0) : p.b + (G::BYTES >> 4);
}
template <int N>
__device__ __forceinline__ void gemm_begin(const Ctx& c, int wg, int wq, Pipe& p, int s, bool local) {
  if (local) {
    fence_async_smem();
    named_bar(2 + wg, 128);
    mbar_arrive_if(c.bar + 8 * BAR_FULLA + 64 * wg + 8 * (threadIdx.x & 1), (threadIdx.x & 126) == 96);
    if (wq < 2) {
      mbar_wait(c.bar + 8 * (BAR_EMPTYA + 9 * wg + 8 - NA + wq), p.kp ^ 1, p.budget);
      if (elect_one()) {
        const uint32_t peer = mapa(c.sm, c.r ^ 1), bar = peer + SM_BAR + 8 * (BAR_FULLA + 8 * wg + 2 + wq);
        mbar_expect_tx_cluster(bar, 8192);
        bulk_copy_cluster(peer + (((wq ? p.a1 : p.a0) - desc_a(c, 0)) << 4), c.sm + SM_X + (2 * wg + wq) * 8192, 8192, bar);
      }
      __syncwarp();
    }
  }
  asm volatile("{\n.reg .pred p;\nsetp.ne.b32 p, %3, 0;\nselp.b32 %2, %0, %2, p;\nselp.b32 %0, %4, %0, p;\nselp.b32 %1, %5, %1, p;\n}"
               : "+r"(p.a0), "+r"(p.a1), "+r"(p.ar) : "r"((uint32_t)local), "r"(desc_a(c, SM_X) + wg * 1024), "r"(desc_a(c, SM_X + 8192) + wg * 1024));
  p.b = desc_b(c, first_slot(s) * BGeo<N>::BYTES);
}
template <class Hook>
__device__ __forceinline__ void yield_turn(const Ctx& c, int wg, Pipe& p, Hook&& hook) {
  if (wg == 1) p.drain();
  hook();
  if (wg == 1) mbar_wait(c.bar + 8 * BAR_TURN, p.turn, p.budget);
  p.turn ^= 1;
}
__device__ __forceinline__ void pass_turn(const Ctx& c, bool now) { mbar_arrive_if(c.bar + 8 * BAR_TURN, now && threadIdx.x == 96); }
struct Nop { __device__ __forceinline__ void operator()() const {} };
template <int N, bool PRED, bool SHIFT = false, class Hook, class Tail>
__device__ __forceinline__ void gemm_steps(float (&acc)[N / 2], const Ctx& c, int wg, Pipe& p, int count, int lead, Hook&& hook, Tail&& tail) {
#pragma unroll 1
  for (int n = count - lead; n > 0; n--) gemm_step<N, PRED, SHIFT>(acc, c, wg, p, Nop());
  yield_turn(c, wg, p, hook);
#pragma unroll 1
  for (int n = lead - 1; n >= 0; n--) {
    gemm_step<N, false, SHIFT>(acc, c, wg, p, Nop());
    pass_turn(c, n == 1);
  }
  tail();
  p.drain();
}

__device__ __forceinline__ void put_stat(float2* gdst, float s, float q, bool cond, uint32_t ep) {
  const float m = s * (1.f / 128), v = fmaxf(fmaf(-m, s, q), 0.f);
  asm volatile("{\n.reg .pred p;\nsetp.ne.b32 p, %3, 0;\n@p st.relaxed.gpu.global.v2.b32 [%0], {%1,%2};\n}"
               :: "l"(gdst), "r"(__float_as_uint(m)), "r"(tagged(v, ep)), "r"((uint32_t)cond) : "memory");
}
__device__ __forceinline__ void put_partial(const float (&v)[64], float2* gdst, uint32_t ep) {
  float s[4] = {v[0], v[1], v[2], v[3]}, q[4] = {v[0] * v[0], v[1] * v[1], v[2] * v[2], v[3] * v[3]};
#pragma unroll
  for (int x = 4; x < 64; x++) { s[x & 3] += v[x]; q[x & 3] = fmaf(v[x], v[x], q[x & 3]); }
  const bool odd = threadIdx.x & 1;
  const float s0 = s[0] + s[1], s1 = s[2] + s[3], q0 = q[0] + q[1], q1 = q[2] + q[3];
  float ss = (odd ? s1 : s0) + __shfl_xor_sync(0xffffffffu, odd ? s0 : s1, 1);
  float qq = (odd ? q1 : q0) + __shfl_xor_sync(0xffffffffu, odd ? q0 : q1, 1);
  ss += __shfl_xor_sync(0xffffffffu, ss, 2);
  qq += __shfl_xor_sync(0xffffffffu, qq, 2);
  put_stat(gdst + (odd ? 8 : 0), ss, qq, !(threadIdx.x & 2), ep);
}
struct RowStats {
  float2 p[4];
  __device__ __forceinline__ void load(const float2* r0, const float2* r1) {
#pragma unroll
    for (int x = 0; x < 4; x++)
      asm volatile("ld.relaxed.gpu.global.v2.f32 {%0,%1}, [%2];" : "=f"(p[x].x), "=f"(p[x].y) : "l"((x & 2 ? r1 : r0) + (x & 1) * SEQ) : "memory");
  }
  __device__ __forceinline__ void finish(const float2* r0, const float2* r1, int& budget, float2& s0, float2& s1) {
#pragma unroll 1
    while (!__all_sync(0xffffffffu, both_valid(__float_as_uint(p[0].y), __float_as_uint(p[1].y), 0) & both_valid(__float_as_uint(p[2].y), __float_as_uint(p[3].y), 0) & 1)) {
      if (--budget <= 0) break;
      load(r0, r1);
    }
#pragma unroll
    for (int h = 0; h < 2; h++) {
      const float2 a = p[2 * h], b = p[2 * h + 1];
      float m = a.x + b.x;
      m += __shfl_xor_sync(0xffffffffu, m, 1);
      m += __shfl_xor_sync(0xffffffffu, m, 2);
      m *= 0.125f;
      const float ea = a.x - m, eb = b.x - m;
      float t = fmaf(fmaf(ea, ea, eb * eb), 128.f, a.y + b.y);
      t += __shfl_xor_sync(0xffffffffu, t, 1);
      t += __shfl_xor_sync(0xffffffffu, t, 2);
      (h ? s1 : s0) = make_float2(m, rsqrt_fast(fmaf(t, 1.f / DM, LN_EPS)));
    }
  }
};

__device__ __forceinline__ void emit_panel(const uint32_t* v, char* gp, uint32_t pub) {
#pragma unroll
  for (int t = 0; t < 8; t++) { stg32(gp + t * CB_BYTES, v[2 * t]); stg32(gp + t * CB_BYTES + 128, v[2 * t + 1]); }
  __syncwarp();
  mbar_arrive_if(pub, (threadIdx.x & 31) == 0);
}
template <int NT>
__device__ __forceinline__ void stage_tiles(const uint32_t* v, uint32_t sp) {
#pragma unroll
  for (int t = 0; t < NT; t += 2) stsm_x4(sp + t * 1024, v[2 * t], v[2 * t + 1], v[2 * t + 2], v[2 * t + 3]);
}

__device__ __forceinline__ float late_zero(uint32_t addr) {
  float z; asm volatile("ld.volatile.shared.f32 %0, [%1];" : "=f"(z) : "r"(addr) : "memory"); return z;
}

template <int NT>
__device__ __forceinline__ void fold_tiles(uint32_t* v, const float* acc, const float2* cs_ptr, float2 st0, float2 st1) {
  const float n0 = -st0.x * st0.y, n1 = -st1.x * st1.y;
#pragma unroll
  for (int tile = 0; tile < NT; tile++) {
    const float2 cs = cs_ptr[tile * 4];
    float a = fmaf(acc[4 * tile + 0], st0.y, n0 * cs.x), b = fmaf(acc[4 * tile + 1], st0.y, n0 * cs.y);
    float cc = fmaf(acc[4 * tile + 2], st1.y, n1 * cs.x), d = fmaf(acc[4 * tile + 3], st1.y, n1 * cs.y);
    v[2 * tile] = pack_bf16(gelu_from_half(a), gelu_from_half(b));
    v[2 * tile + 1] = pack_bf16(gelu_from_half(cc), gelu_from_half(d));
  }
}

__device__ __forceinline__ void move_reg(uint32_t& d, uint32_t s) { asm volatile("mov.b32 %0, %1;" : "=r"(d) : "r"(s)); }
__device__ __forceinline__ void move_reg(float& d, float s) { asm volatile("mov.f32 %0, %1;" : "=f"(d) : "f"(s)); }
template <int CH, int LO, int HI, class T, int NR>
__device__ __forceinline__ void pick_group(T (&held)[NR], int idx) {
  if constexpr (HI - LO == 1) {
#pragma unroll
    for (int x = 0; x < CH; x++) move_reg(held[x], held[CH * LO + x]);
  } else {
    constexpr int MID = (LO + HI) / 2;
    if (idx < MID) pick_group<CH, LO, MID>(held, idx); else pick_group<CH, MID, HI>(held, idx);
  }
}
template <int CH>
__device__ __forceinline__ void gelu_chunk(const uint32_t* t, char* gp) {
#pragma unroll
  for (int x = 0; x < CH; x++) stg32(gp + (x >> 1) * CB_BYTES + (x & 1) * 128, gelu_pair_f16(t[x]));
}

#define REG_CONS 216
#define REG_PROD 72
__global__ void __cluster_dims__(2, 1, 1) __launch_bounds__(384, 1)
fused_kernel(const __grid_constant__ Params maps) {
  extern __shared__ __align__(1024) char smem[];
  const int tid = threadIdx.x, lane = tid & 31;
  const int warp = __shfl_sync(0xffffffffu, tid >> 5, 0), wg = warp >> 2;
  if (tid == 0) STAMP(48);
  const uint32_t sm0 = opaque(smem_u32(smem));
  if (elect_one()) {
    if (warp == 8) {
#pragma unroll
      for (int x = 0; x < CB_Q1; x++) mbar_init(sm0 + CV_BAR + 8 * x, 1);
      asm volatile("fence.mbarrier_init.release.cluster;" ::: "memory");
      load_k(maps, sm0, 0);
#pragma unroll
      for (int y = 0; y < 2; y++) {
        mbar_expect_tx(sm0 + CV_BAR + 8 * (CB_QA + y), 8192);
        load_kv(maps, sm0, y, CB_QA + y);
      }
#pragma unroll
      for (int x = CB_Q1; x < CB_ST0; x++) mbar_init(sm0 + CV_BAR + 8 * x, x < CB_QS ? 1 : x == CB_QS ? 8 : 3);
    } else if (warp == 9) {
#pragma unroll
      for (int x = CB_ST0; x < CB_COUNT; x++) mbar_init(sm0 + CV_BAR + 8 * x, x < CB_O1 ? 2 : x < CB_Y1 ? 3 : x < CB_P2 ? 8 : x == CB_P2 ? 10 : x == CB_YOUT ? 5 : x < CB_STAT ? 2 : 1);
    } else if (warp < 2) {
      asm volatile("prefetch.tensormap [%0];" :: "l"(&maps.m[M_K + warp]) : "memory");
    }
#pragma unroll
    for (int x = 0; x < 7; x++) mbar_init(sm0 + SM_BAR + 56 * warp + 8 * x, 1 << wg);
    asm volatile("fence.mbarrier_init.release.cluster;" ::: "memory");
    if (warp == 11) sts32(sm0 + SM_ZERO, 0);
  }
  static_assert(BAR_END == 84, "start-up work of 12 warps");
  __syncwarp();
  if (warp != 8) asm volatile("barrier.cluster.arrive.relaxed.aligned;" ::: "memory");
  conv_part(maps, sm0, warp);
  __syncwarp();
  asm volatile("barrier.cluster.wait.acquire.aligned;" ::: "memory");
  Ctx c;
  c.sm = sm0;
  c.bar = c.sm + SM_BAR;
  c.r = blockIdx.x & 1;
  {
    uint32_t role;
    asm volatile("ld.shared::cluster.u32 %0, [%1];" : "=r"(role) : "r"(mapa(sm0 + SM_ROLE, 0)) : "memory");
    role = __shfl_sync(0xffffffffu, role, 0);
    c.i = role >> 2; c.j = (role & 3) * 2 + c.r;
    c.bid = c.i * 8 + c.j;
    asm volatile("ld.shared.u32 %0, [%1];" : "=r"(c.ep) : "r"(c.sm + SM_EPOCH) : "memory");
  }

  if (tid == 0) MSTAMP(45);
  if (wg == 2) {
    reg_dealloc<REG_PROD>();
    int budget = SPIN_LIMIT;
    if (warp == 8) {
      const int hh = 16 * c.r + c.i;
      const uint32_t full0 = c.bar + 8 * (BAR_FULLA + c.r * 8), empty0 = c.bar + 8 * (BAR_EMPTYA + c.r * 9), full_peer = mapa(full0, c.r ^ 1);
      const uint32_t ring0 = c.sm + SM_A + c.r * NA * A_SLOT;
      const int nb = hh + (lane & 8 ? (lane & 2) - 1 : 0);
      const uint32_t* lf = g_flag + ((nb >= 0 && nb < 32 ? nb : hh) * 8 + (lane & 7)) * FS;
      const uint32_t* xf = g_xcnt + (hh + ((c.j >> 1) & 1) >= 16 ? 16 : 0) + (lane & 15);
      const uint32_t cb = c.sm + CV_BAR;
      if (lane == 0) mbar_arrive(cb + 8 * CB_XFREE);
      mbar_wait(cb + 8 * CB_Y2, 0, budget);
      if (lane == 0) STAMP(60);
      mbar_wait(cb + 8 * CB_P1, 0, budget);
      fence_async_smem();
      if (lane < 2) mbar_arrive_cluster(mapa(cb + 8 * CB_EARLY, lane));
      int seen = ld_relaxed(xf) - 8 * c.ep;
      mbar_wait(cb + 8 * (CB_EARLY + c.r), 0, budget);
      fence_async_global();
      if (lane == 0) MSTAMP(46);
      uint32_t slot = ring0;
      int k = 0;
#pragma unroll 1
      for (int ph = 0; ph < 10; ph++) {
        const int l = ph >= 5, s = ph - 5 * l;
        const CUtensorMap* m = &maps.m[s == 0 ? M_X3S + l : s == 1 ? M_H + l : s == 4 ? M_HID : M_X1];
        const uint32_t bytes = s == l ? A_SLOT : 8192;
        const bool local = starts_local(l, s);
        const int np = ph == 0 ? 1 : s == 4 ? 7 : 2, cnt = ph == 0 ? 16 : local ? 6 : 8, e0 = ph == 0 ? 2 * (c.j & 6) : (c.j & 6) + (local ? 2 : 0);
        const int need0 = ph == 0 ? 8 : 13 * l + (s == 0 ? 1 : s == 1 ? 3 : s == 4 ? 7 : 5);
        const uint32_t up = ph == 0 ? (c.j & 2 ? 0u : 0xffffu) : ph == 6 ? 0x33u : 0u;
        const uint32_t* fp = ph == 0 ? xf : lf;
        const uint32_t base = ph == 0 ? 8 * c.ep : 32 * c.ep;
        const bool polls = lane < (s == l ? 16 : 8);
        if (ph == 1) seen = 0;
        if (local) {
          k += 4;
          slot += slot >= ring0 + (NA - 2) * A_SLOT ? (2 - NA) * A_SLOT : 2 * A_SLOT;
        }
#pragma unroll 1
        for (int p = 0; p < np; p++) {
          uint32_t ready = __ballot_sync(0xffffffffu, seen >= need0 + p);
          if (ph == 6) ready &= ready >> 8;
#pragma unroll 1
          for (int x = 0; x < cnt; x++) {
            const int e = (e0 + x) & (ph == 0 ? 15 : 7);
            const uint32_t off = 8 * (k & 7);
            mbar_wait(empty0 + 8 * ((k - NA) & 7), ((k - NA) >> 3) & 1, budget);
            if (elect_one()) {
              mbar_expect_tx(full0 + off, bytes);
              mbar_expect_tx_cluster(full_peer + off, bytes);
            }
            if (!((ready >> e) & 1)) {
#pragma unroll 1
              do {
                if (polls) seen = ld_relaxed(fp) - base;
                ready = __ballot_sync(0xffffffffu, seen >= need0 + p);
                if (ph == 6) ready &= ready >> 8;
              } while (!((ready >> e) & 1) && --budget > 0);
              fence_async_global();
            }
            if (elect_one()) tma_2d_mc(slot, m, full0 + off, 128 * hh - 8 * ((up >> e) & 1), (np * e + p) * 8, (uint16_t)3);
            slot += slot == ring0 + (NA - 1) * A_SLOT ? (1 - NA) * A_SLOT : A_SLOT;
            k++;
          }
        }
      }
    } else if (warp == 9) {
      const uint32_t e8 = __funnelshift_r(0x76543210u, 0x76543210u, 4 * (c.j & 6));
      int k = 0;
#pragma unroll 1
      for (int ph = 0; ph < 10; ph++) {
        const int l = ph >= 5, s = ph - 5 * l;
        const uint32_t bytes = s == 2 ? 32768 : s == 3 ? 24576 : 16384, slots = s == 2 ? 3 : s == 3 ? 4 : 6;
        uint32_t dist = s == 2 ? 0x33333345u : s == 3 ? 0x44444333u : s == 4 ? 0x66655544u : 0x66666666u;
        const CUtensorMap* m = &maps.m[M_W1 + s];
        const int np = s == 4 ? 7 : 2;
        const int panel0 = s == 2 ? 7 * c.j : s == 3 ? 7 * c.j + 4 : 2 * c.j;
        const bool local = starts_local(l, s), direct = local || ph == 0;
        uint32_t slot = c.sm + SM_B + first_slot(s) * bytes;
#pragma unroll 1
        for (int o = 0; o < np; o++) {
          uint32_t tab = e8;
          if (local) tab = o ? (e8 >> 24 << 1) | ((e8 << 1) & 0xffffff00u) | 0x11111100u : (0x3210u ^ (c.j * 0x2222u)) | (e8 >> 8 << 17);
          if (ph == 0) tab = (c.j & 2 ? 0xba987654u : 0x76543210u) ^ (((c.j >> 2) ^ o) * 0x88888888u);
          const int mul = direct ? 64 : 64 * np, add = direct ? 0 : 64 * o;
#pragma unroll 1
          for (uint32_t bar = c.bar + 8 * BAR_FULLB; bar < c.bar + 8 * BAR_FULLB + 64; bar += 8) {
            const int last = k - (dist & 15), row = (tab & 15) * mul + add;
            if (last < 0) {
              mbar_wait(c.sm + CV_BAR + 8 * (k < 2 ? CB_XFREE : k < 5 ? CB_EARLY : CB_YOUT), 0, budget);
              fence_async_smem();
            }
            mbar_wait(c.bar + 8 * (BAR_EMPTYB + (last & 7)), (last >> 3) & 1, budget);
            if (elect_one()) {
              mbar_expect_tx(bar, bytes);
              tma_3d(slot, m, bar, 0, row, panel0);
            }
            slot += bytes;
            if (slot == c.sm + SM_B + 98304) slot = c.sm + SM_B;
            dist = __funnelshift_r(dist, slots, 4);
            tab >>= 4;
            k++;
          }
        }
      }
    } else {
      const int w = warp - 10;
      const int row0 = 64 * (16 * w + c.i);
      mbar_wait(c.sm + CV_BAR + 8 * CB_P2, 0, budget);
      if (w == 0) {
        fence_async_smem();
        if (lane < 2) mbar_arrive_cluster(mapa(c.sm + CV_BAR + 8 * CB_LATE, lane));
      } else if (elect_one()) {
        red_release(&g_xcnt[16 + (blockIdx.x >> 3)]);
        mbar_arrive(c.bar + 8 * BAR_REL);
        MSTAMP(44);
      }
      __syncwarp();
      uint32_t* my_flag = g_flag + ((16 * w + c.i) * 8 + c.j) * FS;
#pragma unroll 1
      for (int pc = 1; pc < 26; pc++) {
        const int l = pc >= 13, u = pc - 13 * l;
        if (pc > 1) {
          if (pc == 8) { reinterpret_cast<uint4*>(&g_part[2][c.j][row0])[lane] = make_uint4(0, 0, 0, 0); __syncwarp(); }
          mbar_wait(c.bar + 8 * (BAR_PUB + 13 * w + u), u < 2 ? 0 : l, budget);
          st_release(my_flag, 32 * c.ep + pc + 1);
        }
        float2* part = &g_part[3 * l + (u == 5)][0][0];
#pragma unroll 1
        for (uint32_t jobs = pc == 1 ? 0x453u : u == 5 ? 0x421u : u == 1 ? 4u : 0u; jobs; jobs >>= 4) {
          const int job = jobs & 15;
          if (job < 3) {
            const int r = 32 * (job - 1) + lane;
            float s0 = 0.f, s1 = 0.f, q0 = 0.f, q1 = 0.f;
#pragma unroll 2
            for (int x = 0; x < 16; x++) {
              uint32_t v[4];
              asm volatile("ld.shared.v4.u32 {%0,%1,%2,%3}, [%4];" : "=r"(v[0]), "=r"(v[1]), "=r"(v[2]), "=r"(v[3])
                           : "r"(c.sm + SM_X + w * 16384 + x * 1024 + r * 16) : "memory");
#pragma unroll
              for (int y = 0; y < 4; y++) {
                const float a = bf_lo(v[y]), b = bf_hi(v[y]);
                s0 += a; s1 += b; q0 = fmaf(a, a, q0); q1 = fmaf(b, b, q1);
              }
            }
            put_stat(part + c.j * SEQ + row0 + r, s0 + s1, q0 + q1, true, c.ep);
          } else if (job == 3) {
            if (w == 1) {
              mbar_wait(c.sm + CV_BAR + 8 * CB_YOUT, 0, budget);
              mbar_wait(c.sm + CV_BAR + 8 * CB_EARLY, 0, budget);
              if (lane == 0) red_release(&g_xcnt[32 + (blockIdx.x >> 3)]);
              __syncwarp();
            }
            uint32_t xseen;
#pragma unroll 1
            do {
              asm volatile("ld.acquire.gpu.global.u32 %0, [%1];" : "=r"(xseen) : "l"(g_xcnt + 32 + (lane & 15)) : "memory");
            } while (!__all_sync(0xffffffffu, (int)(xseen - 8 * c.ep) >= 8) && --budget > 0);
            if (w == 0) {
              float4 s = make_float4(0.f, 0.f, 0.f, 0.f);
#pragma unroll
              for (int x = 0; x < 4; x++) {
                const float4 v = __ldcg(reinterpret_cast<const float4*>(&g_cs1[x][c.j * 128]) + lane);
                s.x += v.x; s.y += v.y; s.z += v.z; s.w += v.w;
              }
              reinterpret_cast<float4*>(smem + SM_CS1)[lane] = s;
            } else {
#pragma unroll
              for (int x = 0; x < 4; x++) {
                const int y = min(32 * x + lane, 111);
                const float4 v = __ldcg(reinterpret_cast<const float4*>(g_cs3 + c.j * 448) + y);
                if (x < 2) {
                  uint32_t* d = reinterpret_cast<uint32_t*>(smem + SM_CS3) + (y >> 2) * 8 + (y & 1) * 4 + ((y >> 1) & 1);
                  d[0] = pack_f16(v.x, v.y); d[2] = pack_f16(v.z, v.w);
                } else {
                  reinterpret_cast<float4*>(smem + SM_CS3)[y] = v;
                }
              }
            }
            __syncwarp();
            if (lane == 0) {
              mbar_arrive(c.bar + 8 * BAR_CS);
              if (c.bid == 0 && w == 0) { g_epoch = c.ep + 1; *reinterpret_cast<uint4*>(g_role) = make_uint4(0, 0, 0, 0); }
            }
          } else {
            const int r = job == 4 ? 2 * lane : token_shift(c.j) > 0 ? 64 : -2;
            const float2* src = part + min(max(row0 + r, 0), SEQ - 2);
            float4 v[8];
#pragma unroll 1
            do {
              uint32_t ok = 1;
#pragma unroll
              for (int x = 0; x < 8; x++) {
                asm volatile("ld.relaxed.gpu.global.v4.f32 {%0,%1,%2,%3}, [%4];" : "=f"(v[x].x), "=f"(v[x].y), "=f"(v[x].z), "=f"(v[x].w) : "l"(src + x * SEQ) : "memory");
                ok &= both_valid(__float_as_uint(v[x].y), __float_as_uint(v[x].w), c.ep);
              }
              if (__all_sync(0xffffffffu, ok)) break;
            } while (--budget > 0);
            float ma = 0.f, mb = 0.f, ta = 0.f, tb = 0.f;
#pragma unroll
            for (int x = 0; x < 8; x++) { ma += v[x].x; mb += v[x].z; }
            ma *= 0.125f; mb *= 0.125f;
#pragma unroll
            for (int x = 0; x < 8; x++) {
              const float ea = v[x].x - ma, eb = v[x].z - mb;
              ta += fmaf(128.f * ea, ea, __uint_as_float(__float_as_uint(v[x].y) | 1u));
              tb += fmaf(128.f * eb, eb, __uint_as_float(__float_as_uint(v[x].w) | 1u));
            }
            *reinterpret_cast<float4*>(smem + SM_RS + (68 * w + 2 + r) * 8) =
                make_float4(ma, rsqrt_fast(fmaf(ta, 1.f / DM, LN_EPS)), mb, rsqrt_fast(fmaf(tb, 1.f / DM, LN_EPS)));
            __syncwarp();
            if (job == 4 && lane == 0) mbar_arrive(c.sm + CV_BAR + 8 * (CB_STAT + w));
          }
        }
        if (pc == Y_AT) {
          if (elect_one()) {
            const uint32_t bar = c.bar + 8 * (BAR_OWN + w);
            fence_async_global();
            fence_async_smem();
            mbar_expect_tx(bar, 16384);
            tma_2d(c.sm + SM_X + w * 16384, &maps.m[M_Y], bar, 2 * row0, 16 * c.j);
            tma_2d(c.sm + SM_X + w * 16384 + 8192, &maps.m[M_Y], bar, 2 * row0, 16 * c.j + 8);
          }
          __syncwarp();
        }
      }
    }
    cluster_exit_barrier();
  } else {
    reg_alloc<REG_CONS>();
#define WSTAMP(idx) do {} while (0)
    const int t = tid & 127, g = lane >> 2, qd = lane & 3;
    const int wrow = 64 * (16 * wg + c.i) + (t >> 5) * 16, row = wrow + g;
    const uint32_t frag = row * 16 + qd * 4 + c.j * 16 * CB_BYTES;
    const uint32_t stage = c.sm + SM_X + wg * 16384 + (lane >> 4) * 1024 + ((t >> 5) * 16 + (lane & 15)) * 16;
    const uint32_t pub = c.bar + 8 * (BAR_PUB + 13 * wg);
    const uint32_t rstat = c.sm + SM_RS + (68 * wg + 2 + (t >> 5) * 16 + g) * 8;
    Pipe p;
    p.ko = 0; p.kp = 0; p.po = 64; p.turn = 0; p.budget = SPIN_LIMIT;
    p.a0 = desc_a(c, SM_A) + wg * NA * (A_SLOT >> 4); p.a1 = p.a0 + (A_SLOT >> 4); p.ar = p.a1 + (A_SLOT >> 4);
    p.signals = t == 0 || t == 32 || t == 64;
    p.rel = mapa(c.bar + 8 * (t == 64 ? BAR_EMPTYB : BAR_EMPTYA + wg * 9), t == 32 ? c.r ^ 1 : c.r);
    auto fence_sched = [&]() { mbar_wait(c.bar + 8 * BAR_CS, 0, p.budget); };
    uint32_t x3[32];
    float acc[64];
#pragma unroll
    for (int x = 0; x < 64; x++) acc[x] = 0.f;
    WSTAMP(0);
    if (wg == 1) {
      mbar_wait(c.bar + 8 * BAR_REL, 0, p.budget);
#pragma unroll 2
      for (int x = 0; x < 8; x++)
        reinterpret_cast<uint4*>(g_y)[blockIdx.x * 2048 + 1024 + x * 128 + t] = reinterpret_cast<const uint4*>(smem + CV_K + 128 + 16384)[x * 128 + t];
      __syncwarp();
      mbar_arrive_if(c.sm + CV_BAR + 8 * CB_YOUT, lane == 0);
    }
    {
      mbar_wait(c.bar + 8 * (BAR_FULLA + 8 * wg + 2 * c.r), 0, p.budget);
      mbar_wait(c.bar + 8 * (BAR_FULLA + 8 * wg + 2 * c.r + 1), 0, p.budget);
      const uint32_t own = c.sm + SM_A + (wg * NA + 2 * c.r) * A_SLOT + (lane >> 4) * 1088 + ((token_shift(c.j) < 0 ? 4 : 0) + (t >> 5) * 16 + (lane & 15)) * 16;
#pragma unroll
      for (int x = 0; x < 32; x += 4) ldsm_x4(own + x * 544, x3[x], x3[x + 1], x3[x + 2], x3[x + 3]);
    }
#pragma unroll 1
    for (int ph = 0; ph < 6; ph++) {
      const int l = ph >= 3, s = ph - 3 * l;
      if (s < 2) {
        gemm_begin<128>(c, wg, warp & 3, p, s, s != l);
        p.keep = s;
        if (s == 0) {
          float sum[4] = {0.f, 0.f, 0.f, 0.f}, lo[4] = {0.f, 0.f, 0.f, 0.f}, hi[4] = {0.f, 0.f, 0.f, 0.f};
#pragma unroll
          for (int x = 0; x < 32; x += 4) {
            mma16816(sum, x3[x], x3[x + 1], x3[x + 2], x3[x + 3], 0x3f803f80u, 0x3f803f80u);
            mma16816(lo, x3[x], x3[x + 1], x3[x + 2], x3[x + 3], x3[x], x3[x + 2]);
            mma16816(hi, x3[x], x3[x + 1], x3[x + 2], x3[x + 3], x3[x + 1], x3[x + 3]);
          }
          put_stat(&g_part[3 * l][c.j][row], sum[0], (g & 1) ? lo[1] : lo[0], qd == (g >> 1), c.ep);
          put_stat(&g_part[3 * l][c.j][row + 8], sum[2], (g & 1) ? hi[3] : hi[2], qd == (g >> 1), c.ep);
          WSTAMP(1 + 16 * l);
        }
      } else {
        char* hp = reinterpret_cast<char*>(g_hid) + frag + c.j * 40 * CB_BYTES;
        uint32_t held[64];
        float acc3[128];
        gemm_step<256, true>(acc3, c, wg, p, Nop());
        float2 s0 = make_float2(0.f, 0.f), s1 = s0;
        gemm_steps<256, false>(acc3, c, wg, p, 15, LEAD3, [&]() {
          mbar_wait(c.sm + CV_BAR + 8 * (CB_STAT + wg), 1, p.budget);
          s0 = lds_f2(rstat); s1 = lds_f2(rstat + 64);
          s0.y *= 0.5f; s1.y *= 0.5f;
        }, Nop());
        WSTAMP(6 + 16 * l);
#pragma unroll
        for (int x = 0; x < 64; x++) held[x] = pack_f16(acc3[2 * x] * ((x & 1) ? s1.y : s0.y), acc3[2 * x + 1] * ((x & 1) ? s1.y : s0.y));
        const uint32_t n0 = pack_f16(-s0.x * s0.y, -s0.x * s0.y), n1 = pack_f16(-s1.x * s1.y, -s1.x * s1.y);
        float accb[96];
#pragma unroll
        for (int x = 0; x < 24; x++) {
          const float2 cs = (reinterpret_cast<const float2*>(smem + SM_CS3 + 1024) + qd)[4 * x];
          accb[4 * x] = -s0.x * cs.x; accb[4 * x + 1] = -s0.x * cs.y; accb[4 * x + 2] = -s1.x * cs.x; accb[4 * x + 3] = -s1.x * cs.y;
        }
        pin(accb);
        WSTAMP(7 + 16 * l);
        gemm_begin<192>(c, wg, warp & 3, p, 3, false);
#pragma unroll 1
        for (int pn = 0; pn < 4; pn++) {
#pragma unroll
          for (int u = 0; u < 4; u++)
            gemm_step<192, false>(accb, c, wg, p, [&]() {
              const uint2 cs = reinterpret_cast<const uint2*>(smem + SM_CS3)[16 * pn + 4 * u + qd];
              const uint32_t h[4] = {hfma2(cs.x, n0, held[4 * u]), hfma2(cs.x, n1, held[4 * u + 1]), hfma2(cs.y, n0, held[4 * u + 2]), hfma2(cs.y, n1, held[4 * u + 3])};
              gelu_chunk<4>(h, hp + 2 * u * CB_BYTES);
            });
          hp += 8 * CB_BYTES;
          __syncwarp();
          mbar_arrive_if(pub + 8 * (6 + pn), lane == 0);
          if (pn < 3) pick_group<16, 1, 4>(held, pn + 1);
        }
        WSTAMP(8 + 16 * l);
#pragma unroll
        for (int x = 0; x < 32; x++) { acc[2 * x] = bf_lo(x3[x]); acc[2 * x + 1] = bf_hi(x3[x]); }
        pin(acc);
        WSTAMP(9 + 16 * l);
        gemm_begin<128>(c, wg, warp & 3, p, 4, false);
        gemm_step<128, false>(acc, c, wg, p, Nop());
        pin(accb);
#pragma unroll 1
        for (int hpn = 0; hpn < 6; hpn++) {
#pragma unroll
          for (int u = 0; u < 4; u++)
            gemm_step<128, false>(acc, c, wg, p, [&]() {
              const uint32_t h[2] = {pack_f16(accb[4 * u] * s0.y, accb[4 * u + 1] * s0.y), pack_f16(accb[4 * u + 2] * s1.y, accb[4 * u + 3] * s1.y)};
              gelu_chunk<2>(h, hp + u * CB_BYTES);
            });
          hp += 4 * CB_BYTES;
          __syncwarp();
          mbar_arrive_if(pub + 8 * (10 + (hpn >> 1)), (hpn & 1) && lane == 0);
          if (hpn < 5) pick_group<16, 1, 6>(accb, hpn + 1);
        }
        WSTAMP(12 + 16 * l);
        p.keep = 1;
#pragma unroll
        for (int x = 0; x < 32; x++) x3[x] = 0;
      }
      p.sh = ph == 0 ? (token_shift(c.j) & 3) * 0x55555555u : ph == 4 ? __funnelshift_r(0xaa5faa5fu, 0xaa5faa5fu, 2 * (c.j & 6)) : 0;
      p.wide = s == l ? 4 : 0;
      float2 s0 = make_float2(0.f, 0.f), s1 = s0;
      gemm_steps<128, true, true>(acc, c, wg, p, s == 2 ? 31 : 16, (LEADS >> (4 * ph)) & 15, Nop(), [&]() {
        if (s == 0) {
          const int sh = l == 0 ? token_shift(c.j) : 0;
          mbar_wait(c.sm + CV_BAR + 8 * (CB_STAT + wg), 0, p.budget);
          s0 = lds_f2(rstat + 8 * sh); s1 = lds_f2(rstat + 8 * sh + 64);
          s0.y *= (row + sh < 0 ? 0.f : 0.5f) * rsqrt_fast(fmaxf(fmaf(-LN_EPS * s0.y, s0.y, 1.f), 0.f) + LN_EPS);
          s1.y *= (row + sh + 8 >= SEQ ? 0.f : 0.5f) * rsqrt_fast(fmaxf(fmaf(-LN_EPS * s1.y, s1.y, 1.f), 0.f) + LN_EPS);
          fence_sched();
        }
      });
      WSTAMP((s == 2 ? 10 : 2 + 2 * s) + 16 * l);
      if (s == 0) {
#pragma unroll
        for (int pn = 0; pn < 2; pn++) {
          uint32_t v[16];
          if (pn == 0) {
            fold_tiles<4>(v, acc, reinterpret_cast<const float2*>(smem + SM_CS1) + qd, s0, s1);
#pragma unroll
            for (int x = 0; x < 8; x++) stg32(reinterpret_cast<char*>(g_h) + frag + (x >> 1) * CB_BYTES + (x & 1) * 128, v[x]);
            fence_sched();
            fold_tiles<4>(v + 8, acc + 16, reinterpret_cast<const float2*>(smem + SM_CS1) + qd + 16, s0, s1);
#pragma unroll
            for (int x = 8; x < 16; x++) stg32(reinterpret_cast<char*>(g_h) + frag + (x >> 1) * CB_BYTES + (x & 1) * 128, v[x]);
            __syncwarp();
            mbar_arrive_if(pub + 8 * 2, lane == 0);
          } else {
            fold_tiles<8>(v, acc + 32, reinterpret_cast<const float2*>(smem + SM_CS1) + qd + 32, s0, s1);
            emit_panel(v, reinterpret_cast<char*>(g_h) + frag + 8 * CB_BYTES, pub + 8 * 3);
          }
          if (l == 0) stage_tiles<8>(v, stage + pn * 8192);
        }
        s0 = lds_f2(rstat); s1 = lds_f2(rstat + 64);
        const float nb0 = -s0.x * s0.y, nb1 = -s1.x * s1.y;
#pragma unroll
        for (int x = 0; x < 32; x++) {
          acc[2 * x] = fmaf(bf_lo(x3[x]), (x & 1) ? s1.y : s0.y, (x & 1) ? nb1 : nb0);
          acc[2 * x + 1] = fmaf(bf_hi(x3[x]), (x & 1) ? s1.y : s0.y, (x & 1) ? nb1 : nb0);
        }
        WSTAMP(3 + 16 * l);
      } else if (s == 1) {
        uint32_t v[32];
#pragma unroll
        for (int x = 0; x < 32; x++) v[x] = pack_bf16(acc[2 * x], acc[2 * x + 1]);
        emit_panel(v, reinterpret_cast<char*>(g_x1) + frag, pub + 8 * 4);
        stage_tiles<16>(v, stage);
        gemm_begin<256>(c, wg, warp & 3, p, 2, true);
        emit_panel(v + 16, reinterpret_cast<char*>(g_x1) + frag + 8 * CB_BYTES, pub + 8 * 5);
#pragma unroll
        for (int x = 0; x < 32; x++) x3[x] = badd2(x3[x], v[x]);
        WSTAMP(5 + 16 * l);
      } else if (l == 0) {
        put_partial(acc, &g_part[2][c.j][row], 0);
        WSTAMP(11);
        const float2* sp = &g_part[2][2 * qd][row];
        RowStats rs;
        rs.load(sp, sp + 8);
        float yf[64];
        mbar_wait(c.bar + 8 * (BAR_OWN + wg), 0, p.budget);
#pragma unroll
        for (int x = 0; x < 16; x++) {
          uint32_t y0, y1;
          asm volatile("ld.shared.v2.u32 {%0,%1}, [%2];" : "=r"(y0), "=r"(y1) : "r"(c.sm + SM_X + wg * 16384 + x * 1024 + t * 8) : "memory");
          yf[4 * x] = bf_lo(y0); yf[4 * x + 1] = bf_hi(y0); yf[4 * x + 2] = bf_lo(y1); yf[4 * x + 3] = bf_hi(y1);
        }
        pin(yf);
        rs.finish(sp, sp + 8, p.budget, s0, s1);
        WSTAMP(13);
        float nb0 = -s0.x * s0.y, nb1 = -s1.x * s1.y;
#pragma unroll
        for (int pn = 0; pn < 2; pn++) {
          if (pn == 1) { const float z = late_zero(c.sm + SM_ZERO); nb0 += z; nb1 += z; }
#pragma unroll
          for (int x = 16 * pn; x < 16 * pn + 16; x++) {
            const float r = (x & 1) ? s1.y : s0.y, nb = (x & 1) ? nb1 : nb0;
            x3[x] = pack_bf16(fmaf(fmaf(acc[2 * x], r, nb), yf[2 * x], acc[2 * x]), fmaf(fmaf(acc[2 * x + 1], r, nb), yf[2 * x + 1], acc[2 * x + 1]));
          }
          if (pn == 1) stage_tiles<16>(x3, stage);
          emit_panel(x3 + 16 * pn, reinterpret_cast<char*>(g_x3[1]) + frag + pn * 8 * CB_BYTES, pub + 8 * pn);
        }
      }
    }
    {
      const uint32_t ob = c.sm + SM_X + warp * 4096, oa = ob + (lane & 15) * 128 + (((lane >> 4) ^ (lane & 7)) << 4);
#pragma unroll
      for (int pn = 0; pn < 2; pn++) {
#pragma unroll
        for (int x = 0; x < 8; x += 2) {
          const float* a = acc + 32 * pn + 4 * x;
          stsm_x4((oa ^ (x << 4)) + pn * 2048, pack_bf16(a[0], a[1]), pack_bf16(a[2], a[3]), pack_bf16(a[4], a[5]), pack_bf16(a[6], a[7]));
        }
        fence_async_smem();
        __syncwarp();
        if (elect_one()) {
          tma_store_2d(&maps.m[M_OUT], ob + pn * 2048, c.j * 128 + 64 * pn, 64 * (16 * wg + c.i) + 16 * (warp & 3));
          if (pn == 1) {
            bulk_commit();
            asm volatile("cp.async.bulk.wait_group.read 0;" ::: "memory");
          }
        }
      }
    }
    WSTAMP(27);
    cluster_exit_barrier();
    WSTAMP(30);
  }
}

typedef CUresult (*EncodeFn)(CUtensorMap*, CUtensorMapDataType, cuuint32_t, void*, const cuuint64_t*, const cuuint64_t*, const cuuint32_t*,
                             const cuuint32_t*, CUtensorMapInterleave, CUtensorMapSwizzle, CUtensorMapL2promotion, CUtensorMapFloatOOBfill);

void encode(EncodeFn fn, CUtensorMap* m, CUtensorMapDataType type, const void* ptr, int rank, const cuuint64_t* dims, const cuuint64_t* strides,
            const cuuint32_t* box, CUtensorMapSwizzle swizzle, CUtensorMapL2promotion promo = CU_TENSOR_MAP_L2_PROMOTION_L2_128B) {
  const cuuint32_t es[3] = {1, 1, 1};
  fn(m, type, rank, const_cast<void*>(ptr), dims, strides, box, es, CU_TENSOR_MAP_INTERLEAVE_NONE, swizzle, promo, CU_TENSOR_MAP_FLOAT_OOB_FILL_NONE);
}
void map_act(EncodeFn fn, CUtensorMap* m, const void* ptr, int cols, int rows = 64) {
  const cuuint64_t dims[2] = {(cuuint64_t)SEQ * 2, (cuuint64_t)cols / 8}, st[1] = {(cuuint64_t)CB_BYTES};
  const cuuint32_t box[2] = {(cuuint32_t)rows * 2, 8};
  encode(fn, m, CU_TENSOR_MAP_DATA_TYPE_UINT64, ptr, 2, dims, st, box, CU_TENSOR_MAP_SWIZZLE_NONE);
}
void map_rows(EncodeFn fn, CUtensorMap* m, const void* ptr, int rows, int cols, int box_rows, int box_cols, CUtensorMapSwizzle swizzle,
              CUtensorMapL2promotion promo) {
  const cuuint64_t dims[2] = {(cuuint64_t)cols, (cuuint64_t)rows}, st[1] = {(cuuint64_t)cols * 2};
  const cuuint32_t box[2] = {(cuuint32_t)box_cols, (cuuint32_t)box_rows};
  encode(fn, m, CU_TENSOR_MAP_DATA_TYPE_BFLOAT16, ptr, 2, dims, st, box, swizzle, promo);
}
void map_w(EncodeFn fn, CUtensorMap* m, const void* ptr, int rows, int cols, int panels) {
  const cuuint64_t dims[3] = {64, (cuuint64_t)rows, (cuuint64_t)cols / 64}, st[2] = {(cuuint64_t)cols * 2, 128};
  const cuuint32_t box[3] = {64, 64, (cuuint32_t)panels};
  encode(fn, m, CU_TENSOR_MAP_DATA_TYPE_BFLOAT16, ptr, 3, dims, st, box, CU_TENSOR_MAP_SWIZZLE_128B);
}

}

extern "C" void kernel_launch(void* const* d_in, const int* in_sizes, int n_in, void* d_out, int out_size) {
  (void)in_sizes; (void)n_in; (void)out_size;
  const bf16* q = (const bf16*)d_in[0];
  const bf16* k = (const bf16*)d_in[1];
  const bf16* v = (const bf16*)d_in[2];
  const bf16* shift_k = (const bf16*)d_in[3];
  const bf16* ssm_k = (const bf16*)d_in[4];
  const bf16* ssm_d = (const bf16*)d_in[5];
  const bf16* w1 = (const bf16*)d_in[7];
  const bf16* w2 = (const bf16*)d_in[8];
  const bf16* w3 = (const bf16*)d_in[9];
  const bf16* w4 = (const bf16*)d_in[10];

  static EncodeFn fn = nullptr;
  static void *p_x3, *p_h, *p_x1, *p_hid, *p_y;
  if (!fn) {
    void* p = nullptr;
    cudaDriverEntryPointQueryResult qr;
    cudaGetDriverEntryPoint("cuTensorMapEncodeTiled", &p, cudaEnableDefault, &qr);
    fn = (EncodeFn)p;
    cudaGetSymbolAddress(&p_x3, g_x3);
    cudaGetSymbolAddress(&p_h, g_h);
    cudaGetSymbolAddress(&p_x1, g_x1);
    cudaGetSymbolAddress(&p_hid, g_hid);
    cudaGetSymbolAddress(&p_y, g_y);
    cudaFuncSetAttribute(fused_kernel, cudaFuncAttributeMaxDynamicSharedMemorySize, MEGA_SMEM);
  }
  Params maps;
  map_act(fn, &maps.m[M_X3B], (const bf16*)p_x3 + SEQ * DM, DM);
  map_act(fn, &maps.m[M_X3S], p_x3, DM, 68);
  map_act(fn, &maps.m[M_H], p_h, DM);
  map_act(fn, &maps.m[M_HS], p_h, DM, 68);
  map_act(fn, &maps.m[M_X1], p_x1, DM);
  map_act(fn, &maps.m[M_HID], p_hid, FF);
  map_act(fn, &maps.m[M_Y], p_y, DM);
  map_rows(fn, &maps.m[M_OUT], d_out, SEQ, DM, 16, 64, CU_TENSOR_MAP_SWIZZLE_128B, CU_TENSOR_MAP_L2_PROMOTION_L2_128B);
  map_w(fn, &maps.m[M_W1], w1, DM, DM, 2);
  map_w(fn, &maps.m[M_W2], w2, DM, DM, 2);
  map_w(fn, &maps.m[M_W3A], w3, DM, FF, 4);
  map_w(fn, &maps.m[M_W3B], w3, DM, FF, 3);
  map_w(fn, &maps.m[M_W4], w4, FF, DM, 2);

  map_rows(fn, &maps.m[M_K], k, SEQ, DM, 256, 8, CU_TENSOR_MAP_SWIZZLE_NONE, KV_PROMO);
  map_rows(fn, &maps.m[M_V], v, SEQ, DM, 256, 8, CU_TENSOR_MAP_SWIZZLE_NONE, KV_PROMO);
  map_rows(fn, &maps.m[M_Q], q, SEQ, DM, 256, 8, CU_TENSOR_MAP_SWIZZLE_NONE, KV_PROMO);
  map_rows(fn, &maps.m[M_W1C], w1, DM, DM, 256, 32, CU_TENSOR_MAP_SWIZZLE_64B, CU_TENSOR_MAP_L2_PROMOTION_L2_128B);
  map_rows(fn, &maps.m[M_W3C], w3, DM, FF, 256, 32, CU_TENSOR_MAP_SWIZZLE_64B, CU_TENSOR_MAP_L2_PROMOTION_L2_128B);
  maps.q = q; maps.shift_k = shift_k; maps.ssm_k = ssm_k; maps.ssm_d = ssm_d; maps.w2 = w2;
  fused_kernel<<<128, 384, MEGA_SMEM, cudaStreamPerThread>>>(maps);
}
```

```cpp
#include <cuda_runtime.h>
#include <cuda_bf16.h>
#include <cuda.h>
#include <stdint.h>

namespace {

typedef __nv_bfloat16 bf16;
constexpr int SEQ = 2048, DM = 1024, FF = 3584;
constexpr float LN_EPS = 1e-5f;

constexpr int CB_BYTES = SEQ * 16;
__device__ __align__(1024) bf16 g_x3[2][SEQ * DM];
__device__ __align__(1024) bf16 g_h[SEQ * DM];
__device__ __align__(1024) bf16 g_x1[SEQ * DM];
__device__ __align__(1024) bf16 g_hid[SEQ * FF];
__device__ __align__(1024) bf16 g_y[SEQ * DM];
__device__ __align__(128) float g_cs1[4][DM];
__device__ __align__(128) float g_cs3[FF];
__device__ __align__(128) uint32_t g_epoch;
__device__ __align__(128) float2 g_part[5][8][SEQ];
__device__ __align__(128) float2 g_qstat[SEQ];
__device__ __align__(128) uint32_t g_qcnt;
__device__ __align__(128) uint32_t g_xcnt[48];
constexpr int FS = 8;
__device__ __align__(128) uint32_t g_flag[32 * 8 * FS];
__device__ __align__(128) uint32_t g_clock[12];
__device__ __align__(128) uint32_t g_role[4];

__device__ __forceinline__ uint32_t smem_u32(const void* p) { return (uint32_t)__cvta_generic_to_shared(p); }
__device__ __forceinline__ uint32_t opaque(uint32_t x) { uint32_t y; asm volatile("mov.u32 %0, %1;" : "=r"(y) : "r"(x)); return y; }
__device__ __forceinline__ void mbar_init(uint32_t bar, uint32_t cnt) { asm volatile("mbarrier.init.shared::cta.b64 [%0], %1;" :: "r"(bar), "r"(cnt)); }
__device__ __forceinline__ void mbar_expect_tx(uint32_t bar, uint32_t bytes) {
  asm volatile("mbarrier.arrive.expect_tx.shared::cta.b64 _, [%0], %1;" :: "r"(bar), "r"(bytes) : "memory");
}
__device__ __forceinline__ void mbar_expect_tx_cluster(uint32_t bar, uint32_t bytes) {
  asm volatile("mbarrier.arrive.expect_tx.shared::cluster.b64 _, [%0], %1;" :: "r"(bar), "r"(bytes) : "memory");
}
__device__ __forceinline__ void mbar_arrive_cluster(uint32_t bar) { asm volatile("mbarrier.arrive.shared::cluster.b64 _, [%0];" :: "r"(bar) : "memory"); }
__device__ __forceinline__ void mbar_arrive(uint32_t bar) { asm volatile("mbarrier.arrive.shared::cta.b64 _, [%0];" :: "r"(bar) : "memory"); }
__device__ __forceinline__ void mbar_arrive_if(uint32_t bar, bool cond) {
  asm volatile("{\n.reg .pred p;\nsetp.ne.b32 p, %1, 0;\n@p mbarrier.arrive.shared::cta.b64 _, [%0];\n}" :: "r"(bar), "r"((uint32_t)cond) : "memory");
}
constexpr int SPIN_LIMIT = 1 << 16;
__device__ __forceinline__ bool mbar_try(uint32_t bar, uint32_t parity) {
  uint32_t done;
  asm volatile("{\n.reg .pred p;\nmbarrier.try_wait.parity.shared::cta.b64 p, [%1], %2;\nselp.b32 %0, 1, 0, p;\n}"
               : "=r"(done) : "r"(bar), "r"(parity) : "memory");
  return done != 0;
}
__device__ __forceinline__ void mbar_wait(uint32_t bar, uint32_t parity, int& budget) {
#pragma unroll 1
  while (!mbar_try(bar, parity)) { if (--budget <= 0) break; }
}
__device__ __forceinline__ bool elect_one() {
  uint32_t p;
  asm volatile("{\n.reg .pred P;\nelect.sync _|P, 0xffffffff;\nselp.b32 %0, 1, 0, P;\n}" : "=r"(p));
  return p != 0;
}
__device__ __forceinline__ void fence_async_smem() { asm volatile("fence.proxy.async.shared::cta;" ::: "memory"); }
__device__ __forceinline__ void fence_async_global() { asm volatile("fence.proxy.async.global;" ::: "memory"); }
__device__ __forceinline__ void named_bar(int id, int n) { asm volatile("bar.sync %0, %1;" :: "r"(id), "r"(n) : "memory"); }
__device__ __forceinline__ uint4 ld_nc_u4(const void* p) {
  uint4 v; asm volatile("ld.global.nc.L1::no_allocate.v4.u32 {%0,%1,%2,%3}, [%4];" : "=r"(v.x), "=r"(v.y), "=r"(v.z), "=r"(v.w) : "l"(p)); return v;
}
__device__ __forceinline__ void tma_2d_mc(uint32_t dst, const CUtensorMap* m, uint32_t bar, int c0, int c1, uint16_t mask) {
  asm volatile("cp.async.bulk.tensor.2d.shared::cluster.global.mbarrier::complete_tx::bytes.multicast::cluster [%0], [%1, {%3, %4}], [%2], %5;"
               :: "r"(dst), "l"(m), "r"(bar), "r"(c0), "r"(c1), "h"(mask) : "memory");
}
__device__ __forceinline__ void tma_2d(uint32_t dst, const CUtensorMap* m, uint32_t bar, int c0, int c1) {
  asm volatile("cp.async.bulk.tensor.2d.shared::cluster.global.mbarrier::complete_tx::bytes [%0], [%1, {%3, %4}], [%2];"
               :: "r"(dst), "l"(m), "r"(bar), "r"(c0), "r"(c1) : "memory");
}
__device__ __forceinline__ void bulk_copy_cluster(uint32_t dst, uint32_t src, uint32_t bytes, uint32_t bar) {
  asm volatile("cp.async.bulk.shared::cluster.shared::cta.mbarrier::complete_tx::bytes [%0], [%1], %2, [%3];"
               :: "r"(dst), "r"(src), "r"(bytes), "r"(bar) : "memory");
}
__device__ __forceinline__ uint32_t mapa(uint32_t addr, uint32_t cta) {
  uint32_t r; asm volatile("mapa.shared::cluster.u32 %0, %1, %2;" : "=r"(r) : "r"(addr), "r"(cta)); return r;
}
__device__ __forceinline__ void bulk_store(void* dst, uint32_t src, uint32_t bytes) {
  asm volatile("cp.async.bulk.global.shared::cta.bulk_group [%0], [%1], %2;" :: "l"(dst), "r"(src), "r"(bytes) : "memory");
}
__device__ __forceinline__ void tma_3d(uint32_t dst, const CUtensorMap* m, uint32_t bar, int c0, int c1, int c2) {
  asm volatile("cp.async.bulk.tensor.3d.shared::cluster.global.mbarrier::complete_tx::bytes [%0], [%1, {%3, %4, %5}], [%2];"
               :: "r"(dst), "l"(m), "r"(bar), "r"(c0), "r"(c1), "r"(c2) : "memory");
}
__device__ __forceinline__ void tma_store_2d(const CUtensorMap* m, uint32_t src, int c0, int c1) {
  asm volatile("cp.async.bulk.tensor.2d.global.shared::cta.bulk_group [%0, {%2, %3}], [%1];" :: "l"(m), "r"(src), "r"(c0), "r"(c1) : "memory");
}
__device__ __forceinline__ void bulk_commit() { asm volatile("cp.async.bulk.commit_group;" ::: "memory"); }
__device__ __forceinline__ void bulk_wait_all() { asm volatile("cp.async.bulk.wait_group 0;" ::: "memory"); }
__device__ __forceinline__ void prefetch_l2(const void* p, uint32_t bytes) { asm volatile("cp.async.bulk.prefetch.L2.global [%0], %1;" :: "l"(p), "r"(bytes) : "memory"); }
__device__ __forceinline__ void cluster_exit_barrier() {
  __syncwarp();
  asm volatile("barrier.cluster.arrive.relaxed;\nbarrier.cluster.wait;" ::: "memory");
}
__device__ __forceinline__ void wg_fence() { asm volatile("wgmma.fence.sync.aligned;" ::: "memory"); }
__device__ __forceinline__ void wg_commit() { asm volatile("wgmma.commit_group.sync.aligned;" ::: "memory"); }
template <int N> __device__ __forceinline__ void wg_wait() { asm volatile("wgmma.wait_group.sync.aligned %0;" :: "n"(N) : "memory"); }
template <int R> __device__ __forceinline__ void reg_alloc() { asm volatile("setmaxnreg.inc.sync.aligned.u32 %0;" :: "n"(R)); }
template <int R> __device__ __forceinline__ void reg_dealloc() { asm volatile("setmaxnreg.dec.sync.aligned.u32 %0;" :: "n"(R)); }
__device__ __forceinline__ void ldsm_x4(uint32_t addr, uint32_t& r0, uint32_t& r1, uint32_t& r2, uint32_t& r3) {
  asm volatile("ldmatrix.sync.aligned.m8n8.x4.shared.b16 {%0,%1,%2,%3}, [%4];" : "=r"(r0), "=r"(r1), "=r"(r2), "=r"(r3) : "r"(addr));
}
__device__ __forceinline__ void ldsm_x4_t(uint32_t addr, uint32_t& r0, uint32_t& r1, uint32_t& r2, uint32_t& r3) {
  asm volatile("ldmatrix.sync.aligned.m8n8.x4.trans.shared.b16 {%0,%1,%2,%3}, [%4];" : "=r"(r0), "=r"(r1), "=r"(r2), "=r"(r3) : "r"(addr));
}
__device__ __forceinline__ void stsm_x4(uint32_t addr, uint32_t r0, uint32_t r1, uint32_t r2, uint32_t r3) {
  asm volatile("stmatrix.sync.aligned.m8n8.x4.shared.b16 [%0], {%1,%2,%3,%4};" :: "r"(addr), "r"(r0), "r"(r1), "r"(r2), "r"(r3) : "memory");
}
__device__ __forceinline__ float2 lds_f2(uint32_t addr) { float2 v; asm volatile("ld.shared.v2.f32 {%0,%1}, [%2];" : "=f"(v.x), "=f"(v.y) : "r"(addr)); return v; }
__device__ __forceinline__ void sts16(uint32_t addr, uint16_t v) { asm volatile("st.shared.u16 [%0], %1;" :: "r"(addr), "h"(v) : "memory"); }
__device__ __forceinline__ void sts32(uint32_t addr, uint32_t v) { asm volatile("st.shared.u32 [%0], %1;" :: "r"(addr), "r"(v) : "memory"); }
__device__ __forceinline__ void sts128(uint32_t addr, uint4 v) {
  asm volatile("st.shared.v4.u32 [%0], {%1,%2,%3,%4};" :: "r"(addr), "r"(v.x), "r"(v.y), "r"(v.z), "r"(v.w) : "memory");
}
__device__ __forceinline__ void mma16816(float (&d)[4], uint32_t a0, uint32_t a1, uint32_t a2, uint32_t a3, uint32_t b0, uint32_t b1) {
  asm("mma.sync.aligned.m16n8k16.row.col.f32.bf16.bf16.f32 {%0,%1,%2,%3}, {%4,%5,%6,%7}, {%8,%9}, {%0,%1,%2,%3};"
               : "+f"(d[0]), "+f"(d[1]), "+f"(d[2]), "+f"(d[3]) : "r"(a0), "r"(a1), "r"(a2), "r"(a3), "r"(b0), "r"(b1));
}
__device__ __forceinline__ uint32_t pack_bf16(float lo, float hi) {
  uint32_t r; asm("cvt.rn.bf16x2.f32 %0, %1, %2;" : "=r"(r) : "f"(hi), "f"(lo)); return r;
}
__device__ __forceinline__ float bf_lo(uint32_t v) { return __uint_as_float(v << 16); }
__device__ __forceinline__ float bf_hi(uint32_t v) { return __uint_as_float(v & 0xffff0000u); }
__device__ __forceinline__ uint32_t bmul2(uint32_t a, uint32_t b) { uint32_t r; asm("mul.rn.bf16x2 %0, %1, %2;" : "=r"(r) : "r"(a), "r"(b)); return r; }
__device__ __forceinline__ uint32_t badd2(uint32_t a, uint32_t b) { uint32_t r; asm("add.rn.bf16x2 %0, %1, %2;" : "=r"(r) : "r"(a), "r"(b)); return r; }
#define STAMP(idx) do {} while (0)
#define MSTAMP(idx) do {} while (0)
#define BSTAMP(idx, saddr) do {} while (0)

__device__ __forceinline__ uint32_t pack_f16(float lo, float hi) {
  uint32_t r; asm("cvt.rn.satfinite.f16x2.f32 %0, %1, %2;" : "=r"(r) : "f"(hi), "f"(lo)); return r;
}
__device__ __forceinline__ uint32_t hfma2(uint32_t a, uint32_t b, uint32_t c) { uint32_t r; asm("fma.rn.f16x2 %0, %1, %2, %3;" : "=r"(r) : "r"(a), "r"(b), "r"(c)); return r; }
__device__ __forceinline__ uint32_t gelu_pair_f16(uint32_t h) {
  const uint32_t c0 = 0x3e623e62u, c1 = 0x34913491u;
  uint32_t u, p, z, t, r, o;
  asm("mul.rn.f16x2 %0, %1, %1;" : "=r"(u) : "r"(h));
  asm("fma.rn.f16x2 %0, %1, %2, %3;" : "=r"(p) : "r"(u), "r"(c1), "r"(c0));
  asm("mul.rn.f16x2 %0, %1, %2;" : "=r"(z) : "r"(h), "r"(p));
  asm("tanh.approx.f16x2 %0, %1;" : "=r"(t) : "r"(z));
  asm("fma.rn.f16x2 %0, %1, %2, %1;" : "=r"(r) : "r"(h), "r"(t));
  float lo, hi;
  asm("{\n.reg .f16 a, b;\nmov.b32 {a, b}, %2;\ncvt.f32.f16 %0, a;\ncvt.f32.f16 %1, b;\n}" : "=f"(lo), "=f"(hi) : "r"(r));
  asm("cvt.rn.bf16x2.f32 %0, %1, %2;" : "=r"(o) : "f"(hi), "f"(lo));
  return o;
}
__device__ __forceinline__ float gelu_from_half(float h) {
  const float c0 = 2.f * 0.7978845608028654f, c1 = 8.f * 0.7978845608028654f * 0.044715f;
  float z = h * fmaf(h * h, c1, c0);
  float t; asm("tanh.approx.f32 %0, %1;" : "=f"(t) : "f"(z));
  return fmaf(h, t, h);
}
__device__ __forceinline__ void wgmma_ss_n128(float (&d)[64], uint32_t a_lo, uint32_t b_lo) {
  asm volatile(
    "{\n.reg .b64 da, db;\nmov.b64 da, {%64, 8};\nmov.b64 db, {%65, 0x40000040};\n"
    "wgmma.mma_async.sync.aligned.m64n128k16.f32.bf16.bf16 "
    "{%0, %1, %2, %3, %4, %5, %6, %7, %8, %9, %10, %11, %12, %13, %14, %15, "
    "%16, %17, %18, %19, %20, %21, %22, %23, %24, %25, %26, %27, %28, %29, %30, %31, "
    "%32, %33, %34, %35, %36, %37, %38, %39, %40, %41, %42, %43, %44, %45, %46, %47, "
    "%48, %49, %50, %51, %52, %53, %54, %55, %56, %57, %58, %59, %60, %61, %62, %63}, "
    "da, db, 1, 1, 1, 0, 1;\n}\n"
    : "+f"(d[0]), "+f"(d[1]), "+f"(d[2]), "+f"(d[3]), "+f"(d[4]), "+f"(d[5]), "+f"(d[6]), "+f"(d[7]),
      "+f"(d[8]), "+f"(d[9]), "+f"(d[10]), "+f"(d[11]), "+f"(d[12]), "+f"(d[13]), "+f"(d[14]), "+f"(d[15]),
      "+f"(d[16]), "+f"(d[17]), "+f"(d[18]), "+f"(d[19]), "+f"(d[20]), "+f"(d[21]), "+f"(d[22]), "+f"(d[23]),
      "+f"(d[24]), "+f"(d[25]), "+f"(d[26]), "+f"(d[27]), "+f"(d[28]), "+f"(d[29]), "+f"(d[30]), "+f"(d[31]),
      "+f"(d[32]), "+f"(d[33]), "+f"(d[34]), "+f"(d[35]), "+f"(d[36]), "+f"(d[37]), "+f"(d[38]), "+f"(d[39]),
      "+f"(d[40]), "+f"(d[41]), "+f"(d[42]), "+f"(d[43]), "+f"(d[44]), "+f"(d[45]), "+f"(d[46]), "+f"(d[47]),
      "+f"(d[48]), "+f"(d[49]), "+f"(d[50]), "+f"(d[51]), "+f"(d[52]), "+f"(d[53]), "+f"(d[54]), "+f"(d[55]),
      "+f"(d[56]), "+f"(d[57]), "+f"(d[58]), "+f"(d[59]), "+f"(d[60]), "+f"(d[61]), "+f"(d[62]), "+f"(d[63])
    : "r"(a_lo), "r"(b_lo));
}
__device__ __forceinline__ void wgmma_ss_n192(float (&d)[96], uint32_t a_lo, uint32_t b_lo) {
  asm volatile(
    "{\n.reg .b64 da, db;\nmov.b64 da, {%96, 8};\nmov.b64 db, {%97, 0x40000040};\n"
    "wgmma.mma_async.sync.aligned.m64n192k16.f32.bf16.bf16 "
    "{%0, %1, %2, %3, %4, %5, %6, %7, %8, %9, %10, %11, %12, %13, %14, %15, "
    "%16, %17, %18, %19, %20, %21, %22, %23, %24, %25, %26, %27, %28, %29, %30, %31, "
    "%32, %33, %34, %35, %36, %37, %38, %39, %40, %41, %42, %43, %44, %45, %46, %47, "
    "%48, %49, %50, %51, %52, %53, %54, %55, %56, %57, %58, %59, %60, %61, %62, %63, "
    "%64, %65, %66, %67, %68, %69, %70, %71, %72, %73, %74, %75, %76, %77, %78, %79, "
    "%80, %81, %82, %83, %84, %85, %86, %87, %88, %89, %90, %91, %92, %93, %94, %95}, "
    "da, db, 1, 1, 1, 0, 1;\n}\n"
    : "+f"(d[0]), "+f"(d[1]), "+f"(d[2]), "+f"(d[3]), "+f"(d[4]), "+f"(d[5]), "+f"(d[6]), "+f"(d[7]),
      "+f"(d[8]), "+f"(d[9]), "+f"(d[10]), "+f"(d[11]), "+f"(d[12]), "+f"(d[13]), "+f"(d[14]), "+f"(d[15]),
      "+f"(d[16]), "+f"(d[17]), "+f"(d[18]), "+f"(d[19]), "+f"(d[20]), "+f"(d[21]), "+f"(d[22]), "+f"(d[23]),
      "+f"(d[24]), "+f"(d[25]), "+f"(d[26]), "+f"(d[27]), "+f"(d[28]), "+f"(d[29]), "+f"(d[30]), "+f"(d[31]),
      "+f"(d[32]), "+f"(d[33]), "+f"(d[34]), "+f"(d[35]), "+f"(d[36]), "+f"(d[37]), "+f"(d[38]), "+f"(d[39]),
      "+f"(d[40]), "+f"(d[41]), "+f"(d[42]), "+f"(d[43]), "+f"(d[44]), "+f"(d[45]), "+f"(d[46]), "+f"(d[47]),
      "+f"(d[48]), "+f"(d[49]), "+f"(d[50]), "+f"(d[51]), "+f"(d[52]), "+f"(d[53]), "+f"(d[54]), "+f"(d[55]),
      "+f"(d[56]), "+f"(d[57]), "+f"(d[58]), "+f"(d[59]), "+f"(d[60]), "+f"(d[61]), "+f"(d[62]), "+f"(d[63]),
      "+f"(d[64]), "+f"(d[65]), "+f"(d[66]), "+f"(d[67]), "+f"(d[68]), "+f"(d[69]), "+f"(d[70]), "+f"(d[71]),
      "+f"(d[72]), "+f"(d[73]), "+f"(d[74]), "+f"(d[75]), "+f"(d[76]), "+f"(d[77]), "+f"(d[78]), "+f"(d[79]),
      "+f"(d[80]), "+f"(d[81]), "+f"(d[82]), "+f"(d[83]), "+f"(d[84]), "+f"(d[85]), "+f"(d[86]), "+f"(d[87]),
      "+f"(d[88]), "+f"(d[89]), "+f"(d[90]), "+f"(d[91]), "+f"(d[92]), "+f"(d[93]), "+f"(d[94]), "+f"(d[95])
    : "r"(a_lo), "r"(b_lo));
}
__device__ __forceinline__ void wgmma_ss_n256(float (&d)[128], uint32_t a_lo, uint32_t b_lo) {
  asm volatile(
    "{\n.reg .b64 da, db;\nmov.b64 da, {%128, 8};\nmov.b64 db, {%129, 0x40000040};\n"
    "wgmma.mma_async.sync.aligned.m64n256k16.f32.bf16.bf16 "
    "{%0, %1, %2, %3, %4, %5, %6, %7, %8, %9, %10, %11, %12, %13, %14, %15, "
    "%16, %17, %18, %19, %20, %21, %22, %23, %24, %25, %26, %27, %28, %29, %30, %31, "
    "%32, %33, %34, %35, %36, %37, %38, %39, %40, %41, %42, %43, %44, %45, %46, %47, "
    "%48, %49, %50, %51, %52, %53, %54, %55, %56, %57, %58, %59, %60, %61, %62, %63, "
    "%64, %65, %66, %67, %68, %69, %70, %71, %72, %73, %74, %75, %76, %77, %78, %79, "
    "%80, %81, %82, %83, %84, %85, %86, %87, %88, %89, %90, %91, %92, %93, %94, %95, "
    "%96, %97, %98, %99, %100, %101, %102, %103, %104, %105, %106, %107, %108, %109, %110, %111, "
    "%112, %113, %114, %115, %116, %117, %118, %119, %120, %121, %122, %123, %124, %125, %126, %127}, "
    "da, db, 1, 1, 1, 0, 1;\n}\n"
    : "+f"(d[0]), "+f"(d[1]), "+f"(d[2]), "+f"(d[3]), "+f"(d[4]), "+f"(d[5]), "+f"(d[6]), "+f"(d[7]),
      "+f"(d[8]), "+f"(d[9]), "+f"(d[10]), "+f"(d[11]), "+f"(d[12]), "+f"(d[13]), "+f"(d[14]), "+f"(d[15]),
      "+f"(d[16]), "+f"(d[17]), "+f"(d[18]), "+f"(d[19]), "+f"(d[20]), "+f"(d[21]), "+f"(d[22]), "+f"(d[23]),
      "+f"(d[24]), "+f"(d[25]), "+f"(d[26]), "+f"(d[27]), "+f"(d[28]), "+f"(d[29]), "+f"(d[30]), "+f"(d[31]),
      "+f"(d[32]), "+f"(d[33]), "+f"(d[34]), "+f"(d[35]), "+f"(d[36]), "+f"(d[37]), "+f"(d[38]), "+f"(d[39]),
      "+f"(d[40]), "+f"(d[41]), "+f"(d[42]), "+f"(d[43]), "+f"(d[44]), "+f"(d[45]), "+f"(d[46]), "+f"(d[47]),
      "+f"(d[48]), "+f"(d[49]), "+f"(d[50]), "+f"(d[51]), "+f"(d[52]), "+f"(d[53]), "+f"(d[54]), "+f"(d[55]),
      "+f"(d[56]), "+f"(d[57]), "+f"(d[58]), "+f"(d[59]), "+f"(d[60]), "+f"(d[61]), "+f"(d[62]), "+f"(d[63]),
      "+f"(d[64]), "+f"(d[65]), "+f"(d[66]), "+f"(d[67]), "+f"(d[68]), "+f"(d[69]), "+f"(d[70]), "+f"(d[71]),
      "+f"(d[72]), "+f"(d[73]), "+f"(d[74]), "+f"(d[75]), "+f"(d[76]), "+f"(d[77]), "+f"(d[78]), "+f"(d[79]),
      "+f"(d[80]), "+f"(d[81]), "+f"(d[82]), "+f"(d[83]), "+f"(d[84]), "+f"(d[85]), "+f"(d[86]), "+f"(d[87]),
      "+f"(d[88]), "+f"(d[89]), "+f"(d[90]), "+f"(d[91]), "+f"(d[92]), "+f"(d[93]), "+f"(d[94]), "+f"(d[95]),
      "+f"(d[96]), "+f"(d[97]), "+f"(d[98]), "+f"(d[99]), "+f"(d[100]), "+f"(d[101]), "+f"(d[102]), "+f"(d[103]),
      "+f"(d[104]), "+f"(d[105]), "+f"(d[106]), "+f"(d[107]), "+f"(d[108]), "+f"(d[109]), "+f"(d[110]), "+f"(d[111]),
      "+f"(d[112]), "+f"(d[113]), "+f"(d[114]), "+f"(d[115]), "+f"(d[116]), "+f"(d[117]), "+f"(d[118]), "+f"(d[119]),
      "+f"(d[120]), "+f"(d[121]), "+f"(d[122]), "+f"(d[123]), "+f"(d[124]), "+f"(d[125]), "+f"(d[126]), "+f"(d[127])
    : "r"(a_lo), "r"(b_lo));
}
__device__ __forceinline__ void wgmma_ss_n128_p(float (&d)[64], uint32_t a_lo, uint32_t b_lo, uint32_t keep) {
  asm volatile(
    "{\n.reg .pred p;\nsetp.ne.b32 p, %66, 0;\n"
    "{\n.reg .b64 da, db;\nmov.b64 da, {%64, 8};\nmov.b64 db, {%65, 0x40000040};\n"
    "wgmma.mma_async.sync.aligned.m64n128k16.f32.bf16.bf16 "
    "{%0, %1, %2, %3, %4, %5, %6, %7, %8, %9, %10, %11, %12, %13, %14, %15, "
    "%16, %17, %18, %19, %20, %21, %22, %23, %24, %25, %26, %27, %28, %29, %30, %31, "
    "%32, %33, %34, %35, %36, %37, %38, %39, %40, %41, %42, %43, %44, %45, %46, %47, "
    "%48, %49, %50, %51, %52, %53, %54, %55, %56, %57, %58, %59, %60, %61, %62, %63}, "
    "da, db, p, 1, 1, 0, 1;\n}\n}\n"
    : "+f"(d[0]), "+f"(d[1]), "+f"(d[2]), "+f"(d[3]), "+f"(d[4]), "+f"(d[5]), "+f"(d[6]), "+f"(d[7]),
      "+f"(d[8]), "+f"(d[9]), "+f"(d[10]), "+f"(d[11]), "+f"(d[12]), "+f"(d[13]), "+f"(d[14]), "+f"(d[15]),
      "+f"(d[16]), "+f"(d[17]), "+f"(d[18]), "+f"(d[19]), "+f"(d[20]), "+f"(d[21]), "+f"(d[22]), "+f"(d[23]),
      "+f"(d[24]), "+f"(d[25]), "+f"(d[26]), "+f"(d[27]), "+f"(d[28]), "+f"(d[29]), "+f"(d[30]), "+f"(d[31]),
      "+f"(d[32]), "+f"(d[33]), "+f"(d[34]), "+f"(d[35]), "+f"(d[36]), "+f"(d[37]), "+f"(d[38]), "+f"(d[39]),
      "+f"(d[40]), "+f"(d[41]), "+f"(d[42]), "+f"(d[43]), "+f"(d[44]), "+f"(d[45]), "+f"(d[46]), "+f"(d[47]),
      "+f"(d[48]), "+f"(d[49]), "+f"(d[50]), "+f"(d[51]), "+f"(d[52]), "+f"(d[53]), "+f"(d[54]), "+f"(d[55]),
      "+f"(d[56]), "+f"(d[57]), "+f"(d[58]), "+f"(d[59]), "+f"(d[60]), "+f"(d[61]), "+f"(d[62]), "+f"(d[63])
    : "r"(a_lo), "r"(b_lo), "r"(keep));
}
__device__ __forceinline__ void wgmma_ss_n256_first(float (&d)[128], uint32_t a_lo, uint32_t b_lo) {
  asm volatile(
    "{\n.reg .b64 da, db;\nmov.b64 da, {%128, 8};\nmov.b64 db, {%129, 0x40000040};\n"
    "mov.b32 %0, 0; mov.b32 %1, 0; mov.b32 %2, 0; mov.b32 %3, 0; mov.b32 %4, 0; mov.b32 %5, 0; mov.b32 %6, 0; mov.b32 %7, 0;\n"
    "mov.b32 %8, 0; mov.b32 %9, 0; mov.b32 %10, 0; mov.b32 %11, 0; mov.b32 %12, 0; mov.b32 %13, 0; mov.b32 %14, 0; mov.b32 %15, 0;\n"
    "mov.b32 %16, 0; mov.b32 %17, 0; mov.b32 %18, 0; mov.b32 %19, 0; mov.b32 %20, 0; mov.b32 %21, 0; mov.b32 %22, 0; mov.b32 %23, 0;\n"
    "mov.b32 %24, 0; mov.b32 %25, 0; mov.b32 %26, 0; mov.b32 %27, 0; mov.b32 %28, 0; mov.b32 %29, 0; mov.b32 %30, 0; mov.b32 %31, 0;\n"
    "mov.b32 %32, 0; mov.b32 %33, 0; mov.b32 %34, 0; mov.b32 %35, 0; mov.b32 %36, 0; mov.b32 %37, 0; mov.b32 %38, 0; mov.b32 %39, 0;\n"
    "mov.b32 %40, 0; mov.b32 %41, 0; mov.b32 %42, 0; mov.b32 %43, 0; mov.b32 %44, 0; mov.b32 %45, 0; mov.b32 %46, 0; mov.b32 %47, 0;\n"
    "mov.b32 %48, 0; mov.b32 %49, 0; mov.b32 %50, 0; mov.b32 %51, 0; mov.b32 %52, 0; mov.b32 %53, 0; mov.b32 %54, 0; mov.b32 %55, 0;\n"
    "mov.b32 %56, 0; mov.b32 %57, 0; mov.b32 %58, 0; mov.b32 %59, 0; mov.b32 %60, 0; mov.b32 %61, 0; mov.b32 %62, 0; mov.b32 %63, 0;\n"
    "mov.b32 %64, 0; mov.b32 %65, 0; mov.b32 %66, 0; mov.b32 %67, 0; mov.b32 %68, 0; mov.b32 %69, 0; mov.b32 %70, 0; mov.b32 %71, 0;\n"
    "mov.b32 %72, 0; mov.b32 %73, 0; mov.b32 %74, 0; mov.b32 %75, 0; mov.b32 %76, 0; mov.b32 %77, 0; mov.b32 %78, 0; mov.b32 %79, 0;\n"
    "mov.b32 %80, 0; mov.b32 %81, 0; mov.b32 %82, 0; mov.b32 %83, 0; mov.b32 %84, 0; mov.b32 %85, 0; mov.b32 %86, 0; mov.b32 %87, 0;\n"
    "mov.b32 %88, 0; mov.b32 %89, 0; mov.b32 %90, 0; mov.b32 %91, 0; mov.b32 %92, 0; mov.b32 %93, 0; mov.b32 %94, 0; mov.b32 %95, 0;\n"
    "mov.b32 %96, 0; mov.b32 %97, 0; mov.b32 %98, 0; mov.b32 %99, 0; mov.b32 %100, 0; mov.b32 %101, 0; mov.b32 %102, 0; mov.b32 %103, 0;\n"
    "mov.b32 %104, 0; mov.b32 %105, 0; mov.b32 %106, 0; mov.b32 %107, 0; mov.b32 %108, 0; mov.b32 %109, 0; mov.b32 %110, 0; mov.b32 %111, 0;\n"
    "mov.b32 %112, 0; mov.b32 %113, 0; mov.b32 %114, 0; mov.b32 %115, 0; mov.b32 %116, 0; mov.b32 %117, 0; mov.b32 %118, 0; mov.b32 %119, 0;\n"
    "mov.b32 %120, 0; mov.b32 %121, 0; mov.b32 %122, 0; mov.b32 %123, 0; mov.b32 %124, 0; mov.b32 %125, 0; mov.b32 %126, 0; mov.b32 %127, 0;\n"
    "wgmma.mma_async.sync.aligned.m64n256k16.f32.bf16.bf16 "
    "{%0, %1, %2, %3, %4, %5, %6, %7, %8, %9, %10, %11, %12, %13, %14, %15, "
    "%16, %17, %18, %19, %20, %21, %22, %23, %24, %25, %26, %27, %28, %29, %30, %31, "
    "%32, %33, %34, %35, %36, %37, %38, %39, %40, %41, %42, %43, %44, %45, %46, %47, "
    "%48, %49, %50, %51, %52, %53, %54, %55, %56, %57, %58, %59, %60, %61, %62, %63, "
    "%64, %65, %66, %67, %68, %69, %70, %71, %72, %73, %74, %75, %76, %77, %78, %79, "
    "%80, %81, %82, %83, %84, %85, %86, %87, %88, %89, %90, %91, %92, %93, %94, %95, "
    "%96, %97, %98, %99, %100, %101, %102, %103, %104, %105, %106, %107, %108, %109, %110, %111, "
    "%112, %113, %114, %115, %116, %117, %118, %119, %120, %121, %122, %123, %124, %125, %126, %127}, "
    "da, db, 1, 1, 1, 0, 1;\n}\n"
    : "=f"(d[0]), "=f"(d[1]), "=f"(d[2]), "=f"(d[3]), "=f"(d[4]), "=f"(d[5]), "=f"(d[6]), "=f"(d[7]),
      "=f"(d[8]), "=f"(d[9]), "=f"(d[10]), "=f"(d[11]), "=f"(d[12]), "=f"(d[13]), "=f"(d[14]), "=f"(d[15]),
      "=f"(d[16]), "=f"(d[17]), "=f"(d[18]), "=f"(d[19]), "=f"(d[20]), "=f"(d[21]), "=f"(d[22]), "=f"(d[23]),
      "=f"(d[24]), "=f"(d[25]), "=f"(d[26]), "=f"(d[27]), "=f"(d[28]), "=f"(d[29]), "=f"(d[30]), "=f"(d[31]),
      "=f"(d[32]), "=f"(d[33]), "=f"(d[34]), "=f"(d[35]), "=f"(d[36]), "=f"(d[37]), "=f"(d[38]), "=f"(d[39]),
      "=f"(d[40]), "=f"(d[41]), "=f"(d[42]), "=f"(d[43]), "=f"(d[44]), "=f"(d[45]), "=f"(d[46]), "=f"(d[47]),
      "=f"(d[48]), "=f"(d[49]), "=f"(d[50]), "=f"(d[51]), "=f"(d[52]), "=f"(d[53]), "=f"(d[54]), "=f"(d[55]),
      "=f"(d[56]), "=f"(d[57]), "=f"(d[58]), "=f"(d[59]), "=f"(d[60]), "=f"(d[61]), "=f"(d[62]), "=f"(d[63]),
      "=f"(d[64]), "=f"(d[65]), "=f"(d[66]), "=f"(d[67]), "=f"(d[68]), "=f"(d[69]), "=f"(d[70]), "=f"(d[71]),
      "=f"(d[72]), "=f"(d[73]), "=f"(d[74]), "=f"(d[75]), "=f"(d[76]), "=f"(d[77]), "=f"(d[78]), "=f"(d[79]),
      "=f"(d[80]), "=f"(d[81]), "=f"(d[82]), "=f"(d[83]), "=f"(d[84]), "=f"(d[85]), "=f"(d[86]), "=f"(d[87]),
      "=f"(d[88]), "=f"(d[89]), "=f"(d[90]), "=f"(d[91]), "=f"(d[92]), "=f"(d[93]), "=f"(d[94]), "=f"(d[95]),
      "=f"(d[96]), "=f"(d[97]), "=f"(d[98]), "=f"(d[99]), "=f"(d[100]), "=f"(d[101]), "=f"(d[102]), "=f"(d[103]),
      "=f"(d[104]), "=f"(d[105]), "=f"(d[106]), "=f"(d[107]), "=f"(d[108]), "=f"(d[109]), "=f"(d[110]), "=f"(d[111]),
      "=f"(d[112]), "=f"(d[113]), "=f"(d[114]), "=f"(d[115]), "=f"(d[116]), "=f"(d[117]), "=f"(d[118]), "=f"(d[119]),
      "=f"(d[120]), "=f"(d[121]), "=f"(d[122]), "=f"(d[123]), "=f"(d[124]), "=f"(d[125]), "=f"(d[126]), "=f"(d[127])
    : "r"(a_lo), "r"(b_lo));
}

template <int N> struct Mma;
template <> struct Mma<128> {
  static __device__ __forceinline__ void ss(float (&d)[64], uint32_t a, uint32_t b) { wgmma_ss_n128(d, a, b); }
  static __device__ __forceinline__ void ss(float (&d)[64], uint32_t a, uint32_t b, uint32_t keep) { wgmma_ss_n128_p(d, a, b, keep); }
};
template <> struct Mma<192> {
  static __device__ __forceinline__ void ss(float (&d)[96], uint32_t a, uint32_t b) { wgmma_ss_n192(d, a, b); }
};
template <> struct Mma<256> {
  static __device__ __forceinline__ void ss(float (&d)[128], uint32_t a, uint32_t b) { wgmma_ss_n256(d, a, b); }
  static __device__ __forceinline__ void ss(float (&d)[128], uint32_t a, uint32_t b, uint32_t) { wgmma_ss_n256_first(d, a, b); }
};
template <int R> __device__ __forceinline__ void pin(float (&d)[R]) {
#pragma unroll
  for (int x = 0; x < R; x++) asm volatile("" : "+f"(d[x]));
}

__device__ __forceinline__ uint32_t ld_relaxed(const uint32_t* p) {
  uint32_t v; asm volatile("ld.relaxed.gpu.global.u32 %0, [%1];" : "=r"(v) : "l"(p) : "memory"); return v;
}
__device__ __forceinline__ void red_release(uint32_t* p) { asm volatile("red.release.gpu.global.add.u32 [%0], 1;" :: "l"(p) : "memory"); }
__device__ __forceinline__ uint32_t both_valid(uint32_t a, uint32_t b, uint32_t ep) {
  uint32_t r; asm("lop3.b32 %0, %1, %2, %3, 0x42;" : "=r"(r) : "r"(a), "r"(b), "r"(ep)); return r;
}
__device__ __forceinline__ uint32_t tagged(float v, uint32_t ep) { return (__float_as_uint(v) | 1u) ^ (ep & 1u); }
__device__ __forceinline__ void st_release(uint32_t* p, uint32_t v) { asm volatile("st.release.gpu.global.u32 [%0], %1;" :: "l"(p), "r"(v) : "memory"); }
__device__ __forceinline__ void stg32(void* p, uint32_t v) { asm volatile("st.global.u32 [%0], %1;" :: "l"(p), "r"(v) : "memory"); }
__device__ __forceinline__ float rsqrt_fast(float x) { float r; asm("rsqrt.approx.ftz.f32 %0, %1;" : "=f"(r) : "f"(x)); return r; }
__device__ __forceinline__ uint32_t gate_pair(uint32_t x, uint32_t y, uint32_t r, uint32_t nb) {
  uint32_t o;
  asm("{\n.reg .b16 l, h;\n.reg .b32 ll, hh, t;\nmov.b32 {l, h}, %3;\nmov.b32 ll, {l, l};\nmov.b32 hh, {h, h};\n"
      "fma.rn.bf16x2 t, %1, ll, %4;\nfma.rn.bf16x2 t, %1, hh, t;\nfma.rn.bf16x2 %0, t, %2, %1;\n}" : "=r"(o) : "r"(x), "r"(y), "r"(r), "r"(nb));
  return o;
}

constexpr int CV_KT_O = 4144;
constexpr int CV_KT_CH = 8336;
constexpr int CV_KH = 2064;
constexpr int CV_U_PLANE = 2240;
constexpr int CV_U_CH = 4496;
constexpr int CV_VQ = 8320, CV_Y_CH = 1040, CV_XROW = 2064;
constexpr int SM_BAR = 0;
constexpr int CV_K = 896;
constexpr int CV_X = CV_K + 128 + 32768;
constexpr int CV_ST0 = CV_X + 16 * CV_XROW;
constexpr int CV_KT = CV_ST0 + 8192;
constexpr int CV_QS = CV_KT + 8 * CV_KT_CH;
constexpr int CV_U = 142848;
constexpr int CV_V = CV_U + 8 * CV_U_CH;
constexpr int CV_ST1 = CV_V + 4 * CV_VQ;
constexpr int SM_ZERO = CV_ST1 + 8192, SM_ROLE = SM_ZERO + 4, SM_EPOCH = SM_ZERO + 8;
constexpr int CV_END = SM_ZERO + 16;
static_assert(CV_QS + 1024 <= CV_U && CV_X % 1024 == 0 && CV_V % 128 == 0, "layout");
constexpr int CV_BAR = SM_BAR + 8 * 84, BAR_REL = 25;
enum { CB_K0, CB_QA, CB_Q0, CB_Q1, CB_Q2, CB_Q3, CB_K1, CB_X0, CB_X1, CB_QC0, CB_QC1, CB_QS, CB_U1, CB_U2,
       CB_ST0, CB_ST1, CB_O1, CB_P1, CB_Y1, CB_Y2, CB_P2, CB_EARLY, CB_LATE, CB_YOUT, CB_STAT, CB_XFREE = CB_STAT + 2, CB_COUNT };
static_assert(CV_BAR + 8 * CB_COUNT <= CV_K, "layout");

__device__ __forceinline__ uint32_t lds32_nv(uint32_t addr) { uint32_t v; asm("ld.shared.u32 %0, [%1];" : "=r"(v) : "r"(addr)); return v; }
__device__ __forceinline__ void ldsm_x4_nv(uint32_t addr, uint32_t& r0, uint32_t& r1, uint32_t& r2, uint32_t& r3) {
  asm("ldmatrix.sync.aligned.m8n8.x4.shared.b16 {%0,%1,%2,%3}, [%4];" : "=r"(r0), "=r"(r1), "=r"(r2), "=r"(r3) : "r"(addr));
}
__device__ __forceinline__ void stsm_x4_t(uint32_t addr, uint32_t r0, uint32_t r1, uint32_t r2, uint32_t r3) {
  asm volatile("stmatrix.sync.aligned.m8n8.x4.trans.shared.b16 [%0], {%1,%2,%3,%4};" :: "r"(addr), "r"(r0), "r"(r1), "r"(r2), "r"(r3) : "memory");
}
__device__ __forceinline__ void bulk_load(uint32_t dst, const void* src, uint32_t bytes, uint32_t bar) {
  asm volatile("cp.async.bulk.shared::cluster.global.mbarrier::complete_tx::bytes [%0], [%1], %2, [%3];" :: "r"(dst), "l"(src), "r"(bytes), "r"(bar) : "memory");
}
__device__ __forceinline__ void mbar_wait_plain(uint32_t bar, uint32_t parity) {
#pragma unroll 1
  for (int spins = 0; spins < SPIN_LIMIT && !mbar_try(bar, parity); spins++) {}
}

__device__ __forceinline__ void shift_chunk(uint32_t src) {
  uint4 e;
  uint32_t nx;
  asm volatile("ld.shared.v4.u32 {%0,%1,%2,%3}, [%4];" : "=r"(e.x), "=r"(e.y), "=r"(e.z), "=r"(e.w) : "r"(src));
  asm volatile("ld.shared.u32 %0, [%1];" : "=r"(nx) : "r"(src + 16));
  sts128(src + CV_KT_O, make_uint4(__byte_perm(e.x, e.y, 0x5432), __byte_perm(e.y, e.z, 0x5432), __byte_perm(e.z, e.w, 0x5432), __byte_perm(e.w, nx, 0x5432)));
}
__device__ __forceinline__ void kv_block(uint32_t sm, int t0, const uint32_t (&wp)[4], int lane) {
  const int mi = lane >> 3, rev = 7 - (lane & 7);
  uint32_t vv[4], res[4];
  ldsm_x4(sm + CV_V + (t0 >> 9) * (CV_VQ - 8192) + (t0 + 8 * mi + rev) * 16, vv[0], vv[1], vv[2], vv[3]);
#pragma unroll
  for (int i = 0; i < 4; i++) {
    uint32_t k0, k1, k2, k3;
    ldsm_x4(sm + CV_K + (8 + t0 + 8 * i + rev - mi) * 16, k0, k1, k2, k3);
    res[i] = bmul2(badd2(badd2(badd2(bmul2(k3, wp[3]), bmul2(k2, wp[2])), bmul2(k1, wp[1])), bmul2(k0, wp[0])), vv[i]);
  }
  stsm_x4_t(sm + CV_U + (lane & 7) * CV_U_CH + (1 - (mi & 1)) * CV_U_PLANE + (8 + (t0 >> 4) + (mi >> 1)) * 16, res[0], res[1], res[2], res[3]);
}
template <int T0, int NT, int D0, int D1, int J0, int J1>
__device__ __forceinline__ void conv_phase(float (&acc)[16][4], uint32_t abase, uint32_t bbase, uint32_t zero) {
  abase += zero; bbase += zero;
#pragma unroll 1
  for (int dl = 0; dl < 8; dl++) {
    uint32_t bf[NT][2];
#pragma unroll
    for (int j = 0; j < NT; j += 2) ldsm_x4_nv(bbase + (T0 + j) * 128 - dl * 16, bf[j][0], bf[j][1], bf[j + 1][0], bf[j + 1][1]);
    const uint32_t ap = abase + dl * 32;
#pragma unroll
    for (int dh = D0; dh < D1; dh++) {
      const uint32_t a0 = lds32_nv(ap + dh * 256), a1 = lds32_nv(ap + dh * 256 - 16), a2 = lds32_nv(ap + dh * 256 + 16);
      const uint32_t a3 = a0 + zero;
#pragma unroll
      for (int j = 0; j < NT; j++)
        if (dh + T0 + j >= J0 && dh + T0 + j < J1) mma16816(acc[dh + T0 + j], a0, a1, a2, a3, bf[j][0], bf[j][1]);
    }
  }
}
__device__ __forceinline__ uint32_t hidden_zero(uint32_t addr) {
  uint32_t z; asm volatile("ld.volatile.shared.u32 %0, [%1];" : "=r"(z) : "r"(addr) : "memory"); return z;
}
template <int J0, int J1>
__device__ __forceinline__ void stage_y(const float (&acc)[16][4], uint32_t ys, uint32_t bar) {
#pragma unroll
  for (int j = J0; j < J1; j += 2)
    stsm_x4_t(ys + (j >> 2) * CV_VQ + (j & 3) * 128, pack_bf16(acc[j][0], acc[j][1]), pack_bf16(acc[j][2], acc[j][3]),
              pack_bf16(acc[j + 1][0], acc[j + 1][1]), pack_bf16(acc[j + 1][2], acc[j + 1][3]));
  if (J0) {
    __syncwarp();
    mbar_arrive_if(bar, (threadIdx.x & 31) == 0);
  }
}

#define KV_PROMO CU_TENSOR_MAP_L2_PROMOTION_L2_128B
#define STATS_EARLY 0
#define QC1_AT 2
#define QROW_AT 3
constexpr int CV_JS = 8;
enum { M_K, M_V, M_Q, M_W1C, M_W3C, M_X3S, M_X3B, M_H, M_HS, M_X1, M_HID, M_W1, M_W2, M_W3A, M_W3B, M_W4, M_OUT, M_Y, M_COUNT };
struct alignas(64) Params {
  const bf16 *q, *shift_k, *ssm_k, *ssm_d, *w2;
  CUtensorMap m[M_COUNT];
};
__device__ __forceinline__ void prefetch_line(const void* p) { asm volatile("prefetch.global.L2 [%0];" :: "l"(p) : "memory"); }

__device__ __forceinline__ uint32_t tpc_id() { uint32_t smid; asm volatile("mov.u32 %0, %%smid;" : "=r"(smid)); return smid >> 1; }
__device__ __forceinline__ uint32_t pick_role(uint32_t t, int lane) {
  uint32_t gpc = t < 32 ? t & 7 : t < 60 ? 1 + (t - 32) % 7 : t < 62 ? t - 54 : 0;
  const uint32_t d = ld_relaxed(g_clock + 8 + (lane >> 3)) - ld_relaxed(g_clock + (lane & 7)) + 4096;
  const uint32_t match = __ballot_sync(0xffffffffu, d < 8192) & 0x3e3e3e3eu;
  const uint32_t nine = (match | match >> 8 | match >> 16 | match >> 24) & 0xff;
  if (t >= 62) gpc = max(__ffs((match >> (8 * t - 496)) & 0xff) - 1, 0);
  const uint32_t below = (1u << gpc) - 1, pos = (nine >> gpc) & 1 ? __popc(nine & below) : __popc(nine) + __popc(~nine & below & 0xfe);
  uint32_t cls = gpc == 0 ? 0 : min(pos, 7 - pos);
  if (pos > 3 && cls < __popc(nine) && t < 8) cls = 0;
  uint32_t role = 0;
  if (lane == 0) {
#pragma unroll 1
    for (uint32_t k = 0; k < 4; k++) {
      const uint32_t p = (cls + k) & 3, ticket = atomicAdd(&g_role[p], 1u);
      if (ticket < 16) { role = ticket * 4 + p; break; }
    }
  }
  return role;
}

__device__ __forceinline__ void load_k(const Params& pr, uint32_t sm, int x) {
  const uint32_t bar = sm + CV_BAR + 8 * (x ? CB_K1 : CB_K0), bytes = x ? 4096 - CV_KH : CV_KH;
  mbar_expect_tx(bar, 8 * bytes);
#pragma unroll 1
  for (int ch = 0; ch < 8; ch++)
    bulk_load(sm + CV_KT + ch * CV_KT_CH + 32 + x * CV_KH, reinterpret_cast<const char*>(pr.ssm_k) + (blockIdx.x * 8 + ch) * 4096 + x * CV_KH, bytes, bar);
}
__device__ __forceinline__ void load_kv(const Params& pr, uint32_t sm, int y, int barrier) {
  tma_2d(sm + CV_K + 128 + y * 4096, &pr.m[M_K], sm + CV_BAR + 8 * barrier, blockIdx.x * 8, y * 256);
  tma_2d(sm + CV_V + (y >> 1) * CV_VQ + (y & 1) * 4096, &pr.m[M_V], sm + CV_BAR + 8 * barrier, blockIdx.x * 8, y * 256);
}

__device__ __forceinline__ void conv_part(const Params& pr, uint32_t sm, int warp) {
  const int tid = threadIdx.x, lane = tid & 31;
  const int b = blockIdx.x, d0 = b * 8;
  const uint32_t kt = sm + CV_KT, ub = sm + CV_U, bar = sm + CV_BAR;
  const int g = lane >> 2, qd = lane & 3, mi = lane >> 3;
  if (warp == 8) {
    asm volatile("bar.arrive 1, 384;" ::: "memory");
    const uint32_t ep = ld_relaxed(&g_epoch);
    if (elect_one()) {
      load_k(pr, sm, 1);
#pragma unroll 1
      for (int y = 2; y < 8; y++) {
        if (y == 2 * QROW_AT) {
          mbar_expect_tx(bar + 8 * CB_X0, 32768);
#pragma unroll 1
          for (int r = 0; r < 16; r++) bulk_load(sm + CV_X + r * CV_XROW, pr.q + (size_t)(b * 16 + r) * DM, 2048, bar + 8 * CB_X0);
        }
        if (!(y & 1)) mbar_expect_tx(bar + 8 * (CB_Q0 + (y >> 1)), 16384);
        load_kv(pr, sm, y, CB_Q0 + (y >> 1));
      }
#pragma unroll 1
      for (int x = M_Q; x < M_COUNT; x++) asm volatile("prefetch.tensormap [%0];" :: "l"(&pr.m[x]) : "memory");
    }
    __syncwarp();
    const uint32_t role = b & 1 ? 0 : pick_role(tpc_id(), lane);
    if (lane == 0) {
      sts32(sm + SM_EPOCH, ep);
      sts32(sm + SM_ROLE, role);
      asm volatile("fence.release.sync_restrict::shared::cta.cluster;" ::: "memory");
    }
    __syncwarp();
    asm volatile("barrier.cluster.arrive.relaxed.aligned;" ::: "memory");
    auto load_q = [&](int x) {
      mbar_wait_plain(bar + 8 * (CB_U1 + x), 0);
      fence_async_smem();
      if (elect_one()) {
        mbar_expect_tx(bar + 8 * (CB_QC0 + x), 16384);
#pragma unroll 1
        for (int y = 4 * x; y < 4 * x + 4; y++) tma_2d(sm + CV_K + 128 + y * 4096, &pr.m[M_Q], bar + 8 * (CB_QC0 + x), d0, y * 256);
      }
    };
    const int npieces = b < 112 ? 5 : 1;
    const int xr = (mi >> 1) * 8 + (lane & 7);
    const uint32_t xa = sm + CV_X + xr * 64 + (((mi & 1) ^ ((xr >> 1) & 3)) << 4);
    float cs[8][4] = {};
    auto q_stats = [&]() {
      mbar_wait_plain(bar + 8 * CB_QS, 0);
      float sum = 0.f, sq = 0.f;
#pragma unroll
      for (int x = 0; x < 8; x++) { const float2 v = lds_f2(sm + CV_QS + x * 128 + (lane & 15) * 8); sum += v.x; sq += v.y; }
      const float mean = sum * (1.f / DM), rs = rsqrt_fast(fmaxf(fmaf(-mean, mean, sq * (1.f / DM)), 0.f) + LN_EPS);
      const uint32_t rh = pack_bf16(0.f, rs);
      if (lane < 16)
        asm volatile("st.relaxed.gpu.global.v2.b32 [%0], {%1,%2};" :: "l"(g_qstat + b * 16 + lane), "r"(tagged(__uint_as_float(pack_bf16(rs - bf_hi(rh), bf_hi(rh))), ep)),
                     "r"(pack_bf16(-mean * rs, -mean * rs)) : "memory");
      if (lane == 0) { STAMP(47); asm volatile("red.relaxed.gpu.global.add.u32 [%0], 1;" :: "l"(&g_qcnt) : "memory"); }
    };
#pragma unroll 1
    for (int pc = -3; pc < npieces; pc++) {
      if (pc == -2) q_stats();
      if (pc >= 0) {
        mbar_wait_plain(bar + 8 * (CB_X0 + ((pc + 1) & 1)), ((pc + 1) >> 1) & 1);
#pragma unroll 1
        for (int r = 0; r < 16; r += 4) {
#pragma unroll
          for (int x = 0; x < 8; x++) {
            uint32_t a0, a1, a2, a3;
            ldsm_x4_t((xa ^ ((x & 1) << 5)) + ((pc + 1) & 1) * 16384 + (r + (x >> 1)) * 1024, a0, a1, a2, a3);
            mma16816(cs[x], a0, a1, a2, a3, 0x3f803f80u, 0x3f803f80u);
          }
        }
        if (pc == 0 || pc == 4) {
          float t = 0.f;
#pragma unroll
          for (int x = 0; x < 8; x += 2) {
            t += qd & 2 ? (qd & 1 ? cs[x + 1][2] : cs[x + 1][0]) : (qd & 1 ? cs[x][2] : cs[x][0]);
            cs[x][0] = cs[x][2] = cs[x + 1][0] = cs[x + 1][2] = 0.f;
          }
          (pc ? g_cs3 + 32 * b : g_cs1[b & 3] + 32 * (b >> 2))[8 * qd + g] = t;
        }
        __syncwarp();
      }
      if (pc > -3 && pc + 2 < npieces && elect_one()) {
        const uint32_t bx = bar + 8 * (CB_X0 + ((pc + 1) & 1));
        mbar_expect_tx(bx, 16384);
        tma_2d(sm + CV_X + ((pc + 1) & 1) * 16384, &pr.m[pc == -2 ? M_W1C : M_W3C], bx, 32 * (pc == -2 ? b >> 2 : b), 256 * (pc == -2 ? b & 3 : pc + 1));
      }
      if (pc == -3 || pc == min(QC1_AT, npieces - 1)) load_q(pc >= 0);
    }
#pragma unroll 1
    for (int x = 0; x < 4; x++) prefetch_line(reinterpret_cast<const char*>(pr.w2) + (b * 128 + x * 32 + lane) * 128);
    if (lane == 0) STAMP(52);
    return;
  }

  const uint32_t dpair = __ldg(reinterpret_cast<const uint32_t*>(pr.ssm_d + d0 + 2 * qd));
  const int wi = warp - (warp > 8), ti = 32 * wi + lane;
  {
    if (tid < 160) {
      const int x = tid - 128, y = x & 3;
      sts128(tid < 128 ? ub + (tid >> 4) * CV_U_CH + ((tid >> 3) & 1) * CV_U_PLANE + (tid & 7) * 16
                       : y == 3 ? sm + CV_K + (x >> 2) * 16 : kt + (x >> 2) * CV_KT_CH + (y == 2 ? 4128 : y * 16), make_uint4(0, 0, 0, 0));
    }
    uint32_t wp[4];
    {
      const uint4 a = ld_nc_u4(pr.shift_k + (d0 + 2 * qd) * 4);
      wp[0] = __byte_perm(a.x, a.z, 0x5410); wp[1] = __byte_perm(a.x, a.z, 0x7632);
      wp[2] = __byte_perm(a.y, a.w, 0x5410); wp[3] = __byte_perm(a.y, a.w, 0x7632);
    }
    const uint32_t kc = kt + (lane & 7) * CV_KT_CH;
    named_bar(1, 384);
#pragma unroll 1
    for (int x = 0; x < 2; x++) {
      mbar_wait_plain(bar + 8 * (x ? CB_K1 : CB_K0), 0);
#pragma unroll 1
      for (uint32_t a = kc + ((ti >> 3) + (x ? 130 - 32 : 0)) * 16; a < kc + (x ? 258 : 130) * 16; a += x ? 192 : 704) shift_chunk(a);
      __syncwarp();
      mbar_arrive_if(bar + 8 * CB_O1, x && lane == 0);
      if (tid == 0) BSTAMP(54, kt);
#pragma unroll 1
      for (int t0 = warp < 8 ? 32 * wi : 32 * wi + 256; t0 < (x ? SEQ : 512); t0 += x ? 96 : 256) {
        mbar_wait_plain(bar + 8 * (t0 < 256 ? CB_QA : CB_Q0 + (t0 >> 9)), 0);
        if (tid == 0) BSTAMP(56, kt);
        kv_block(sm, t0, wp, lane);
        constexpr int T1 = 128 * CV_JS + 32;
        __syncwarp();
        mbar_arrive_if(bar + 8 * (CB_U1 + (t0 >= T1)), t0 + 96 >= (t0 < T1 ? T1 : SEQ) && lane == 0);
      }
      if (x == 0) named_bar(4, 352);
      if (warp < 8) break;
    }
  }

  if (warp < 8) {
    const int o = 2 * qd - g;
    const uint32_t abase = kt + warp * CV_KT_CH + 32 + ((g & 1) ? CV_KT_O + (o - 1) * 2 : o * 2);
    const uint32_t bbase = ub + warp * CV_U_CH + (mi & 1) * CV_U_PLANE + (8 + (lane >> 4) * 8 + (lane & 7)) * 16;
    const uint32_t ys = sm + CV_V + warp * CV_Y_CH + (mi & 1) * 512 + ((lane >> 4) * 8 + (lane & 7)) * 16;
    auto q_sums = [&]() {
      mbar_wait_plain(bar + 8 * CB_X0, 0);
      float sum[4] = {0.f, 0.f, 0.f, 0.f}, lo[4] = {0.f, 0.f, 0.f, 0.f}, hi[4] = {0.f, 0.f, 0.f, 0.f};
#pragma unroll
      for (int x = 0; x < 8; x++) {
        uint32_t a0, a1, a2, a3;
        ldsm_x4(sm + CV_X + (lane & 15) * CV_XROW + warp * 256 + (lane >> 4) * 16 + x * 32, a0, a1, a2, a3);
        mma16816(sum, a0, a1, a2, a3, 0x3f803f80u, 0x3f803f80u);
        mma16816(lo, a0, a1, a2, a3, a0, a2);
        mma16816(hi, a0, a1, a2, a3, a1, a3);
      }
      if (qd == (g >> 1)) {
        asm volatile("st.shared.v2.f32 [%0], {%1,%2};" :: "r"(sm + CV_QS + warp * 128 + g * 8), "f"(sum[0]), "f"((g & 1) ? lo[1] : lo[0]) : "memory");
        asm volatile("st.shared.v2.f32 [%0], {%1,%2};" :: "r"(sm + CV_QS + warp * 128 + g * 8 + 64), "f"(sum[2]), "f"((g & 1) ? hi[3] : hi[2]) : "memory");
      }
      __syncwarp();
      mbar_arrive_if(bar + 8 * CB_QS, lane == 0);
    };
    if (tid == 0) STAMP(49);
    float acc[16][4];
#pragma unroll
    for (int j = 0; j < 16; j++) { acc[j][0] = acc[j][1] = acc[j][2] = acc[j][3] = 0.f; }
    conv_phase<0, 4, 0, 8, 0, 16>(acc, abase, bbase, hidden_zero(ub));
    stage_y<0, 4>(acc, ys, 0);
    if (tid == 0) STAMP(57);
    if (STATS_EARLY) q_sums();
    mbar_wait_plain(bar + 8 * CB_K1, 0);
    mbar_wait_plain(bar + 8 * CB_O1, 0);
    conv_phase<0, 4, 8, 16, 0, 16>(acc, abase, bbase, hidden_zero(ub));
    if (tid == 0) STAMP(58);
    if (!STATS_EARLY) q_sums();
    mbar_wait_plain(bar + 8 * CB_U1, 0);
    conv_phase<4, CV_JS - 4, 0, CV_JS - 4, 0, CV_JS>(acc, abase, bbase, hidden_zero(ub));
    stage_y<4, CV_JS>(acc, ys, bar + 8 * CB_Y1);
    if (tid == 0) STAMP(59);
    mbar_wait_plain(bar + 8 * CB_U2, 0);
    if (tid == 0) BSTAMP(55, kt);
    conv_phase<4, 12, 0, 12, CV_JS, 16>(acc, abase, bbase, hidden_zero(ub));
    stage_y<CV_JS, 16>(acc, ys, bar + 8 * CB_Y2);
    if (tid == 0) STAMP(50);
    if (tid == 32) STAMP(62);
  }
  {
    const int ch = lane & 7;
    const uint32_t ya = sm + CV_V + ch * CV_Y_CH + (mi & 1) * 512 + (mi >> 1) * 16;
    const uint32_t ua = ub + ch * CV_U_CH + (mi & 1) * CV_U_PLANE + (8 + (mi >> 1)) * 16;
    const uint32_t qa = sm + CV_K + 128 + (16 * (mi >> 1) + 15 - 8 * (mi & 1) - ch) * 16;
    char* xo = reinterpret_cast<char*>(g_x3[0]) + (size_t)b * CB_BYTES + (15 - g) * 16 + qd * 4;
    const uint32_t yo = sm + CV_K + 128 + ((7 - g) * 4 + qd) * 8;
    int budget = SPIN_LIMIT;
    uint32_t ep = 0;
    if (warp > 9) {
      if (tid == 320) STAMP(53);
      ep = ld_relaxed(&g_epoch);
#pragma unroll 1
      while (ld_relaxed(&g_qcnt) - 128 * ep < 128 && --budget > 0) __nanosleep(100);
      if (tid == 320) STAMP(43);
    }
#pragma unroll 1
    for (int part = warp < 8; part < 2; part++) {
      if (warp == 9 && part) break;
      if (warp > 9) {
        uint4 v[8];
#pragma unroll 1
        do {
          uint32_t ok = 1;
#pragma unroll
          for (int y = 0; y < 8; y++) {
            asm volatile("ld.relaxed.gpu.global.v4.u32 {%0,%1,%2,%3}, [%4];" : "=r"(v[y].x), "=r"(v[y].y), "=r"(v[y].z), "=r"(v[y].w)
                         : "l"(g_qstat + 1024 * part + 2 * (tid & 63) + 128 * y) : "memory");
            ok &= both_valid(v[y].x, v[y].z, ep);
          }
          if (__all_sync(0xffffffffu, ok)) break;
        } while (--budget > 0);
#pragma unroll
        for (int y = 0; y < 8; y++) sts128(sm + (part ? CV_ST1 : CV_ST0) + (tid & 63) * 16 + 1024 * y, make_uint4(v[y].x | 1u, v[y].y, v[y].z | 1u, v[y].w));
        __syncwarp();
        mbar_arrive_if(bar + 8 * (CB_ST0 + part), lane == 0);
      }
      mbar_wait_plain(bar + 8 * (CB_ST0 + part), 0);
      mbar_wait_plain(bar + 8 * (CB_QC0 + part), 0);
      if (tid == 288) STAMP(63);
      mbar_wait_plain(bar + 8 * (CB_Y1 + part), 0);
      const uint32_t sa = sm + (part ? CV_ST1 - 8192 : CV_ST0) + (15 - g) * 8;
#pragma unroll 1
      for (int u = part ? 4 * CV_JS + warp - 2 * (warp > 8) : warp - 9; u < (part ? 64 : 4 * CV_JS); u += part ? 10 : 3) {
        uint32_t y[4], uu[4], qq[4];
        ldsm_x4_t(ya + ((u >> 4) * (CV_VQ - 512) + u * 32), y[0], y[1], y[2], y[3]);
        ldsm_x4_t(ua + u * 32, uu[0], uu[1], uu[2], uu[3]);
        ldsm_x4(qa + u * 512, qq[0], qq[1], qq[2], qq[3]);
#pragma unroll
        for (int i = 0; i < 4; i++) {
          const int off = 16 * (i >> 1) - 8 * (i & 1);
          const float2 s = lds_f2(sa + (u * 256 + off * 8));
          y[i] = badd2(y[i], bmul2(uu[i], dpair));
          stg32(xo + (uint32_t)u * 512 + off * 16, gate_pair(qq[i], y[i], __float_as_uint(s.x), __float_as_uint(s.y)));
        }
        asm volatile("st.shared.v2.u32 [%0], {%1,%2};" :: "r"(yo + u * 512), "r"(y[1]), "r"(y[0]) : "memory");
        asm volatile("st.shared.v2.u32 [%0], {%1,%2};" :: "r"(yo + u * 512 + 256), "r"(y[3]), "r"(y[2]) : "memory");
      }
      __syncwarp();
      mbar_arrive_if(bar + 8 * (part ? CB_P2 : CB_P1), lane == 0);
    }
  }
  if (warp == 9) {
    mbar_wait_plain(bar + 8 * CB_P1, 0);
    if (elect_one()) {
      STAMP(61);
      red_release(&g_xcnt[b >> 3]);
      fence_async_smem();
      bulk_store(reinterpret_cast<char*>(g_y) + (size_t)b * CB_BYTES, sm + CV_K + 128, 16384);
      bulk_commit();
      bulk_wait_all();
      mbar_arrive(bar + 8 * CB_YOUT);
    }
  }
  if (tid == 0) STAMP(51);
}

constexpr int NA = 5, A_SLOT = 68 * 128;
constexpr int SM_B = 1024;
constexpr int SM_A = SM_B + 98304;
constexpr int SM_X = SM_A + 2 * NA * A_SLOT;
constexpr int SM_CS1 = CV_END;
constexpr int SM_CS3 = SM_CS1 + 512;
static_assert(SM_X % 1024 == 0 && SM_X + 32768 <= SM_CS1 && SM_B + 2 * 16384 == CV_X && SM_A + NA * A_SLOT == CV_U, "layout");
constexpr int BAR_FULLA = 0, BAR_FULLB = 16, BAR_TURN = 24, BAR_OWN = 26;
constexpr int BAR_EMPTYA = 28, BAR_EMPTYB = BAR_EMPTYA + 18, BAR_CS = BAR_EMPTYB + 9;
constexpr int BAR_PUB = 56;
constexpr int BAR_END = 84;
constexpr int SM_RS = SM_CS3 + 1792;
constexpr int MEGA_SMEM = SM_RS + 2 * 68 * 8;
static_assert(MEGA_SMEM <= 232448, "shared memory");
#define LEADS 0x444444
#define Y_AT 6
#define LEAD3 2

template <int N> struct BGeo;
template <> struct BGeo<128> { static constexpr int SLOTS = 6, BYTES = 16384; };
template <> struct BGeo<256> { static constexpr int SLOTS = 3, BYTES = 32768; };
template <> struct BGeo<192> { static constexpr int SLOTS = 4, BYTES = 24576; };
__host__ __device__ constexpr int first_slot(int s) { return s == 0 || s == 2 ? 2 : 0; }
__device__ __forceinline__ bool starts_local(int l, int s) { return s == 2 || s == 1 - l; }
__device__ __forceinline__ int token_shift(int j) { return ((j >> 1) & 1 ? 1 : -1) * (1 + (j >> 2)); }

struct Ctx {
  uint32_t sm;
  uint32_t bar;
  int i, j, r;
  int bid;
  uint32_t ep;
};

struct Pipe {
  uint32_t ko, kp;
  uint32_t po;
  uint32_t a0, a1, ar;
  uint32_t b;
  uint32_t keep;
  uint32_t sh, wide;
  uint32_t turn;
  int budget;
  uint32_t rel;
  bool signals;
  __device__ __forceinline__ void release() const {
    asm volatile("{\n.reg .pred p;\nsetp.ne.b32 p, %1, 0;\n@p mbarrier.arrive.shared::cluster.b64 _, [%0];\n}" :: "r"(rel + po), "r"((uint32_t)signals) : "memory");
  }
  __device__ __forceinline__ void drain() { wg_wait<0>(); release(); po = 64; }
};
__device__ __forceinline__ uint32_t desc_a(const Ctx& c, int off) { return ((c.sm & 0x3FFFFu) >> 4) + 0x400000u + (off >> 4); }
__device__ __forceinline__ uint32_t desc_b(const Ctx& c, int off) { return ((c.sm & 0x3FFFFu) >> 4) + 0x2000000u + ((SM_B + off) >> 4); }

template <int N, bool PRED, bool SHIFT = false, class Extra>
__device__ __forceinline__ void gemm_step(float (&acc)[N / 2], const Ctx& c, int wg, Pipe& p, Extra&& extra) {
  using G = BGeo<N>;
  const uint32_t fa = c.bar + 8 * BAR_FULLA + 64 * wg + p.ko, fb = c.bar + 8 * BAR_FULLB + p.ko;
#pragma unroll 1
  while (true) {
    uint32_t ready;
    asm volatile("{\n.reg .pred p, q;\nmbarrier.try_wait.parity.shared::cta.b64 p, [%1], %3;\nmbarrier.try_wait.parity.shared::cta.b64 q, [%2], %3;\n"
                 "and.pred p, p, q;\nselp.b32 %0, 1, 0, p;\n}" : "=r"(ready) : "r"(fa), "r"(fb), "r"(p.kp) : "memory");
    if (ready || --p.budget <= 0) break;
  }
  wg_fence();
  const uint32_t a = SHIFT ? p.a0 + (p.sh & 3) + (p.wide << 16) : p.a0, ak = SHIFT ? 128 + 2 * p.wide : 128;
  if constexpr (SHIFT) p.sh >>= 2;
  if constexpr (PRED) { Mma<N>::ss(acc, a, p.b, p.keep); p.keep = 1; } else Mma<N>::ss(acc, a, p.b);
#pragma unroll
  for (int kk = 1; kk < 4; kk++) Mma<N>::ss(acc, a + kk * ak, p.b + kk * 128);
  wg_commit();
  extra();
  wg_wait<1>();
  p.release();
  p.po = p.ko;
  p.ko = (p.ko + 8) & 63;
  p.kp ^= p.ko == 0;
  p.a0 = p.a1; p.a1 = p.ar;
  p.ar = p.ar == desc_a(c, SM_A + (NA - 1) * A_SLOT) + wg * NA * (A_SLOT >> 4) ? p.ar - (NA - 1) * (A_SLOT >> 4) : p.ar + (A_SLOT >> 4);
  p.b = p.b == desc_b(c, (G::SLOTS - 1) * G::BYTES) ? desc_b(c, 0) : p.b + (G::BYTES >> 4);
}
template <int N>
__device__ __forceinline__ void gemm_begin(const Ctx& c, int wg, int wq, Pipe& p, int s, bool local) {
  if (local) {
    fence_async_smem();
    named_bar(2 + wg, 128);
    mbar_arrive_if(c.bar + 8 * BAR_FULLA + 64 * wg + 8 * (threadIdx.x & 1), (threadIdx.x & 126) == 96);
    if (wq < 2) {
      mbar_wait(c.bar + 8 * (BAR_EMPTYA + 9 * wg + 8 - NA + wq), p.kp ^ 1, p.budget);
      if (elect_one()) {
        const uint32_t peer = mapa(c.sm, c.r ^ 1), bar = peer + SM_BAR + 8 * (BAR_FULLA + 8 * wg + 2 + wq);
        mbar_expect_tx_cluster(bar, 8192);
        bulk_copy_cluster(peer + (((wq ? p.a1 : p.a0) - desc_a(c, 0)) << 4), c.sm + SM_X + (2 * wg + wq) * 8192, 8192, bar);
      }
      __syncwarp();
    }
  }
  asm volatile("{\n.reg .pred p;\nsetp.ne.b32 p, %3, 0;\nselp.b32 %2, %0, %2, p;\nselp.b32 %0, %4, %0, p;\nselp.b32 %1, %5, %1, p;\n}"
               : "+r"(p.a0), "+r"(p.a1), "+r"(p.ar) : "r"((uint32_t)local), "r"(desc_a(c, SM_X) + wg * 1024), "r"(desc_a(c, SM_X + 8192) + wg * 1024));
  p.b = desc_b(c, first_slot(s) * BGeo<N>::BYTES);
}
template <class Hook>
__device__ __forceinline__ void yield_turn(const Ctx& c, int wg, Pipe& p, Hook&& hook) {
  if (wg == 1) p.drain();
  hook();
  if (wg == 1) mbar_wait(c.bar + 8 * BAR_TURN, p.turn, p.budget);
  p.turn ^= 1;
}
__device__ __forceinline__ void pass_turn(const Ctx& c, bool now) { mbar_arrive_if(c.bar + 8 * BAR_TURN, now && threadIdx.x == 96); }
struct Nop { __device__ __forceinline__ void operator()() const {} };
template <int N, bool PRED, bool SHIFT = false, class Hook, class Tail>
__device__ __forceinline__ void gemm_steps(float (&acc)[N / 2], const Ctx& c, int wg, Pipe& p, int count, int lead, Hook&& hook, Tail&& tail) {
#pragma unroll 1
  for (int n = count - lead; n > 0; n--) gemm_step<N, PRED, SHIFT>(acc, c, wg, p, Nop());
  yield_turn(c, wg, p, hook);
#pragma unroll 1
  for (int n = lead - 1; n >= 0; n--) {
    gemm_step<N, false, SHIFT>(acc, c, wg, p, Nop());
    pass_turn(c, n == 1);
  }
  tail();
  p.drain();
}

__device__ __forceinline__ void put_stat(float2* gdst, float s, float q, bool cond, uint32_t ep) {
  const float m = s * (1.f / 128), v = fmaxf(fmaf(-m, s, q), 0.f);
  asm volatile("{\n.reg .pred p;\nsetp.ne.b32 p, %3, 0;\n@p st.relaxed.gpu.global.v2.b32 [%0], {%1,%2};\n}"
               :: "l"(gdst), "r"(__float_as_uint(m)), "r"(tagged(v, ep)), "r"((uint32_t)cond) : "memory");
}
__device__ __forceinline__ void put_partial(const float (&v)[64], float2* gdst, uint32_t ep) {
  float s[4] = {v[0], v[1], v[2], v[3]}, q[4] = {v[0] * v[0], v[1] * v[1], v[2] * v[2], v[3] * v[3]};
#pragma unroll
  for (int x = 4; x < 64; x++) { s[x & 3] += v[x]; q[x & 3] = fmaf(v[x], v[x], q[x & 3]); }
  const bool odd = threadIdx.x & 1;
  const float s0 = s[0] + s[1], s1 = s[2] + s[3], q0 = q[0] + q[1], q1 = q[2] + q[3];
  float ss = (odd ? s1 : s0) + __shfl_xor_sync(0xffffffffu, odd ? s0 : s1, 1);
  float qq = (odd ? q1 : q0) + __shfl_xor_sync(0xffffffffu, odd ? q0 : q1, 1);
  ss += __shfl_xor_sync(0xffffffffu, ss, 2);
  qq += __shfl_xor_sync(0xffffffffu, qq, 2);
  put_stat(gdst + (odd ? 8 : 0), ss, qq, !(threadIdx.x & 2), ep);
}
struct RowStats {
  float2 p[4];
  __device__ __forceinline__ void load(const float2* r0, const float2* r1) {
#pragma unroll
    for (int x = 0; x < 4; x++)
      asm volatile("ld.relaxed.gpu.global.v2.f32 {%0,%1}, [%2];" : "=f"(p[x].x), "=f"(p[x].y) : "l"((x & 2 ? r1 : r0) + (x & 1) * SEQ) : "memory");
  }
  __device__ __forceinline__ void finish(const float2* r0, const float2* r1, int& budget, float2& s0, float2& s1) {
#pragma unroll 1
    while (!__all_sync(0xffffffffu, both_valid(__float_as_uint(p[0].y), __float_as_uint(p[1].y), 0) & both_valid(__float_as_uint(p[2].y), __float_as_uint(p[3].y), 0) & 1)) {
      if (--budget <= 0) break;
      load(r0, r1);
    }
#pragma unroll
    for (int h = 0; h < 2; h++) {
      const float2 a = p[2 * h], b = p[2 * h + 1];
      float m = a.x + b.x;
      m += __shfl_xor_sync(0xffffffffu, m, 1);
      m += __shfl_xor_sync(0xffffffffu, m, 2);
      m *= 0.125f;
      const float ea = a.x - m, eb = b.x - m;
      float t = fmaf(fmaf(ea, ea, eb * eb), 128.f, a.y + b.y);
      t += __shfl_xor_sync(0xffffffffu, t, 1);
      t += __shfl_xor_sync(0xffffffffu, t, 2);
      (h ? s1 : s0) = make_float2(m, rsqrt_fast(fmaf(t, 1.f / DM, LN_EPS)));
    }
  }
};

__device__ __forceinline__ void emit_panel(const uint32_t* v, char* gp, uint32_t pub) {
#pragma unroll
  for (int t = 0; t < 8; t++) { stg32(gp + t * CB_BYTES, v[2 * t]); stg32(gp + t * CB_BYTES + 128, v[2 * t + 1]); }
  __syncwarp();
  mbar_arrive_if(pub, (threadIdx.x & 31) == 0);
}
template <int NT>
__device__ __forceinline__ void stage_tiles(const uint32_t* v, uint32_t sp) {
#pragma unroll
  for (int t = 0; t < NT; t += 2) stsm_x4(sp + t * 1024, v[2 * t], v[2 * t + 1], v[2 * t + 2], v[2 * t + 3]);
}

__device__ __forceinline__ float late_zero(uint32_t addr) {
  float z; asm volatile("ld.volatile.shared.f32 %0, [%1];" : "=f"(z) : "r"(addr) : "memory"); return z;
}

template <int NT>
__device__ __forceinline__ void fold_tiles(uint32_t* v, const float* acc, const float2* cs_ptr, float2 st0, float2 st1) {
  const float n0 = -st0.x * st0.y, n1 = -st1.x * st1.y;
#pragma unroll
  for (int tile = 0; tile < NT; tile++) {
    const float2 cs = cs_ptr[tile * 4];
    float a = fmaf(acc[4 * tile + 0], st0.y, n0 * cs.x), b = fmaf(acc[4 * tile + 1], st0.y, n0 * cs.y);
    float cc = fmaf(acc[4 * tile + 2], st1.y, n1 * cs.x), d = fmaf(acc[4 * tile + 3], st1.y, n1 * cs.y);
    v[2 * tile] = pack_bf16(gelu_from_half(a), gelu_from_half(b));
    v[2 * tile + 1] = pack_bf16(gelu_from_half(cc), gelu_from_half(d));
  }
}

__device__ __forceinline__ void move_reg(uint32_t& d, uint32_t s) { asm volatile("mov.b32 %0, %1;" : "=r"(d) : "r"(s)); }
__device__ __forceinline__ void move_reg(float& d, float s) { asm volatile("mov.f32 %0, %1;" : "=f"(d) : "f"(s)); }
template <int CH, int LO, int HI, class T, int NR>
__device__ __forceinline__ void pick_group(T (&held)[NR], int idx) {
  if constexpr (HI - LO == 1) {
#pragma unroll
    for (int x = 0; x < CH; x++) move_reg(held[x], held[CH * LO + x]);
  } else {
    constexpr int MID = (LO + HI) / 2;
    if (idx < MID) pick_group<CH, LO, MID>(held, idx); else pick_group<CH, MID, HI>(held, idx);
  }
}
template <int CH>
__device__ __forceinline__ void gelu_chunk(const uint32_t* t, char* gp) {
#pragma unroll
  for (int x = 0; x < CH; x++) stg32(gp + (x >> 1) * CB_BYTES + (x & 1) * 128, gelu_pair_f16(t[x]));
}

#define REG_CONS 216
#define REG_PROD 72
__global__ void __cluster_dims__(2, 1, 1) __launch_bounds__(384, 1)
fused_kernel(const __grid_constant__ Params maps) {
  extern __shared__ __align__(1024) char smem[];
  const int tid = threadIdx.x, lane = tid & 31;
  const int warp = __shfl_sync(0xffffffffu, tid >> 5, 0), wg = warp >> 2;
  if (tid == 0) STAMP(48);
  const uint32_t sm0 = opaque(smem_u32(smem));
  if (elect_one()) {
    if (warp == 8) {
#pragma unroll
      for (int x = 0; x < CB_Q1; x++) mbar_init(sm0 + CV_BAR + 8 * x, 1);
      asm volatile("fence.mbarrier_init.release.cluster;" ::: "memory");
      load_k(maps, sm0, 0);
#pragma unroll
      for (int y = 0; y < 2; y++) {
        mbar_expect_tx(sm0 + CV_BAR + 8 * (CB_QA + y), 8192);
        load_kv(maps, sm0, y, CB_QA + y);
      }
#pragma unroll
      for (int x = CB_Q1; x < CB_ST0; x++) mbar_init(sm0 + CV_BAR + 8 * x, x < CB_QS ? 1 : x == CB_QS ? 8 : 3);
    } else if (warp == 9) {
#pragma unroll
      for (int x = CB_ST0; x < CB_COUNT; x++) mbar_init(sm0 + CV_BAR + 8 * x, x < CB_O1 ? 2 : x < CB_Y1 ? 3 : x < CB_P2 ? 8 : x == CB_P2 ? 10 : x == CB_YOUT ? 5 : x < CB_STAT ? 2 : 1);
    } else if (warp < 2) {
      asm volatile("prefetch.tensormap [%0];" :: "l"(&maps.m[M_K + warp]) : "memory");
    }
#pragma unroll
    for (int x = 0; x < 7; x++) mbar_init(sm0 + SM_BAR + 56 * warp + 8 * x, 1 << wg);
    asm volatile("fence.mbarrier_init.release.cluster;" ::: "memory");
    if (warp == 11) {
      sts32(sm0 + SM_ZERO, 0);
      const uint32_t t = tpc_id();
      if (t < 8 || (t >= 62 && t < 66)) asm volatile("{\n.reg .b32 c;\nmov.u32 c, %%clock;\nst.relaxed.gpu.global.u32 [%0], c;\n}" :: "l"(g_clock + (t < 8 ? t : t - 54)) : "memory");
    }
  }
  static_assert(BAR_END == 84, "start-up work of 12 warps");
  __syncwarp();
  if (warp != 8) asm volatile("barrier.cluster.arrive.relaxed.aligned;" ::: "memory");
  conv_part(maps, sm0, warp);
  __syncwarp();
  asm volatile("barrier.cluster.wait.acquire.aligned;" ::: "memory");
  Ctx c;
  c.sm = sm0;
  c.bar = c.sm + SM_BAR;
  c.r = blockIdx.x & 1;
  {
    uint32_t role;
    asm volatile("ld.shared::cluster.u32 %0, [%1];" : "=r"(role) : "r"(mapa(sm0 + SM_ROLE, 0)) : "memory");
    role = __shfl_sync(0xffffffffu, role, 0);
    c.i = role >> 2; c.j = (role & 3) * 2 + c.r;
    c.bid = c.i * 8 + c.j;
    asm volatile("ld.shared.u32 %0, [%1];" : "=r"(c.ep) : "r"(c.sm + SM_EPOCH) : "memory");
  }

  if (tid == 0) MSTAMP(45);
  if (wg == 2) {
    reg_dealloc<REG_PROD>();
    int budget = SPIN_LIMIT;
    if (warp == 8) {
      const int hh = 16 * c.r + c.i;
      const uint32_t full0 = c.bar + 8 * (BAR_FULLA + c.r * 8), empty0 = c.bar + 8 * (BAR_EMPTYA + c.r * 9), full_peer = mapa(full0, c.r ^ 1);
      const uint32_t ring0 = c.sm + SM_A + c.r * NA * A_SLOT;
      const int nb = hh + (lane & 8 ? (lane & 2) - 1 : 0);
      const uint32_t* lf = g_flag + ((nb >= 0 && nb < 32 ? nb : hh) * 8 + (lane & 7)) * FS;
      const uint32_t* xf = g_xcnt + (hh + ((c.j >> 1) & 1) >= 16 ? 16 : 0) + (lane & 15);
      const uint32_t cb = c.sm + CV_BAR;
      if (lane == 0) mbar_arrive(cb + 8 * CB_XFREE);
      mbar_wait(cb + 8 * CB_Y2, 0, budget);
      if (lane == 0) STAMP(60);
      mbar_wait(cb + 8 * CB_P1, 0, budget);
      fence_async_smem();
      if (lane < 2) mbar_arrive_cluster(mapa(cb + 8 * CB_EARLY, lane));
      int seen = ld_relaxed(xf) - 8 * c.ep;
      mbar_wait(cb + 8 * (CB_EARLY + c.r), 0, budget);
      fence_async_global();
      if (lane == 0) MSTAMP(46);
      uint32_t slot = ring0;
      int k = 0;
#pragma unroll 1
      for (int ph = 0; ph < 10; ph++) {
        const int l = ph >= 5, s = ph - 5 * l;
        const CUtensorMap* m = &maps.m[s == 0 ? M_X3S + l : s == 1 ? M_H + l : s == 4 ? M_HID : M_X1];
        const uint32_t bytes = s == l ? A_SLOT : 8192;
        const bool local = starts_local(l, s);
        const int np = ph == 0 ? 1 : s == 4 ? 7 : 2, cnt = ph == 0 ? 16 : local ? 6 : 8, e0 = ph == 0 ? 2 * (c.j & 6) : (c.j & 6) + (local ? 2 : 0);
        const int need0 = ph == 0 ? 8 : 13 * l + (s == 0 ? 1 : s == 1 ? 3 : s == 4 ? 7 : 5);
        const uint32_t up = ph == 0 ? (c.j & 2 ? 0u : 0xffffu) : ph == 6 ? 0x33u : 0u;
        const uint32_t* fp = ph == 0 ? xf : lf;
        const uint32_t base = ph == 0 ? 8 * c.ep : 32 * c.ep;
        const bool polls = lane < (s == l ? 16 : 8);
        if (ph == 1) seen = 0;
        if (local) {
          k += 4;
          slot += slot >= ring0 + (NA - 2) * A_SLOT ? (2 - NA) * A_SLOT : 2 * A_SLOT;
        }
#pragma unroll 1
        for (int p = 0; p < np; p++) {
          uint32_t ready = __ballot_sync(0xffffffffu, seen >= need0 + p);
          if (ph == 6) ready &= ready >> 8;
#pragma unroll 1
          for (int x = 0; x < cnt; x++) {
            const int e = (e0 + x) & (ph == 0 ? 15 : 7);
            const uint32_t off = 8 * (k & 7);
            mbar_wait(empty0 + 8 * ((k - NA) & 7), ((k - NA) >> 3) & 1, budget);
            if (elect_one()) {
              mbar_expect_tx(full0 + off, bytes);
              mbar_expect_tx_cluster(full_peer + off, bytes);
            }
            if (!((ready >> e) & 1)) {
#pragma unroll 1
              do {
                if (polls) seen = ld_relaxed(fp) - base;
                ready = __ballot_sync(0xffffffffu, seen >= need0 + p);
                if (ph == 6) ready &= ready >> 8;
              } while (!((ready >> e) & 1) && --budget > 0);
              fence_async_global();
            }
            if (elect_one()) tma_2d_mc(slot, m, full0 + off, 128 * hh - 8 * ((up >> e) & 1), (np * e + p) * 8, (uint16_t)3);
            slot += slot == ring0 + (NA - 1) * A_SLOT ? (1 - NA) * A_SLOT : A_SLOT;
            k++;
          }
        }
      }
    } else if (warp == 9) {
      const uint32_t e8 = __funnelshift_r(0x76543210u, 0x76543210u, 4 * (c.j & 6));
      int k = 0;
#pragma unroll 1
      for (int ph = 0; ph < 10; ph++) {
        const int l = ph >= 5, s = ph - 5 * l;
        const uint32_t bytes = s == 2 ? 32768 : s == 3 ? 24576 : 16384, slots = s == 2 ? 3 : s == 3 ? 4 : 6;
        uint32_t dist = s == 2 ? 0x33333345u : s == 3 ? 0x44444333u : s == 4 ? 0x66655544u : 0x66666666u;
        const CUtensorMap* m = &maps.m[M_W1 + s];
        const int np = s == 4 ? 7 : 2;
        const int panel0 = s == 2 ? 7 * c.j : s == 3 ? 7 * c.j + 4 : 2 * c.j;
        const bool local = starts_local(l, s), direct = local || ph == 0;
        uint32_t slot = c.sm + SM_B + first_slot(s) * bytes;
#pragma unroll 1
        for (int o = 0; o < np; o++) {
          uint32_t tab = e8;
          if (local) tab = o ? (e8 >> 24 << 1) | ((e8 << 1) & 0xffffff00u) | 0x11111100u : (0x3210u ^ (c.j * 0x2222u)) | (e8 >> 8 << 17);
          if (ph == 0) tab = (c.j & 2 ? 0xba987654u : 0x76543210u) ^ (((c.j >> 2) ^ o) * 0x88888888u);
          const int mul = direct ? 64 : 64 * np, add = direct ? 0 : 64 * o;
#pragma unroll 1
          for (uint32_t bar = c.bar + 8 * BAR_FULLB; bar < c.bar + 8 * BAR_FULLB + 64; bar += 8) {
            const int last = k - (dist & 15), row = (tab & 15) * mul + add;
            if (last < 0) {
              mbar_wait(c.sm + CV_BAR + 8 * (k < 2 ? CB_XFREE : k < 5 ? CB_EARLY : CB_YOUT), 0, budget);
              fence_async_smem();
            }
            mbar_wait(c.bar + 8 * (BAR_EMPTYB + (last & 7)), (last >> 3) & 1, budget);
            if (elect_one()) {
              mbar_expect_tx(bar, bytes);
              tma_3d(slot, m, bar, 0, row, panel0);
            }
            slot += bytes;
            if (slot == c.sm + SM_B + 98304) slot = c.sm + SM_B;
            dist = __funnelshift_r(dist, slots, 4);
            tab >>= 4;
            k++;
          }
        }
      }
    } else {
      const int w = warp - 10;
      const int row0 = 64 * (16 * w + c.i);
      mbar_wait(c.sm + CV_BAR + 8 * CB_P2, 0, budget);
      if (w == 0) {
        fence_async_smem();
        if (lane < 2) mbar_arrive_cluster(mapa(c.sm + CV_BAR + 8 * CB_LATE, lane));
      } else if (elect_one()) {
        red_release(&g_xcnt[16 + (blockIdx.x >> 3)]);
        mbar_arrive(c.bar + 8 * BAR_REL);
        MSTAMP(44);
      }
      __syncwarp();
      uint32_t* my_flag = g_flag + ((16 * w + c.i) * 8 + c.j) * FS;
#pragma unroll 1
      for (int pc = 1; pc < 26; pc++) {
        const int l = pc >= 13, u = pc - 13 * l;
        if (pc > 1) {
          if (pc == 8) { reinterpret_cast<uint4*>(&g_part[2][c.j][row0])[lane] = make_uint4(0, 0, 0, 0); __syncwarp(); }
          mbar_wait(c.bar + 8 * (BAR_PUB + 13 * w + u), u < 2 ? 0 : l, budget);
          st_release(my_flag, 32 * c.ep + pc + 1);
        }
        float2* part = &g_part[3 * l + (u == 5)][0][0];
#pragma unroll 1
        for (uint32_t jobs = pc == 1 ? 0x453u : u == 5 ? 0x421u : u == 1 ? 4u : 0u; jobs; jobs >>= 4) {
          const int job = jobs & 15;
          if (job < 3) {
            const int r = 32 * (job - 1) + lane;
            float s0 = 0.f, s1 = 0.f, q0 = 0.f, q1 = 0.f;
#pragma unroll 2
            for (int x = 0; x < 16; x++) {
              uint32_t v[4];
              asm volatile("ld.shared.v4.u32 {%0,%1,%2,%3}, [%4];" : "=r"(v[0]), "=r"(v[1]), "=r"(v[2]), "=r"(v[3])
                           : "r"(c.sm + SM_X + w * 16384 + x * 1024 + r * 16) : "memory");
#pragma unroll
              for (int y = 0; y < 4; y++) {
                const float a = bf_lo(v[y]), b = bf_hi(v[y]);
                s0 += a; s1 += b; q0 = fmaf(a, a, q0); q1 = fmaf(b, b, q1);
              }
            }
            put_stat(part + c.j * SEQ + row0 + r, s0 + s1, q0 + q1, true, c.ep);
          } else if (job == 3) {
            if (w == 1) {
              mbar_wait(c.sm + CV_BAR + 8 * CB_YOUT, 0, budget);
              mbar_wait(c.sm + CV_BAR + 8 * CB_EARLY, 0, budget);
              if (lane == 0) red_release(&g_xcnt[32 + (blockIdx.x >> 3)]);
              __syncwarp();
            }
            uint32_t xseen;
#pragma unroll 1
            do {
              asm volatile("ld.acquire.gpu.global.u32 %0, [%1];" : "=r"(xseen) : "l"(g_xcnt + 32 + (lane & 15)) : "memory");
            } while (!__all_sync(0xffffffffu, (int)(xseen - 8 * c.ep) >= 8) && --budget > 0);
            if (w == 0) {
              float4 s = make_float4(0.f, 0.f, 0.f, 0.f);
#pragma unroll
              for (int x = 0; x < 4; x++) {
                const float4 v = __ldcg(reinterpret_cast<const float4*>(&g_cs1[x][c.j * 128]) + lane);
                s.x += v.x; s.y += v.y; s.z += v.z; s.w += v.w;
              }
              reinterpret_cast<float4*>(smem + SM_CS1)[lane] = s;
            } else {
#pragma unroll
              for (int x = 0; x < 4; x++) {
                const int y = min(32 * x + lane, 111);
                const float4 v = __ldcg(reinterpret_cast<const float4*>(g_cs3 + c.j * 448) + y);
                if (x < 2) {
                  uint32_t* d = reinterpret_cast<uint32_t*>(smem + SM_CS3) + (y >> 2) * 8 + (y & 1) * 4 + ((y >> 1) & 1);
                  d[0] = pack_f16(v.x, v.y); d[2] = pack_f16(v.z, v.w);
                } else {
                  reinterpret_cast<float4*>(smem + SM_CS3)[y] = v;
                }
              }
            }
            __syncwarp();
            if (lane == 0) {
              mbar_arrive(c.bar + 8 * BAR_CS);
              if (c.bid == 0 && w == 0) { g_epoch = c.ep + 1; *reinterpret_cast<uint4*>(g_role) = make_uint4(0, 0, 0, 0); }
            }
          } else {
            const int r = job == 4 ? 2 * lane : token_shift(c.j) > 0 ? 64 : -2;
            const float2* src = part + min(max(row0 + r, 0), SEQ - 2);
            float4 v[8];
#pragma unroll 1
            do {
              uint32_t ok = 1;
#pragma unroll
              for (int x = 0; x < 8; x++) {
                asm volatile("ld.relaxed.gpu.global.v4.f32 {%0,%1,%2,%3}, [%4];" : "=f"(v[x].x), "=f"(v[x].y), "=f"(v[x].z), "=f"(v[x].w) : "l"(src + x * SEQ) : "memory");
                ok &= both_valid(__float_as_uint(v[x].y), __float_as_uint(v[x].w), c.ep);
              }
              if (__all_sync(0xffffffffu, ok)) break;
            } while (--budget > 0);
            float ma = 0.f, mb = 0.f, ta = 0.f, tb = 0.f;
#pragma unroll
            for (int x = 0; x < 8; x++) { ma += v[x].x; mb += v[x].z; }
            ma *= 0.125f; mb *= 0.125f;
#pragma unroll
            for (int x = 0; x < 8; x++) {
              const float ea = v[x].x - ma, eb = v[x].z - mb;
              ta += fmaf(128.f * ea, ea, __uint_as_float(__float_as_uint(v[x].y) | 1u));
              tb += fmaf(128.f * eb, eb, __uint_as_float(__float_as_uint(v[x].w) | 1u));
            }
            *reinterpret_cast<float4*>(smem + SM_RS + (68 * w + 2 + r) * 8) =
                make_float4(ma, rsqrt_fast(fmaf(ta, 1.f / DM, LN_EPS)), mb, rsqrt_fast(fmaf(tb, 1.f / DM, LN_EPS)));
            __syncwarp();
            if (job == 4 && lane == 0) mbar_arrive(c.sm + CV_BAR + 8 * (CB_STAT + w));
          }
        }
        if (pc == Y_AT) {
          if (elect_one()) {
            const uint32_t bar = c.bar + 8 * (BAR_OWN + w);
            fence_async_global();
            fence_async_smem();
            mbar_expect_tx(bar, 16384);
            tma_2d(c.sm + SM_X + w * 16384, &maps.m[M_Y], bar, 2 * row0, 16 * c.j);
            tma_2d(c.sm + SM_X + w * 16384 + 8192, &maps.m[M_Y], bar, 2 * row0, 16 * c.j + 8);
          }
          __syncwarp();
        }
      }
    }
    cluster_exit_barrier();
  } else {
    reg_alloc<REG_CONS>();
#define WSTAMP(idx) do {} while (0)
    const int t = tid & 127, g = lane >> 2, qd = lane & 3;
    const int wrow = 64 * (16 * wg + c.i) + (t >> 5) * 16, row = wrow + g;
    const uint32_t frag = row * 16 + qd * 4 + c.j * 16 * CB_BYTES;
    const uint32_t stage = c.sm + SM_X + wg * 16384 + (lane >> 4) * 1024 + ((t >> 5) * 16 + (lane & 15)) * 16;
    const uint32_t pub = c.bar + 8 * (BAR_PUB + 13 * wg);
    const uint32_t rstat = c.sm + SM_RS + (68 * wg + 2 + (t >> 5) * 16 + g) * 8;
    Pipe p;
    p.ko = 0; p.kp = 0; p.po = 64; p.turn = 0; p.budget = SPIN_LIMIT;
    p.a0 = desc_a(c, SM_A) + wg * NA * (A_SLOT >> 4); p.a1 = p.a0 + (A_SLOT >> 4); p.ar = p.a1 + (A_SLOT >> 4);
    p.signals = t == 0 || t == 32 || t == 64;
    p.rel = mapa(c.bar + 8 * (t == 64 ? BAR_EMPTYB : BAR_EMPTYA + wg * 9), t == 32 ? c.r ^ 1 : c.r);
    auto fence_sched = [&]() { mbar_wait(c.bar + 8 * BAR_CS, 0, p.budget); };
    uint32_t x3[32];
    float acc[64];
#pragma unroll
    for (int x = 0; x < 64; x++) acc[x] = 0.f;
    WSTAMP(0);
    if (wg == 1) {
      mbar_wait(c.bar + 8 * BAR_REL, 0, p.budget);
#pragma unroll 2
      for (int x = 0; x < 8; x++)
        reinterpret_cast<uint4*>(g_y)[blockIdx.x * 2048 + 1024 + x * 128 + t] = reinterpret_cast<const uint4*>(smem + CV_K + 128 + 16384)[x * 128 + t];
      __syncwarp();
      mbar_arrive_if(c.sm + CV_BAR + 8 * CB_YOUT, lane == 0);
    }
    {
      mbar_wait(c.bar + 8 * (BAR_FULLA + 8 * wg + 2 * c.r), 0, p.budget);
      mbar_wait(c.bar + 8 * (BAR_FULLA + 8 * wg + 2 * c.r + 1), 0, p.budget);
      const uint32_t own = c.sm + SM_A + (wg * NA + 2 * c.r) * A_SLOT + (lane >> 4) * 1088 + ((token_shift(c.j) < 0 ? 4 : 0) + (t >> 5) * 16 + (lane & 15)) * 16;
#pragma unroll
      for (int x = 0; x < 32; x += 4) ldsm_x4(own + x * 544, x3[x], x3[x + 1], x3[x + 2], x3[x + 3]);
    }
#pragma unroll 1
    for (int ph = 0; ph < 6; ph++) {
      const int l = ph >= 3, s = ph - 3 * l;
      if (s < 2) {
        gemm_begin<128>(c, wg, warp & 3, p, s, s != l);
        p.keep = s;
        if (s == 0) {
          float sum[4] = {0.f, 0.f, 0.f, 0.f}, lo[4] = {0.f, 0.f, 0.f, 0.f}, hi[4] = {0.f, 0.f, 0.f, 0.f};
#pragma unroll
          for (int x = 0; x < 32; x += 4) {
            mma16816(sum, x3[x], x3[x + 1], x3[x + 2], x3[x + 3], 0x3f803f80u, 0x3f803f80u);
            mma16816(lo, x3[x], x3[x + 1], x3[x + 2], x3[x + 3], x3[x], x3[x + 2]);
            mma16816(hi, x3[x], x3[x + 1], x3[x + 2], x3[x + 3], x3[x + 1], x3[x + 3]);
          }
          put_stat(&g_part[3 * l][c.j][row], sum[0], (g & 1) ? lo[1] : lo[0], qd == (g >> 1), c.ep);
          put_stat(&g_part[3 * l][c.j][row + 8], sum[2], (g & 1) ? hi[3] : hi[2], qd == (g >> 1), c.ep);
          WSTAMP(1 + 16 * l);
        }
      } else {
        char* hp = reinterpret_cast<char*>(g_hid) + frag + c.j * 40 * CB_BYTES;
        uint32_t held[64];
        float acc3[128];
        gemm_step<256, true>(acc3, c, wg, p, Nop());
        float2 s0 = make_float2(0.f, 0.f), s1 = s0;
        gemm_steps<256, false>(acc3, c, wg, p, 15, LEAD3, [&]() {
          mbar_wait(c.sm + CV_BAR + 8 * (CB_STAT + wg), 1, p.budget);
          s0 = lds_f2(rstat); s1 = lds_f2(rstat + 64);
          s0.y *= 0.5f; s1.y *= 0.5f;
        }, Nop());
        WSTAMP(6 + 16 * l);
#pragma unroll
        for (int x = 0; x < 64; x++) held[x] = pack_f16(acc3[2 * x] * ((x & 1) ? s1.y : s0.y), acc3[2 * x + 1] * ((x & 1) ? s1.y : s0.y));
        const uint32_t n0 = pack_f16(-s0.x * s0.y, -s0.x * s0.y), n1 = pack_f16(-s1.x * s1.y, -s1.x * s1.y);
        float accb[96];
#pragma unroll
        for (int x = 0; x < 24; x++) {
          const float2 cs = (reinterpret_cast<const float2*>(smem + SM_CS3 + 1024) + qd)[4 * x];
          accb[4 * x] = -s0.x * cs.x; accb[4 * x + 1] = -s0.x * cs.y; accb[4 * x + 2] = -s1.x * cs.x; accb[4 * x + 3] = -s1.x * cs.y;
        }
        pin(accb);
        WSTAMP(7 + 16 * l);
        gemm_begin<192>(c, wg, warp & 3, p, 3, false);
#pragma unroll 1
        for (int pn = 0; pn < 4; pn++) {
#pragma unroll
          for (int u = 0; u < 4; u++)
            gemm_step<192, false>(accb, c, wg, p, [&]() {
              const uint2 cs = reinterpret_cast<const uint2*>(smem + SM_CS3)[16 * pn + 4 * u + qd];
              const uint32_t h[4] = {hfma2(cs.x, n0, held[4 * u]), hfma2(cs.x, n1, held[4 * u + 1]), hfma2(cs.y, n0, held[4 * u + 2]), hfma2(cs.y, n1, held[4 * u + 3])};
              gelu_chunk<4>(h, hp + 2 * u * CB_BYTES);
            });
          hp += 8 * CB_BYTES;
          __syncwarp();
          mbar_arrive_if(pub + 8 * (6 + pn), lane == 0);
          if (pn < 3) pick_group<16, 1, 4>(held, pn + 1);
        }
        WSTAMP(8 + 16 * l);
#pragma unroll
        for (int x = 0; x < 32; x++) { acc[2 * x] = bf_lo(x3[x]); acc[2 * x + 1] = bf_hi(x3[x]); }
        pin(acc);
        WSTAMP(9 + 16 * l);
        gemm_begin<128>(c, wg, warp & 3, p, 4, false);
        gemm_step<128, false>(acc, c, wg, p, Nop());
        pin(accb);
#pragma unroll 1
        for (int hpn = 0; hpn < 6; hpn++) {
#pragma unroll
          for (int u = 0; u < 4; u++)
            gemm_step<128, false>(acc, c, wg, p, [&]() {
              const uint32_t h[2] = {pack_f16(accb[4 * u] * s0.y, accb[4 * u + 1] * s0.y), pack_f16(accb[4 * u + 2] * s1.y, accb[4 * u + 3] * s1.y)};
              gelu_chunk<2>(h, hp + u * CB_BYTES);
            });
          hp += 4 * CB_BYTES;
          __syncwarp();
          mbar_arrive_if(pub + 8 * (10 + (hpn >> 1)), (hpn & 1) && lane == 0);
          if (hpn < 5) pick_group<16, 1, 6>(accb, hpn + 1);
        }
        WSTAMP(12 + 16 * l);
        p.keep = 1;
#pragma unroll
        for (int x = 0; x < 32; x++) x3[x] = 0;
      }
      p.sh = ph == 0 ? (token_shift(c.j) & 3) * 0x55555555u : ph == 4 ? __funnelshift_r(0xaa5faa5fu, 0xaa5faa5fu, 2 * (c.j & 6)) : 0;
      p.wide = s == l ? 4 : 0;
      float2 s0 = make_float2(0.f, 0.f), s1 = s0;
      gemm_steps<128, true, true>(acc, c, wg, p, s == 2 ? 31 : 16, (LEADS >> (4 * ph)) & 15, Nop(), [&]() {
        if (s == 0) {
          const int sh = l == 0 ? token_shift(c.j) : 0;
          mbar_wait(c.sm + CV_BAR + 8 * (CB_STAT + wg), 0, p.budget);
          s0 = lds_f2(rstat + 8 * sh); s1 = lds_f2(rstat + 8 * sh + 64);
          s0.y *= (row + sh < 0 ? 0.f : 0.5f) * rsqrt_fast(fmaxf(fmaf(-LN_EPS * s0.y, s0.y, 1.f), 0.f) + LN_EPS);
          s1.y *= (row + sh + 8 >= SEQ ? 0.f : 0.5f) * rsqrt_fast(fmaxf(fmaf(-LN_EPS * s1.y, s1.y, 1.f), 0.f) + LN_EPS);
          fence_sched();
        }
      });
      WSTAMP((s == 2 ? 10 : 2 + 2 * s) + 16 * l);
      if (s == 0) {
#pragma unroll
        for (int pn = 0; pn < 2; pn++) {
          uint32_t v[16];
          if (pn == 0) {
            fold_tiles<4>(v, acc, reinterpret_cast<const float2*>(smem + SM_CS1) + qd, s0, s1);
#pragma unroll
            for (int x = 0; x < 8; x++) stg32(reinterpret_cast<char*>(g_h) + frag + (x >> 1) * CB_BYTES + (x & 1) * 128, v[x]);
            fence_sched();
            fold_tiles<4>(v + 8, acc + 16, reinterpret_cast<const float2*>(smem + SM_CS1) + qd + 16, s0, s1);
#pragma unroll
            for (int x = 8; x < 16; x++) stg32(reinterpret_cast<char*>(g_h) + frag + (x >> 1) * CB_BYTES + (x & 1) * 128, v[x]);
            __syncwarp();
            mbar_arrive_if(pub + 8 * 2, lane == 0);
          } else {
            fold_tiles<8>(v, acc + 32, reinterpret_cast<const float2*>(smem + SM_CS1) + qd + 32, s0, s1);
            emit_panel(v, reinterpret_cast<char*>(g_h) + frag + 8 * CB_BYTES, pub + 8 * 3);
          }
          if (l == 0) stage_tiles<8>(v, stage + pn * 8192);
        }
        s0 = lds_f2(rstat); s1 = lds_f2(rstat + 64);
        const float nb0 = -s0.x * s0.y, nb1 = -s1.x * s1.y;
#pragma unroll
        for (int x = 0; x < 32; x++) {
          acc[2 * x] = fmaf(bf_lo(x3[x]), (x & 1) ? s1.y : s0.y, (x & 1) ? nb1 : nb0);
          acc[2 * x + 1] = fmaf(bf_hi(x3[x]), (x & 1) ? s1.y : s0.y, (x & 1) ? nb1 : nb0);
        }
        WSTAMP(3 + 16 * l);
      } else if (s == 1) {
        uint32_t v[32];
#pragma unroll
        for (int x = 0; x < 32; x++) v[x] = pack_bf16(acc[2 * x], acc[2 * x + 1]);
        emit_panel(v, reinterpret_cast<char*>(g_x1) + frag, pub + 8 * 4);
        stage_tiles<16>(v, stage);
        gemm_begin<256>(c, wg, warp & 3, p, 2, true);
        emit_panel(v + 16, reinterpret_cast<char*>(g_x1) + frag + 8 * CB_BYTES, pub + 8 * 5);
#pragma unroll
        for (int x = 0; x < 32; x++) x3[x] = badd2(x3[x], v[x]);
        WSTAMP(5 + 16 * l);
      } else if (l == 0) {
        put_partial(acc, &g_part[2][c.j][row], 0);
        WSTAMP(11);
        const float2* sp = &g_part[2][2 * qd][row];
        RowStats rs;
        rs.load(sp, sp + 8);
        float yf[64];
        mbar_wait(c.bar + 8 * (BAR_OWN + wg), 0, p.budget);
#pragma unroll
        for (int x = 0; x < 16; x++) {
          uint32_t y0, y1;
          asm volatile("ld.shared.v2.u32 {%0,%1}, [%2];" : "=r"(y0), "=r"(y1) : "r"(c.sm + SM_X + wg * 16384 + x * 1024 + t * 8) : "memory");
          yf[4 * x] = bf_lo(y0); yf[4 * x + 1] = bf_hi(y0); yf[4 * x + 2] = bf_lo(y1); yf[4 * x + 3] = bf_hi(y1);
        }
        pin(yf);
        rs.finish(sp, sp + 8, p.budget, s0, s1);
        WSTAMP(13);
        float nb0 = -s0.x * s0.y, nb1 = -s1.x * s1.y;
#pragma unroll
        for (int pn = 0; pn < 2; pn++) {
          if (pn == 1) { const float z = late_zero(c.sm + SM_ZERO); nb0 += z; nb1 += z; }
#pragma unroll
          for (int x = 16 * pn; x < 16 * pn + 16; x++) {
            const float r = (x & 1) ? s1.y : s0.y, nb = (x & 1) ? nb1 : nb0;
            x3[x] = pack_bf16(fmaf(fmaf(acc[2 * x], r, nb), yf[2 * x], acc[2 * x]), fmaf(fmaf(acc[2 * x + 1], r, nb), yf[2 * x + 1], acc[2 * x + 1]));
          }
          if (pn == 1) stage_tiles<16>(x3, stage);
          emit_panel(x3 + 16 * pn, reinterpret_cast<char*>(g_x3[1]) + frag + pn * 8 * CB_BYTES, pub + 8 * pn);
        }
      }
    }
    {
      const uint32_t ob = c.sm + SM_X + warp * 4096, oa = ob + (lane & 15) * 128 + (((lane >> 4) ^ (lane & 7)) << 4);
#pragma unroll
      for (int pn = 0; pn < 2; pn++) {
#pragma unroll
        for (int x = 0; x < 8; x += 2) {
          const float* a = acc + 32 * pn + 4 * x;
          stsm_x4((oa ^ (x << 4)) + pn * 2048, pack_bf16(a[0], a[1]), pack_bf16(a[2], a[3]), pack_bf16(a[4], a[5]), pack_bf16(a[6], a[7]));
        }
        fence_async_smem();
        __syncwarp();
        if (elect_one()) {
          tma_store_2d(&maps.m[M_OUT], ob + pn * 2048, c.j * 128 + 64 * pn, 64 * (16 * wg + c.i) + 16 * (warp & 3));
          if (pn == 1) {
            bulk_commit();
            asm volatile("cp.async.bulk.wait_group.read 0;" ::: "memory");
          }
        }
      }
    }
    WSTAMP(27);
    cluster_exit_barrier();
    WSTAMP(30);
  }
}

typedef CUresult (*EncodeFn)(CUtensorMap*, CUtensorMapDataType, cuuint32_t, void*, const cuuint64_t*, const cuuint64_t*, const cuuint32_t*,
                             const cuuint32_t*, CUtensorMapInterleave, CUtensorMapSwizzle, CUtensorMapL2promotion, CUtensorMapFloatOOBfill);

void encode(EncodeFn fn, CUtensorMap* m, CUtensorMapDataType type, const void* ptr, int rank, const cuuint64_t* dims, const cuuint64_t* strides,
            const cuuint32_t* box, CUtensorMapSwizzle swizzle, CUtensorMapL2promotion promo = CU_TENSOR_MAP_L2_PROMOTION_L2_128B) {
  const cuuint32_t es[3] = {1, 1, 1};
  fn(m, type, rank, const_cast<void*>(ptr), dims, strides, box, es, CU_TENSOR_MAP_INTERLEAVE_NONE, swizzle, promo, CU_TENSOR_MAP_FLOAT_OOB_FILL_NONE);
}
void map_act(EncodeFn fn, CUtensorMap* m, const void* ptr, int cols, int rows = 64) {
  const cuuint64_t dims[2] = {(cuuint64_t)SEQ * 2, (cuuint64_t)cols / 8}, st[1] = {(cuuint64_t)CB_BYTES};
  const cuuint32_t box[2] = {(cuuint32_t)rows * 2, 8};
  encode(fn, m, CU_TENSOR_MAP_DATA_TYPE_UINT64, ptr, 2, dims, st, box, CU_TENSOR_MAP_SWIZZLE_NONE);
}
void map_rows(EncodeFn fn, CUtensorMap* m, const void* ptr, int rows, int cols, int box_rows, int box_cols, CUtensorMapSwizzle swizzle,
              CUtensorMapL2promotion promo) {
  const cuuint64_t dims[2] = {(cuuint64_t)cols, (cuuint64_t)rows}, st[1] = {(cuuint64_t)cols * 2};
  const cuuint32_t box[2] = {(cuuint32_t)box_cols, (cuuint32_t)box_rows};
  encode(fn, m, CU_TENSOR_MAP_DATA_TYPE_BFLOAT16, ptr, 2, dims, st, box, swizzle, promo);
}
void map_w(EncodeFn fn, CUtensorMap* m, const void* ptr, int rows, int cols, int panels) {
  const cuuint64_t dims[3] = {64, (cuuint64_t)rows, (cuuint64_t)cols / 64}, st[2] = {(cuuint64_t)cols * 2, 128};
  const cuuint32_t box[3] = {64, 64, (cuuint32_t)panels};
  encode(fn, m, CU_TENSOR_MAP_DATA_TYPE_BFLOAT16, ptr, 3, dims, st, box, CU_TENSOR_MAP_SWIZZLE_128B);
}

}

extern "C" void kernel_launch(void* const* d_in, const int* in_sizes, int n_in, void* d_out, int out_size) {
  (void)in_sizes; (void)n_in; (void)out_size;
  const bf16* q = (const bf16*)d_in[0];
  const bf16* k = (const bf16*)d_in[1];
  const bf16* v = (const bf16*)d_in[2];
  const bf16* shift_k = (const bf16*)d_in[3];
  const bf16* ssm_k = (const bf16*)d_in[4];
  const bf16* ssm_d = (const bf16*)d_in[5];
  const bf16* w1 = (const bf16*)d_in[7];
  const bf16* w2 = (const bf16*)d_in[8];
  const bf16* w3 = (const bf16*)d_in[9];
  const bf16* w4 = (const bf16*)d_in[10];

  static EncodeFn fn = nullptr;
  static void *p_x3, *p_h, *p_x1, *p_hid, *p_y;
  if (!fn) {
    void* p = nullptr;
    cudaDriverEntryPointQueryResult qr;
    cudaGetDriverEntryPoint("cuTensorMapEncodeTiled", &p, cudaEnableDefault, &qr);
    fn = (EncodeFn)p;
    cudaGetSymbolAddress(&p_x3, g_x3);
    cudaGetSymbolAddress(&p_h, g_h);
    cudaGetSymbolAddress(&p_x1, g_x1);
    cudaGetSymbolAddress(&p_hid, g_hid);
    cudaGetSymbolAddress(&p_y, g_y);
    cudaFuncSetAttribute(fused_kernel, cudaFuncAttributeMaxDynamicSharedMemorySize, MEGA_SMEM);
  }
  Params maps;
  map_act(fn, &maps.m[M_X3B], (const bf16*)p_x3 + SEQ * DM, DM);
  map_act(fn, &maps.m[M_X3S], p_x3, DM, 68);
  map_act(fn, &maps.m[M_H], p_h, DM);
  map_act(fn, &maps.m[M_HS], p_h, DM, 68);
  map_act(fn, &maps.m[M_X1], p_x1, DM);
  map_act(fn, &maps.m[M_HID], p_hid, FF);
  map_act(fn, &maps.m[M_Y], p_y, DM);
  map_rows(fn, &maps.m[M_OUT], d_out, SEQ, DM, 16, 64, CU_TENSOR_MAP_SWIZZLE_128B, CU_TENSOR_MAP_L2_PROMOTION_L2_128B);
  map_w(fn, &maps.m[M_W1], w1, DM, DM, 2);
  map_w(fn, &maps.m[M_W2], w2, DM, DM, 2);
  map_w(fn, &maps.m[M_W3A], w3, DM, FF, 4);
  map_w(fn, &maps.m[M_W3B], w3, DM, FF, 3);
  map_w(fn, &maps.m[M_W4], w4, FF, DM, 2);

  map_rows(fn, &maps.m[M_K], k, SEQ, DM, 256, 8, CU_TENSOR_MAP_SWIZZLE_NONE, KV_PROMO);
  map_rows(fn, &maps.m[M_V], v, SEQ, DM, 256, 8, CU_TENSOR_MAP_SWIZZLE_NONE, KV_PROMO);
  map_rows(fn, &maps.m[M_Q], q, SEQ, DM, 256, 8, CU_TENSOR_MAP_SWIZZLE_NONE, KV_PROMO);
  map_rows(fn, &maps.m[M_W1C], w1, DM, DM, 256, 32, CU_TENSOR_MAP_SWIZZLE_64B, CU_TENSOR_MAP_L2_PROMOTION_L2_128B);
  map_rows(fn, &maps.m[M_W3C], w3, DM, FF, 256, 32, CU_TENSOR_MAP_SWIZZLE_64B, CU_TENSOR_MAP_L2_PROMOTION_L2_128B);
  maps.q = q; maps.shift_k = shift_k; maps.ssm_k = ssm_k; maps.ssm_d = ssm_d; maps.w2 = w2;
  fused_kernel<<<128, 384, MEGA_SMEM, cudaStreamPerThread>>>(maps);
}
```

```cpp
#include <cuda_runtime.h>
#include <cuda_bf16.h>
#include <cuda.h>
#include <stdint.h>

namespace {

typedef __nv_bfloat16 bf16;
constexpr int SEQ = 2048, DM = 1024, FF = 3584;
constexpr float LN_EPS = 1e-5f;

constexpr int CB_BYTES = SEQ * 16;
__device__ __align__(1024) bf16 g_x3[2][SEQ * DM];
__device__ __align__(1024) bf16 g_h[SEQ * DM];
__device__ __align__(1024) bf16 g_x1[SEQ * DM];
__device__ __align__(1024) bf16 g_hid[SEQ * FF];
__device__ __align__(1024) bf16 g_y[SEQ * DM];
__device__ __align__(128) float g_cs1[4][DM];
__device__ __align__(128) float g_cs3[FF];
__device__ __align__(128) uint32_t g_epoch;
__device__ __align__(128) float2 g_part[5][8][SEQ];
__device__ __align__(128) float2 g_qstat[SEQ];
__device__ __align__(128) uint32_t g_qcnt;
__device__ __align__(128) uint32_t g_xcnt[48];
constexpr int FS = 8;
__device__ __align__(128) uint32_t g_flag[32 * 8 * FS];
__device__ __align__(128) uint32_t g_clock[12];
__device__ __align__(128) uint32_t g_role[4];

__device__ __forceinline__ uint32_t smem_u32(const void* p) { return (uint32_t)__cvta_generic_to_shared(p); }
__device__ __forceinline__ uint32_t opaque(uint32_t x) { uint32_t y; asm volatile("mov.u32 %0, %1;" : "=r"(y) : "r"(x)); return y; }
__device__ __forceinline__ void mbar_init(uint32_t bar, uint32_t cnt) { asm volatile("mbarrier.init.shared::cta.b64 [%0], %1;" :: "r"(bar), "r"(cnt)); }
__device__ __forceinline__ void mbar_expect_tx(uint32_t bar, uint32_t bytes) {
  asm volatile("mbarrier.arrive.expect_tx.shared::cta.b64 _, [%0], %1;" :: "r"(bar), "r"(bytes) : "memory");
}
__device__ __forceinline__ void mbar_expect_tx_cluster(uint32_t bar, uint32_t bytes) {
  asm volatile("mbarrier.arrive.expect_tx.shared::cluster.b64 _, [%0], %1;" :: "r"(bar), "r"(bytes) : "memory");
}
__device__ __forceinline__ void mbar_arrive_cluster(uint32_t bar) { asm volatile("mbarrier.arrive.shared::cluster.b64 _, [%0];" :: "r"(bar) : "memory"); }
__device__ __forceinline__ void mbar_arrive(uint32_t bar) { asm volatile("mbarrier.arrive.shared::cta.b64 _, [%0];" :: "r"(bar) : "memory"); }
__device__ __forceinline__ void mbar_arrive_if(uint32_t bar, bool cond) {
  asm volatile("{\n.reg .pred p;\nsetp.ne.b32 p, %1, 0;\n@p mbarrier.arrive.shared::cta.b64 _, [%0];\n}" :: "r"(bar), "r"((uint32_t)cond) : "memory");
}
constexpr int SPIN_LIMIT = 1 << 16;
__device__ __forceinline__ bool mbar_try(uint32_t bar, uint32_t parity) {
  uint32_t done;
  asm volatile("{\n.reg .pred p;\nmbarrier.try_wait.parity.shared::cta.b64 p, [%1], %2;\nselp.b32 %0, 1, 0, p;\n}"
               : "=r"(done) : "r"(bar), "r"(parity) : "memory");
  return done != 0;
}
__device__ __forceinline__ void mbar_wait(uint32_t bar, uint32_t parity, int& budget) {
#pragma unroll 1
  while (!mbar_try(bar, parity)) { if (--budget <= 0) break; }
}
__device__ __forceinline__ bool elect_one() {
  uint32_t p;
  asm volatile("{\n.reg .pred P;\nelect.sync _|P, 0xffffffff;\nselp.b32 %0, 1, 0, P;\n}" : "=r"(p));
  return p != 0;
}
__device__ __forceinline__ void fence_async_smem() { asm volatile("fence.proxy.async.shared::cta;" ::: "memory"); }
__device__ __forceinline__ void fence_async_global() { asm volatile("fence.proxy.async.global;" ::: "memory"); }
__device__ __forceinline__ void named_bar(int id, int n) { asm volatile("bar.sync %0, %1;" :: "r"(id), "r"(n) : "memory"); }
__device__ __forceinline__ uint4 ld_nc_u4(const void* p) {
  uint4 v; asm volatile("ld.global.nc.L1::no_allocate.v4.u32 {%0,%1,%2,%3}, [%4];" : "=r"(v.x), "=r"(v.y), "=r"(v.z), "=r"(v.w) : "l"(p)); return v;
}
__device__ __forceinline__ void tma_2d_mc(uint32_t dst, const CUtensorMap* m, uint32_t bar, int c0, int c1, uint16_t mask) {
  asm volatile("cp.async.bulk.tensor.2d.shared::cluster.global.mbarrier::complete_tx::bytes.multicast::cluster [%0], [%1, {%3, %4}], [%2], %5;"
               :: "r"(dst), "l"(m), "r"(bar), "r"(c0), "r"(c1), "h"(mask) : "memory");
}
__device__ __forceinline__ void tma_2d(uint32_t dst, const CUtensorMap* m, uint32_t bar, int c0, int c1) {
  asm volatile("cp.async.bulk.tensor.2d.shared::cluster.global.mbarrier::complete_tx::bytes [%0], [%1, {%3, %4}], [%2];"
               :: "r"(dst), "l"(m), "r"(bar), "r"(c0), "r"(c1) : "memory");
}
__device__ __forceinline__ void bulk_copy_cluster(uint32_t dst, uint32_t src, uint32_t bytes, uint32_t bar) {
  asm volatile("cp.async.bulk.shared::cluster.shared::cta.mbarrier::complete_tx::bytes [%0], [%1], %2, [%3];"
               :: "r"(dst), "r"(src), "r"(bytes), "r"(bar) : "memory");
}
__device__ __forceinline__ uint32_t mapa(uint32_t addr, uint32_t cta) {
  uint32_t r; asm volatile("mapa.shared::cluster.u32 %0, %1, %2;" : "=r"(r) : "r"(addr), "r"(cta)); return r;
}
__device__ __forceinline__ void bulk_store(void* dst, uint32_t src, uint32_t bytes) {
  asm volatile("cp.async.bulk.global.shared::cta.bulk_group [%0], [%1], %2;" :: "l"(dst), "r"(src), "r"(bytes) : "memory");
}
__device__ __forceinline__ void tma_3d(uint32_t dst, const CUtensorMap* m, uint32_t bar, int c0, int c1, int c2) {
  asm volatile("cp.async.bulk.tensor.3d.shared::cluster.global.mbarrier::complete_tx::bytes [%0], [%1, {%3, %4, %5}], [%2];"
               :: "r"(dst), "l"(m), "r"(bar), "r"(c0), "r"(c1), "r"(c2) : "memory");
}
__device__ __forceinline__ void tma_store_2d(const CUtensorMap* m, uint32_t src, int c0, int c1) {
  asm volatile("cp.async.bulk.tensor.2d.global.shared::cta.bulk_group [%0, {%2, %3}], [%1];" :: "l"(m), "r"(src), "r"(c0), "r"(c1) : "memory");
}
__device__ __forceinline__ void bulk_commit() { asm volatile("cp.async.bulk.commit_group;" ::: "memory"); }
__device__ __forceinline__ void bulk_wait_all() { asm volatile("cp.async.bulk.wait_group 0;" ::: "memory"); }
__device__ __forceinline__ void prefetch_l2(const void* p, uint32_t bytes) { asm volatile("cp.async.bulk.prefetch.L2.global [%0], %1;" :: "l"(p), "r"(bytes) : "memory"); }
__device__ __forceinline__ void cluster_exit_barrier() {
  __syncwarp();
  asm volatile("barrier.cluster.arrive.relaxed;\nbarrier.cluster.wait;" ::: "memory");
}
__device__ __forceinline__ void wg_fence() { asm volatile("wgmma.fence.sync.aligned;" ::: "memory"); }
__device__ __forceinline__ void wg_commit() { asm volatile("wgmma.commit_group.sync.aligned;" ::: "memory"); }
template <int N> __device__ __forceinline__ void wg_wait() { asm volatile("wgmma.wait_group.sync.aligned %0;" :: "n"(N) : "memory"); }
template <int R> __device__ __forceinline__ void reg_alloc() { asm volatile("setmaxnreg.inc.sync.aligned.u32 %0;" :: "n"(R)); }
template <int R> __device__ __forceinline__ void reg_dealloc() { asm volatile("setmaxnreg.dec.sync.aligned.u32 %0;" :: "n"(R)); }
__device__ __forceinline__ void ldsm_x4(uint32_t addr, uint32_t& r0, uint32_t& r1, uint32_t& r2, uint32_t& r3) {
  asm volatile("ldmatrix.sync.aligned.m8n8.x4.shared.b16 {%0,%1,%2,%3}, [%4];" : "=r"(r0), "=r"(r1), "=r"(r2), "=r"(r3) : "r"(addr));
}
__device__ __forceinline__ void ldsm_x4_t(uint32_t addr, uint32_t& r0, uint32_t& r1, uint32_t& r2, uint32_t& r3) {
  asm volatile("ldmatrix.sync.aligned.m8n8.x4.trans.shared.b16 {%0,%1,%2,%3}, [%4];" : "=r"(r0), "=r"(r1), "=r"(r2), "=r"(r3) : "r"(addr));
}
__device__ __forceinline__ void stsm_x4(uint32_t addr, uint32_t r0, uint32_t r1, uint32_t r2, uint32_t r3) {
  asm volatile("stmatrix.sync.aligned.m8n8.x4.shared.b16 [%0], {%1,%2,%3,%4};" :: "r"(addr), "r"(r0), "r"(r1), "r"(r2), "r"(r3) : "memory");
}
__device__ __forceinline__ float2 lds_f2(uint32_t addr) { float2 v; asm volatile("ld.shared.v2.f32 {%0,%1}, [%2];" : "=f"(v.x), "=f"(v.y) : "r"(addr)); return v; }
__device__ __forceinline__ void sts16(uint32_t addr, uint16_t v) { asm volatile("st.shared.u16 [%0], %1;" :: "r"(addr), "h"(v) : "memory"); }
__device__ __forceinline__ void sts32(uint32_t addr, uint32_t v) { asm volatile("st.shared.u32 [%0], %1;" :: "r"(addr), "r"(v) : "memory"); }
__device__ __forceinline__ void sts128(uint32_t addr, uint4 v) {
  asm volatile("st.shared.v4.u32 [%0], {%1,%2,%3,%4};" :: "r"(addr), "r"(v.x), "r"(v.y), "r"(v.z), "r"(v.w) : "memory");
}
__device__ __forceinline__ void mma16816(float (&d)[4], uint32_t a0, uint32_t a1, uint32_t a2, uint32_t a3, uint32_t b0, uint32_t b1) {
  asm("mma.sync.aligned.m16n8k16.row.col.f32.bf16.bf16.f32 {%0,%1,%2,%3}, {%4,%5,%6,%7}, {%8,%9}, {%0,%1,%2,%3};"
               : "+f"(d[0]), "+f"(d[1]), "+f"(d[2]), "+f"(d[3]) : "r"(a0), "r"(a1), "r"(a2), "r"(a3), "r"(b0), "r"(b1));
}
__device__ __forceinline__ uint32_t pack_bf16(float lo, float hi) {
  uint32_t r; asm("cvt.rn.bf16x2.f32 %0, %1, %2;" : "=r"(r) : "f"(hi), "f"(lo)); return r;
}
__device__ __forceinline__ float bf_lo(uint32_t v) { return __uint_as_float(v << 16); }
__device__ __forceinline__ float bf_hi(uint32_t v) { return __uint_as_float(v & 0xffff0000u); }
__device__ __forceinline__ uint32_t bmul2(uint32_t a, uint32_t b) { uint32_t r; asm("mul.rn.bf16x2 %0, %1, %2;" : "=r"(r) : "r"(a), "r"(b)); return r; }
__device__ __forceinline__ uint32_t badd2(uint32_t a, uint32_t b) { uint32_t r; asm("add.rn.bf16x2 %0, %1, %2;" : "=r"(r) : "r"(a), "r"(b)); return r; }
#define STAMP(idx) do {} while (0)
#define MSTAMP(idx) do {} while (0)
#define BSTAMP(idx, saddr) do {} while (0)

__device__ __forceinline__ uint32_t pack_f16(float lo, float hi) {
  uint32_t r; asm("cvt.rn.satfinite.f16x2.f32 %0, %1, %2;" : "=r"(r) : "f"(hi), "f"(lo)); return r;
}
__device__ __forceinline__ uint32_t hfma2(uint32_t a, uint32_t b, uint32_t c) { uint32_t r; asm("fma.rn.f16x2 %0, %1, %2, %3;" : "=r"(r) : "r"(a), "r"(b), "r"(c)); return r; }
__device__ __forceinline__ uint32_t gelu_pair_f16(uint32_t h) {
  const uint32_t c0 = 0x3e623e62u, c1 = 0x34913491u;
  uint32_t u, p, z, t, r, o;
  asm("mul.rn.f16x2 %0, %1, %1;" : "=r"(u) : "r"(h));
  asm("fma.rn.f16x2 %0, %1, %2, %3;" : "=r"(p) : "r"(u), "r"(c1), "r"(c0));
  asm("mul.rn.f16x2 %0, %1, %2;" : "=r"(z) : "r"(h), "r"(p));
  asm("tanh.approx.f16x2 %0, %1;" : "=r"(t) : "r"(z));
  asm("fma.rn.f16x2 %0, %1, %2, %1;" : "=r"(r) : "r"(h), "r"(t));
  float lo, hi;
  asm("{\n.reg .f16 a, b;\nmov.b32 {a, b}, %2;\ncvt.f32.f16 %0, a;\ncvt.f32.f16 %1, b;\n}" : "=f"(lo), "=f"(hi) : "r"(r));
  asm("cvt.rn.bf16x2.f32 %0, %1, %2;" : "=r"(o) : "f"(hi), "f"(lo));
  return o;
}
__device__ __forceinline__ float gelu_from_half(float h) {
  const float c0 = 2.f * 0.7978845608028654f, c1 = 8.f * 0.7978845608028654f * 0.044715f;
  float z = h * fmaf(h * h, c1, c0);
  float t; asm("tanh.approx.f32 %0, %1;" : "=f"(t) : "f"(z));
  return fmaf(h, t, h);
}
__device__ __forceinline__ void wgmma_ss_n128(float (&d)[64], uint32_t a_lo, uint32_t b_lo) {
  asm volatile(
    "{\n.reg .b64 da, db;\nmov.b64 da, {%64, 8};\nmov.b64 db, {%65, 0x40000040};\n"
    "wgmma.mma_async.sync.aligned.m64n128k16.f32.bf16.bf16 "
    "{%0, %1, %2, %3, %4, %5, %6, %7, %8, %9, %10, %11, %12, %13, %14, %15, "
    "%16, %17, %18, %19, %20, %21, %22, %23, %24, %25, %26, %27, %28, %29, %30, %31, "
    "%32, %33, %34, %35, %36, %37, %38, %39, %40, %41, %42, %43, %44, %45, %46, %47, "
    "%48, %49, %50, %51, %52, %53, %54, %55, %56, %57, %58, %59, %60, %61, %62, %63}, "
    "da, db, 1, 1, 1, 0, 1;\n}\n"
    : "+f"(d[0]), "+f"(d[1]), "+f"(d[2]), "+f"(d[3]), "+f"(d[4]), "+f"(d[5]), "+f"(d[6]), "+f"(d[7]),
      "+f"(d[8]), "+f"(d[9]), "+f"(d[10]), "+f"(d[11]), "+f"(d[12]), "+f"(d[13]), "+f"(d[14]), "+f"(d[15]),
      "+f"(d[16]), "+f"(d[17]), "+f"(d[18]), "+f"(d[19]), "+f"(d[20]), "+f"(d[21]), "+f"(d[22]), "+f"(d[23]),
      "+f"(d[24]), "+f"(d[25]), "+f"(d[26]), "+f"(d[27]), "+f"(d[28]), "+f"(d[29]), "+f"(d[30]), "+f"(d[31]),
      "+f"(d[32]), "+f"(d[33]), "+f"(d[34]), "+f"(d[35]), "+f"(d[36]), "+f"(d[37]), "+f"(d[38]), "+f"(d[39]),
      "+f"(d[40]), "+f"(d[41]), "+f"(d[42]), "+f"(d[43]), "+f"(d[44]), "+f"(d[45]), "+f"(d[46]), "+f"(d[47]),
      "+f"(d[48]), "+f"(d[49]), "+f"(d[50]), "+f"(d[51]), "+f"(d[52]), "+f"(d[53]), "+f"(d[54]), "+f"(d[55]),
      "+f"(d[56]), "+f"(d[57]), "+f"(d[58]), "+f"(d[59]), "+f"(d[60]), "+f"(d[61]), "+f"(d[62]), "+f"(d[63])
    : "r"(a_lo), "r"(b_lo));
}
__device__ __forceinline__ void wgmma_ss_n192(float (&d)[96], uint32_t a_lo, uint32_t b_lo) {
  asm volatile(
    "{\n.reg .b64 da, db;\nmov.b64 da, {%96, 8};\nmov.b64 db, {%97, 0x40000040};\n"
    "wgmma.mma_async.sync.aligned.m64n192k16.f32.bf16.bf16 "
    "{%0, %1, %2, %3, %4, %5, %6, %7, %8, %9, %10, %11, %12, %13, %14, %15, "
    "%16, %17, %18, %19, %20, %21, %22, %23, %24, %25, %26, %27, %28, %29, %30, %31, "
    "%32, %33, %34, %35, %36, %37, %38, %39, %40, %41, %42, %43, %44, %45, %46, %47, "
    "%48, %49, %50, %51, %52, %53, %54, %55, %56, %57, %58, %59, %60, %61, %62, %63, "
    "%64, %65, %66, %67, %68, %69, %70, %71, %72, %73, %74, %75, %76, %77, %78, %79, "
    "%80, %81, %82, %83, %84, %85, %86, %87, %88, %89, %90, %91, %92, %93, %94, %95}, "
    "da, db, 1, 1, 1, 0, 1;\n}\n"
    : "+f"(d[0]), "+f"(d[1]), "+f"(d[2]), "+f"(d[3]), "+f"(d[4]), "+f"(d[5]), "+f"(d[6]), "+f"(d[7]),
      "+f"(d[8]), "+f"(d[9]), "+f"(d[10]), "+f"(d[11]), "+f"(d[12]), "+f"(d[13]), "+f"(d[14]), "+f"(d[15]),
      "+f"(d[16]), "+f"(d[17]), "+f"(d[18]), "+f"(d[19]), "+f"(d[20]), "+f"(d[21]), "+f"(d[22]), "+f"(d[23]),
      "+f"(d[24]), "+f"(d[25]), "+f"(d[26]), "+f"(d[27]), "+f"(d[28]), "+f"(d[29]), "+f"(d[30]), "+f"(d[31]),
      "+f"(d[32]), "+f"(d[33]), "+f"(d[34]), "+f"(d[35]), "+f"(d[36]), "+f"(d[37]), "+f"(d[38]), "+f"(d[39]),
      "+f"(d[40]), "+f"(d[41]), "+f"(d[42]), "+f"(d[43]), "+f"(d[44]), "+f"(d[45]), "+f"(d[46]), "+f"(d[47]),
      "+f"(d[48]), "+f"(d[49]), "+f"(d[50]), "+f"(d[51]), "+f"(d[52]), "+f"(d[53]), "+f"(d[54]), "+f"(d[55]),
      "+f"(d[56]), "+f"(d[57]), "+f"(d[58]), "+f"(d[59]), "+f"(d[60]), "+f"(d[61]), "+f"(d[62]), "+f"(d[63]),
      "+f"(d[64]), "+f"(d[65]), "+f"(d[66]), "+f"(d[67]), "+f"(d[68]), "+f"(d[69]), "+f"(d[70]), "+f"(d[71]),
      "+f"(d[72]), "+f"(d[73]), "+f"(d[74]), "+f"(d[75]), "+f"(d[76]), "+f"(d[77]), "+f"(d[78]), "+f"(d[79]),
      "+f"(d[80]), "+f"(d[81]), "+f"(d[82]), "+f"(d[83]), "+f"(d[84]), "+f"(d[85]), "+f"(d[86]), "+f"(d[87]),
      "+f"(d[88]), "+f"(d[89]), "+f"(d[90]), "+f"(d[91]), "+f"(d[92]), "+f"(d[93]), "+f"(d[94]), "+f"(d[95])
    : "r"(a_lo), "r"(b_lo));
}
__device__ __forceinline__ void wgmma_ss_n256(float (&d)[128], uint32_t a_lo, uint32_t b_lo) {
  asm volatile(
    "{\n.reg .b64 da, db;\nmov.b64 da, {%128, 8};\nmov.b64 db, {%129, 0x40000040};\n"
    "wgmma.mma_async.sync.aligned.m64n256k16.f32.bf16.bf16 "
    "{%0, %1, %2, %3, %4, %5, %6, %7, %8, %9, %10, %11, %12, %13, %14, %15, "
    "%16, %17, %18, %19, %20, %21, %22, %23, %24, %25, %26, %27, %28, %29, %30, %31, "
    "%32, %33, %34, %35, %36, %37, %38, %39, %40, %41, %42, %43, %44, %45, %46, %47, "
    "%48, %49, %50, %51, %52, %53, %54, %55, %56, %57, %58, %59, %60, %61, %62, %63, "
    "%64, %65, %66, %67, %68, %69, %70, %71, %72, %73, %74, %75, %76, %77, %78, %79, "
    "%80, %81, %82, %83, %84, %85, %86, %87, %88, %89, %90, %91, %92, %93, %94, %95, "
    "%96, %97, %98, %99, %100, %101, %102, %103, %104, %105, %106, %107, %108, %109, %110, %111, "
    "%112, %113, %114, %115, %116, %117, %118, %119, %120, %121, %122, %123, %124, %125, %126, %127}, "
    "da, db, 1, 1, 1, 0, 1;\n}\n"
    : "+f"(d[0]), "+f"(d[1]), "+f"(d[2]), "+f"(d[3]), "+f"(d[4]), "+f"(d[5]), "+f"(d[6]), "+f"(d[7]),
      "+f"(d[8]), "+f"(d[9]), "+f"(d[10]), "+f"(d[11]), "+f"(d[12]), "+f"(d[13]), "+f"(d[14]), "+f"(d[15]),
      "+f"(d[16]), "+f"(d[17]), "+f"(d[18]), "+f"(d[19]), "+f"(d[20]), "+f"(d[21]), "+f"(d[22]), "+f"(d[23]),
      "+f"(d[24]), "+f"(d[25]), "+f"(d[26]), "+f"(d[27]), "+f"(d[28]), "+f"(d[29]), "+f"(d[30]), "+f"(d[31]),
      "+f"(d[32]), "+f"(d[33]), "+f"(d[34]), "+f"(d[35]), "+f"(d[36]), "+f"(d[37]), "+f"(d[38]), "+f"(d[39]),
      "+f"(d[40]), "+f"(d[41]), "+f"(d[42]), "+f"(d[43]), "+f"(d[44]), "+f"(d[45]), "+f"(d[46]), "+f"(d[47]),
      "+f"(d[48]), "+f"(d[49]), "+f"(d[50]), "+f"(d[51]), "+f"(d[52]), "+f"(d[53]), "+f"(d[54]), "+f"(d[55]),
      "+f"(d[56]), "+f"(d[57]), "+f"(d[58]), "+f"(d[59]), "+f"(d[60]), "+f"(d[61]), "+f"(d[62]), "+f"(d[63]),
      "+f"(d[64]), "+f"(d[65]), "+f"(d[66]), "+f"(d[67]), "+f"(d[68]), "+f"(d[69]), "+f"(d[70]), "+f"(d[71]),
      "+f"(d[72]), "+f"(d[73]), "+f"(d[74]), "+f"(d[75]), "+f"(d[76]), "+f"(d[77]), "+f"(d[78]), "+f"(d[79]),
      "+f"(d[80]), "+f"(d[81]), "+f"(d[82]), "+f"(d[83]), "+f"(d[84]), "+f"(d[85]), "+f"(d[86]), "+f"(d[87]),
      "+f"(d[88]), "+f"(d[89]), "+f"(d[90]), "+f"(d[91]), "+f"(d[92]), "+f"(d[93]), "+f"(d[94]), "+f"(d[95]),
      "+f"(d[96]), "+f"(d[97]), "+f"(d[98]), "+f"(d[99]), "+f"(d[100]), "+f"(d[101]), "+f"(d[102]), "+f"(d[103]),
      "+f"(d[104]), "+f"(d[105]), "+f"(d[106]), "+f"(d[107]), "+f"(d[108]), "+f"(d[109]), "+f"(d[110]), "+f"(d[111]),
      "+f"(d[112]), "+f"(d[113]), "+f"(d[114]), "+f"(d[115]), "+f"(d[116]), "+f"(d[117]), "+f"(d[118]), "+f"(d[119]),
      "+f"(d[120]), "+f"(d[121]), "+f"(d[122]), "+f"(d[123]), "+f"(d[124]), "+f"(d[125]), "+f"(d[126]), "+f"(d[127])
    : "r"(a_lo), "r"(b_lo));
}
__device__ __forceinline__ void wgmma_ss_n128_p(float (&d)[64], uint32_t a_lo, uint32_t b_lo, uint32_t keep) {
  asm volatile(
    "{\n.reg .pred p;\nsetp.ne.b32 p, %66, 0;\n"
    "{\n.reg .b64 da, db;\nmov.b64 da, {%64, 8};\nmov.b64 db, {%65, 0x40000040};\n"
    "wgmma.mma_async.sync.aligned.m64n128k16.f32.bf16.bf16 "
    "{%0, %1, %2, %3, %4, %5, %6, %7, %8, %9, %10, %11, %12, %13, %14, %15, "
    "%16, %17, %18, %19, %20, %21, %22, %23, %24, %25, %26, %27, %28, %29, %30, %31, "
    "%32, %33, %34, %35, %36, %37, %38, %39, %40, %41, %42, %43, %44, %45, %46, %47, "
    "%48, %49, %50, %51, %52, %53, %54, %55, %56, %57, %58, %59, %60, %61, %62, %63}, "
    "da, db, p, 1, 1, 0, 1;\n}\n}\n"
    : "+f"(d[0]), "+f"(d[1]), "+f"(d[2]), "+f"(d[3]), "+f"(d[4]), "+f"(d[5]), "+f"(d[6]), "+f"(d[7]),
      "+f"(d[8]), "+f"(d[9]), "+f"(d[10]), "+f"(d[11]), "+f"(d[12]), "+f"(d[13]), "+f"(d[14]), "+f"(d[15]),
      "+f"(d[16]), "+f"(d[17]), "+f"(d[18]), "+f"(d[19]), "+f"(d[20]), "+f"(d[21]), "+f"(d[22]), "+f"(d[23]),
      "+f"(d[24]), "+f"(d[25]), "+f"(d[26]), "+f"(d[27]), "+f"(d[28]), "+f"(d[29]), "+f"(d[30]), "+f"(d[31]),
      "+f"(d[32]), "+f"(d[33]), "+f"(d[34]), "+f"(d[35]), "+f"(d[36]), "+f"(d[37]), "+f"(d[38]), "+f"(d[39]),
      "+f"(d[40]), "+f"(d[41]), "+f"(d[42]), "+f"(d[43]), "+f"(d[44]), "+f"(d[45]), "+f"(d[46]), "+f"(d[47]),
      "+f"(d[48]), "+f"(d[49]), "+f"(d[50]), "+f"(d[51]), "+f"(d[52]), "+f"(d[53]), "+f"(d[54]), "+f"(d[55]),
      "+f"(d[56]), "+f"(d[57]), "+f"(d[58]), "+f"(d[59]), "+f"(d[60]), "+f"(d[61]), "+f"(d[62]), "+f"(d[63])
    : "r"(a_lo), "r"(b_lo), "r"(keep));
}
__device__ __forceinline__ void wgmma_ss_n256_first(float (&d)[128], uint32_t a_lo, uint32_t b_lo) {
  asm volatile(
    "{\n.reg .b64 da, db;\nmov.b64 da, {%128, 8};\nmov.b64 db, {%129, 0x40000040};\n"
    "mov.b32 %0, 0; mov.b32 %1, 0; mov.b32 %2, 0; mov.b32 %3, 0; mov.b32 %4, 0; mov.b32 %5, 0; mov.b32 %6, 0; mov.b32 %7, 0;\n"
    "mov.b32 %8, 0; mov.b32 %9, 0; mov.b32 %10, 0; mov.b32 %11, 0; mov.b32 %12, 0; mov.b32 %13, 0; mov.b32 %14, 0; mov.b32 %15, 0;\n"
    "mov.b32 %16, 0; mov.b32 %17, 0; mov.b32 %18, 0; mov.b32 %19, 0; mov.b32 %20, 0; mov.b32 %21, 0; mov.b32 %22, 0; mov.b32 %23, 0;\n"
    "mov.b32 %24, 0; mov.b32 %25, 0; mov.b32 %26, 0; mov.b32 %27, 0; mov.b32 %28, 0; mov.b32 %29, 0; mov.b32 %30, 0; mov.b32 %31, 0;\n"
    "mov.b32 %32, 0; mov.b32 %33, 0; mov.b32 %34, 0; mov.b32 %35, 0; mov.b32 %36, 0; mov.b32 %37, 0; mov.b32 %38, 0; mov.b32 %39, 0;\n"
    "mov.b32 %40, 0; mov.b32 %41, 0; mov.b32 %42, 0; mov.b32 %43, 0; mov.b32 %44, 0; mov.b32 %45, 0; mov.b32 %46, 0; mov.b32 %47, 0;\n"
    "mov.b32 %48, 0; mov.b32 %49, 0; mov.b32 %50, 0; mov.b32 %51, 0; mov.b32 %52, 0; mov.b32 %53, 0; mov.b32 %54, 0; mov.b32 %55, 0;\n"
    "mov.b32 %56, 0; mov.b32 %57, 0; mov.b32 %58, 0; mov.b32 %59, 0; mov.b32 %60, 0; mov.b32 %61, 0; mov.b32 %62, 0; mov.b32 %63, 0;\n"
    "mov.b32 %64, 0; mov.b32 %65, 0; mov.b32 %66, 0; mov.b32 %67, 0; mov.b32 %68, 0; mov.b32 %69, 0; mov.b32 %70, 0; mov.b32 %71, 0;\n"
    "mov.b32 %72, 0; mov.b32 %73, 0; mov.b32 %74, 0; mov.b32 %75, 0; mov.b32 %76, 0; mov.b32 %77, 0; mov.b32 %78, 0; mov.b32 %79, 0;\n"
    "mov.b32 %80, 0; mov.b32 %81, 0; mov.b32 %82, 0; mov.b32 %83, 0; mov.b32 %84, 0; mov.b32 %85, 0; mov.b32 %86, 0; mov.b32 %87, 0;\n"
    "mov.b32 %88, 0; mov.b32 %89, 0; mov.b32 %90, 0; mov.b32 %91, 0; mov.b32 %92, 0; mov.b32 %93, 0; mov.b32 %94, 0; mov.b32 %95, 0;\n"
    "mov.b32 %96, 0; mov.b32 %97, 0; mov.b32 %98, 0; mov.b32 %99, 0; mov.b32 %100, 0; mov.b32 %101, 0; mov.b32 %102, 0; mov.b32 %103, 0;\n"
    "mov.b32 %104, 0; mov.b32 %105, 0; mov.b32 %106, 0; mov.b32 %107, 0; mov.b32 %108, 0; mov.b32 %109, 0; mov.b32 %110, 0; mov.b32 %111, 0;\n"
    "mov.b32 %112, 0; mov.b32 %113, 0; mov.b32 %114, 0; mov.b32 %115, 0; mov.b32 %116, 0; mov.b32 %117, 0; mov.b32 %118, 0; mov.b32 %119, 0;\n"
    "mov.b32 %120, 0; mov.b32 %121, 0; mov.b32 %122, 0; mov.b32 %123, 0; mov.b32 %124, 0; mov.b32 %125, 0; mov.b32 %126, 0; mov.b32 %127, 0;\n"
    "wgmma.mma_async.sync.aligned.m64n256k16.f32.bf16.bf16 "
    "{%0, %1, %2, %3, %4, %5, %6, %7, %8, %9, %10, %11, %12, %13, %14, %15, "
    "%16, %17, %18, %19, %20, %21, %22, %23, %24, %25, %26, %27, %28, %29, %30, %31, "
    "%32, %33, %34, %35, %36, %37, %38, %39, %40, %41, %42, %43, %44, %45, %46, %47, "
    "%48, %49, %50, %51, %52, %53, %54, %55, %56, %57, %58, %59, %60, %61, %62, %63, "
    "%64, %65, %66, %67, %68, %69, %70, %71, %72, %73, %74, %75, %76, %77, %78, %79, "
    "%80, %81, %82, %83, %84, %85, %86, %87, %88, %89, %90, %91, %92, %93, %94, %95, "
    "%96, %97, %98, %99, %100, %101, %102, %103, %104, %105, %106, %107, %108, %109, %110, %111, "
    "%112, %113, %114, %115, %116, %117, %118, %119, %120, %121, %122, %123, %124, %125, %126, %127}, "
    "da, db, 1, 1, 1, 0, 1;\n}\n"
    : "=f"(d[0]), "=f"(d[1]), "=f"(d[2]), "=f"(d[3]), "=f"(d[4]), "=f"(d[5]), "=f"(d[6]), "=f"(d[7]),
      "=f"(d[8]), "=f"(d[9]), "=f"(d[10]), "=f"(d[11]), "=f"(d[12]), "=f"(d[13]), "=f"(d[14]), "=f"(d[15]),
      "=f"(d[16]), "=f"(d[17]), "=f"(d[18]), "=f"(d[19]), "=f"(d[20]), "=f"(d[21]), "=f"(d[22]), "=f"(d[23]),
      "=f"(d[24]), "=f"(d[25]), "=f"(d[26]), "=f"(d[27]), "=f"(d[28]), "=f"(d[29]), "=f"(d[30]), "=f"(d[31]),
      "=f"(d[32]), "=f"(d[33]), "=f"(d[34]), "=f"(d[35]), "=f"(d[36]), "=f"(d[37]), "=f"(d[38]), "=f"(d[39]),
      "=f"(d[40]), "=f"(d[41]), "=f"(d[42]), "=f"(d[43]), "=f"(d[44]), "=f"(d[45]), "=f"(d[46]), "=f"(d[47]),
      "=f"(d[48]), "=f"(d[49]), "=f"(d[50]), "=f"(d[51]), "=f"(d[52]), "=f"(d[53]), "=f"(d[54]), "=f"(d[55]),
      "=f"(d[56]), "=f"(d[57]), "=f"(d[58]), "=f"(d[59]), "=f"(d[60]), "=f"(d[61]), "=f"(d[62]), "=f"(d[63]),
      "=f"(d[64]), "=f"(d[65]), "=f"(d[66]), "=f"(d[67]), "=f"(d[68]), "=f"(d[69]), "=f"(d[70]), "=f"(d[71]),
      "=f"(d[72]), "=f"(d[73]), "=f"(d[74]), "=f"(d[75]), "=f"(d[76]), "=f"(d[77]), "=f"(d[78]), "=f"(d[79]),
      "=f"(d[80]), "=f"(d[81]), "=f"(d[82]), "=f"(d[83]), "=f"(d[84]), "=f"(d[85]), "=f"(d[86]), "=f"(d[87]),
      "=f"(d[88]), "=f"(d[89]), "=f"(d[90]), "=f"(d[91]), "=f"(d[92]), "=f"(d[93]), "=f"(d[94]), "=f"(d[95]),
      "=f"(d[96]), "=f"(d[97]), "=f"(d[98]), "=f"(d[99]), "=f"(d[100]), "=f"(d[101]), "=f"(d[102]), "=f"(d[103]),
      "=f"(d[104]), "=f"(d[105]), "=f"(d[106]), "=f"(d[107]), "=f"(d[108]), "=f"(d[109]), "=f"(d[110]), "=f"(d[111]),
      "=f"(d[112]), "=f"(d[113]), "=f"(d[114]), "=f"(d[115]), "=f"(d[116]), "=f"(d[117]), "=f"(d[118]), "=f"(d[119]),
      "=f"(d[120]), "=f"(d[121]), "=f"(d[122]), "=f"(d[123]), "=f"(d[124]), "=f"(d[125]), "=f"(d[126]), "=f"(d[127])
    : "r"(a_lo), "r"(b_lo));
}

template <int N> struct Mma;
template <> struct Mma<128> {
  static __device__ __forceinline__ void ss(float (&d)[64], uint32_t a, uint32_t b) { wgmma_ss_n128(d, a, b); }
  static __device__ __forceinline__ void ss(float (&d)[64], uint32_t a, uint32_t b, uint32_t keep) { wgmma_ss_n128_p(d, a, b, keep); }
};
template <> struct Mma<192> {
  static __device__ __forceinline__ void ss(float (&d)[96], uint32_t a, uint32_t b) { wgmma_ss_n192(d, a, b); }
};
template <> struct Mma<256> {
  static __device__ __forceinline__ void ss(float (&d)[128], uint32_t a, uint32_t b) { wgmma_ss_n256(d, a, b); }
  static __device__ __forceinline__ void ss(float (&d)[128], uint32_t a, uint32_t b, uint32_t) { wgmma_ss_n256_first(d, a, b); }
};
template <int R> __device__ __forceinline__ void pin(float (&d)[R]) {
#pragma unroll
  for (int x = 0; x < R; x++) asm volatile("" : "+f"(d[x]));
}

__device__ __forceinline__ uint32_t ld_relaxed(const uint32_t* p) {
  uint32_t v; asm volatile("ld.relaxed.gpu.global.u32 %0, [%1];" : "=r"(v) : "l"(p) : "memory"); return v;
}
__device__ __forceinline__ void red_release(uint32_t* p) { asm volatile("red.release.gpu.global.add.u32 [%0], 1;" :: "l"(p) : "memory"); }
__device__ __forceinline__ uint32_t both_valid(uint32_t a, uint32_t b, uint32_t ep) {
  uint32_t r; asm("lop3.b32 %0, %1, %2, %3, 0x42;" : "=r"(r) : "r"(a), "r"(b), "r"(ep)); return r;
}
__device__ __forceinline__ uint32_t tagged(float v, uint32_t ep) { return (__float_as_uint(v) | 1u) ^ (ep & 1u); }
__device__ __forceinline__ void st_release(uint32_t* p, uint32_t v) { asm volatile("st.release.gpu.global.u32 [%0], %1;" :: "l"(p), "r"(v) : "memory"); }
__device__ __forceinline__ void stg32(void* p, uint32_t v) { asm volatile("st.global.u32 [%0], %1;" :: "l"(p), "r"(v) : "memory"); }
__device__ __forceinline__ float rsqrt_fast(float x) { float r; asm("rsqrt.approx.ftz.f32 %0, %1;" : "=f"(r) : "f"(x)); return r; }
__device__ __forceinline__ uint32_t gate_pair(uint32_t x, uint32_t y, uint32_t r, uint32_t nb) {
  uint32_t o;
  asm("{\n.reg .b16 l, h;\n.reg .b32 ll, hh, t;\nmov.b32 {l, h}, %3;\nmov.b32 ll, {l, l};\nmov.b32 hh, {h, h};\n"
      "fma.rn.bf16x2 t, %1, ll, %4;\nfma.rn.bf16x2 t, %1, hh, t;\nfma.rn.bf16x2 %0, t, %2, %1;\n}" : "=r"(o) : "r"(x), "r"(y), "r"(r), "r"(nb));
  return o;
}

constexpr int CV_KT_O = 4144;
constexpr int CV_KT_CH = 8336;
constexpr int CV_KH = 2064;
constexpr int CV_U_PLANE = 2240;
constexpr int CV_U_CH = 4496;
constexpr int CV_VQ = 8320, CV_Y_CH = 1040, CV_XROW = 2064;
constexpr int SM_BAR = 0;
constexpr int CV_K = 896;
constexpr int CV_X = CV_K + 128 + 32768;
constexpr int CV_ST0 = CV_X + 16 * CV_XROW;
constexpr int CV_KT = CV_ST0 + 8192;
constexpr int CV_QS = CV_KT + 8 * CV_KT_CH;
constexpr int CV_U = 142848;
constexpr int CV_V = CV_U + 8 * CV_U_CH;
constexpr int CV_ST1 = CV_V + 4 * CV_VQ;
constexpr int SM_ZERO = CV_ST1 + 8192, SM_ROLE = SM_ZERO + 4, SM_EPOCH = SM_ZERO + 8;
constexpr int CV_END = SM_ZERO + 16;
static_assert(CV_QS + 1024 <= CV_U && CV_X % 1024 == 0 && CV_V % 128 == 0, "layout");
constexpr int CV_BAR = SM_BAR + 8 * 84, BAR_REL = 25;
enum { CB_K0, CB_QA, CB_Q0, CB_Q1, CB_Q2, CB_Q3, CB_K1, CB_X0, CB_X1, CB_QC0, CB_QC1, CB_QS, CB_U1, CB_U2,
       CB_ST0, CB_ST1, CB_O1, CB_P1, CB_Y1, CB_Y2, CB_P2, CB_EARLY, CB_LATE, CB_YOUT, CB_STAT, CB_XFREE = CB_STAT + 2, CB_COUNT };
static_assert(CV_BAR + 8 * CB_COUNT <= CV_K, "layout");

__device__ __forceinline__ uint32_t lds32_nv(uint32_t addr) { uint32_t v; asm("ld.shared.u32 %0, [%1];" : "=r"(v) : "r"(addr)); return v; }
__device__ __forceinline__ void ldsm_x4_nv(uint32_t addr, uint32_t& r0, uint32_t& r1, uint32_t& r2, uint32_t& r3) {
  asm("ldmatrix.sync.aligned.m8n8.x4.shared.b16 {%0,%1,%2,%3}, [%4];" : "=r"(r0), "=r"(r1), "=r"(r2), "=r"(r3) : "r"(addr));
}
__device__ __forceinline__ void stsm_x4_t(uint32_t addr, uint32_t r0, uint32_t r1, uint32_t r2, uint32_t r3) {
  asm volatile("stmatrix.sync.aligned.m8n8.x4.trans.shared.b16 [%0], {%1,%2,%3,%4};" :: "r"(addr), "r"(r0), "r"(r1), "r"(r2), "r"(r3) : "memory");
}
__device__ __forceinline__ void bulk_load(uint32_t dst, const void* src, uint32_t bytes, uint32_t bar) {
  asm volatile("cp.async.bulk.shared::cluster.global.mbarrier::complete_tx::bytes [%0], [%1], %2, [%3];" :: "r"(dst), "l"(src), "r"(bytes), "r"(bar) : "memory");
}
__device__ __forceinline__ void mbar_wait_plain(uint32_t bar, uint32_t parity) {
#pragma unroll 1
  for (int spins = 0; spins < SPIN_LIMIT && !mbar_try(bar, parity); spins++) {}
}

__device__ __forceinline__ void shift_chunk(uint32_t src) {
  uint4 e;
  uint32_t nx;
  asm volatile("ld.shared.v4.u32 {%0,%1,%2,%3}, [%4];" : "=r"(e.x), "=r"(e.y), "=r"(e.z), "=r"(e.w) : "r"(src));
  asm volatile("ld.shared.u32 %0, [%1];" : "=r"(nx) : "r"(src + 16));
  sts128(src + CV_KT_O, make_uint4(__byte_perm(e.x, e.y, 0x5432), __byte_perm(e.y, e.z, 0x5432), __byte_perm(e.z, e.w, 0x5432), __byte_perm(e.w, nx, 0x5432)));
}
__device__ __forceinline__ void kv_block(uint32_t sm, int t0, const uint32_t (&wp)[4], int lane) {
  const int mi = lane >> 3, rev = 7 - (lane & 7);
  uint32_t vv[4], res[4];
  ldsm_x4(sm + CV_V + (t0 >> 9) * (CV_VQ - 8192) + (t0 + 8 * mi + rev) * 16, vv[0], vv[1], vv[2], vv[3]);
#pragma unroll
  for (int i = 0; i < 4; i++) {
    uint32_t k0, k1, k2, k3;
    ldsm_x4(sm + CV_K + (8 + t0 + 8 * i + rev - mi) * 16, k0, k1, k2, k3);
    res[i] = bmul2(badd2(badd2(badd2(bmul2(k3, wp[3]), bmul2(k2, wp[2])), bmul2(k1, wp[1])), bmul2(k0, wp[0])), vv[i]);
  }
  stsm_x4_t(sm + CV_U + (lane & 7) * CV_U_CH + (1 - (mi & 1)) * CV_U_PLANE + (8 + (t0 >> 4) + (mi >> 1)) * 16, res[0], res[1], res[2], res[3]);
}
template <int T0, int NT, int D0, int D1, int J0, int J1>
__device__ __forceinline__ void conv_phase(float (&acc)[16][4], uint32_t abase, uint32_t bbase, uint32_t zero) {
  abase += zero; bbase += zero;
#pragma unroll 1
  for (int dl = 0; dl < 8; dl++) {
    uint32_t bf[NT][2];
#pragma unroll
    for (int j = 0; j < NT; j += 2) ldsm_x4_nv(bbase + (T0 + j) * 128 - dl * 16, bf[j][0], bf[j][1], bf[j + 1][0], bf[j + 1][1]);
    const uint32_t ap = abase + dl * 32;
#pragma unroll
    for (int dh = D0; dh < D1; dh++) {
      const uint32_t a0 = lds32_nv(ap + dh * 256), a1 = lds32_nv(ap + dh * 256 - 16), a2 = lds32_nv(ap + dh * 256 + 16);
      const uint32_t a3 = a0 + zero;
#pragma unroll
      for (int j = 0; j < NT; j++)
        if (dh + T0 + j >= J0 && dh + T0 + j < J1) mma16816(acc[dh + T0 + j], a0, a1, a2, a3, bf[j][0], bf[j][1]);
    }
  }
}
__device__ __forceinline__ uint32_t hidden_zero(uint32_t addr) {
  uint32_t z; asm volatile("ld.volatile.shared.u32 %0, [%1];" : "=r"(z) : "r"(addr) : "memory"); return z;
}
template <int J0, int J1>
__device__ __forceinline__ void stage_y(const float (&acc)[16][4], uint32_t ys, uint32_t bar) {
#pragma unroll
  for (int j = J0; j < J1; j += 2)
    stsm_x4_t(ys + (j >> 2) * CV_VQ + (j & 3) * 128, pack_bf16(acc[j][0], acc[j][1]), pack_bf16(acc[j][2], acc[j][3]),
              pack_bf16(acc[j + 1][0], acc[j + 1][1]), pack_bf16(acc[j + 1][2], acc[j + 1][3]));
  if (J0) {
    __syncwarp();
    mbar_arrive_if(bar, (threadIdx.x & 31) == 0);
  }
}

#define KV_PROMO CU_TENSOR_MAP_L2_PROMOTION_L2_128B
#define STATS_EARLY 0
#define QC1_AT 2
#define QROW_AT 3
constexpr int CV_JS = 8;
enum { M_K, M_V, M_Q, M_W1C, M_W3C, M_X3S, M_X3B, M_H, M_HS, M_X1, M_HID, M_W1, M_W2, M_W3A, M_W3B, M_W4, M_OUT, M_Y, M_COUNT };
struct alignas(64) Params {
  const bf16 *q, *shift_k, *ssm_k, *ssm_d, *w2;
  CUtensorMap m[M_COUNT];
};
__device__ __forceinline__ void prefetch_line(const void* p) { asm volatile("prefetch.global.L2 [%0];" :: "l"(p) : "memory"); }

__device__ __forceinline__ uint32_t tpc_id() { uint32_t smid; asm volatile("mov.u32 %0, %%smid;" : "=r"(smid)); return smid >> 1; }
__device__ __forceinline__ uint32_t pick_role(uint32_t t, int lane) {
  uint32_t gpc = t < 32 ? t & 7 : t < 60 ? 1 + (t - 32) % 7 : t < 62 ? t - 54 : 0;
  const uint32_t d = ld_relaxed(g_clock + 8 + (lane >> 3)) - ld_relaxed(g_clock + (lane & 7)) + 4096;
  const uint32_t match = __ballot_sync(0xffffffffu, d < 8192) & 0x3e3e3e3eu;
  const uint32_t nine = (match | match >> 8 | match >> 16 | match >> 24) & 0xff;
  if (t >= 62) gpc = max(__ffs((match >> (8 * t - 496)) & 0xff) - 1, 0);
  const uint32_t below = (1u << gpc) - 1, pos = (nine >> gpc) & 1 ? __popc(nine & below) : __popc(nine) + __popc(~nine & below & 0xfe);
  uint32_t cls = gpc == 0 ? 0 : min(pos, 7 - pos);
  if (pos > 3 && cls < __popc(nine) && t < 8) cls = 0;
  uint32_t role = 0;
  if (lane == 0) {
#pragma unroll 1
    for (uint32_t k = 0; k < 4; k++) {
      const uint32_t p = (cls + k) & 3, ticket = atomicAdd(&g_role[p], 1u);
      if (ticket < 16) { role = ticket * 4 + p; break; }
    }
  }
  return role;
}

__device__ __forceinline__ void load_k(const Params& pr, uint32_t sm, int x) {
  const uint32_t bar = sm + CV_BAR + 8 * (x ? CB_K1 : CB_K0), bytes = x ? 4096 - CV_KH : CV_KH;
  mbar_expect_tx(bar, 8 * bytes);
#pragma unroll 1
  for (int ch = 0; ch < 8; ch++)
    bulk_load(sm + CV_KT + ch * CV_KT_CH + 32 + x * CV_KH, reinterpret_cast<const char*>(pr.ssm_k) + (blockIdx.x * 8 + ch) * 4096 + x * CV_KH, bytes, bar);
}
__device__ __forceinline__ void load_kv(const Params& pr, uint32_t sm, int y, int barrier) {
  tma_2d(sm + CV_K + 128 + y * 4096, &pr.m[M_K], sm + CV_BAR + 8 * barrier, blockIdx.x * 8, y * 256);
  tma_2d(sm + CV_V + (y >> 1) * CV_VQ + (y & 1) * 4096, &pr.m[M_V], sm + CV_BAR + 8 * barrier, blockIdx.x * 8, y * 256);
}

__device__ __forceinline__ void conv_part(const Params& pr, uint32_t sm, int warp) {
  const int tid = threadIdx.x, lane = tid & 31;
  const int b = blockIdx.x, d0 = b * 8;
  const uint32_t kt = sm + CV_KT, ub = sm + CV_U, bar = sm + CV_BAR;
  const int g = lane >> 2, qd = lane & 3, mi = lane >> 3;
  if (warp == 8) {
    asm volatile("bar.arrive 1, 384;" ::: "memory");
    const uint32_t ep = ld_relaxed(&g_epoch);
    if (elect_one()) {
      load_k(pr, sm, 1);
#pragma unroll 1
      for (int y = 2; y < 8; y++) {
        if (y == 2 * QROW_AT) {
          mbar_expect_tx(bar + 8 * CB_X0, 32768);
#pragma unroll 1
          for (int r = 0; r < 16; r++) bulk_load(sm + CV_X + r * CV_XROW, pr.q + (size_t)(b * 16 + r) * DM, 2048, bar + 8 * CB_X0);
        }
        if (!(y & 1)) mbar_expect_tx(bar + 8 * (CB_Q0 + (y >> 1)), 16384);
        load_kv(pr, sm, y, CB_Q0 + (y >> 1));
      }
#pragma unroll 1
      for (int x = M_Q; x < M_COUNT; x++) asm volatile("prefetch.tensormap [%0];" :: "l"(&pr.m[x]) : "memory");
    }
    __syncwarp();
    const uint32_t role = b & 1 ? 0 : pick_role(tpc_id(), lane);
    if (lane == 0) {
      sts32(sm + SM_EPOCH, ep);
      sts32(sm + SM_ROLE, role);
      asm volatile("fence.release.sync_restrict::shared::cta.cluster;" ::: "memory");
    }
    __syncwarp();
    asm volatile("barrier.cluster.arrive.relaxed.aligned;" ::: "memory");
    auto load_q = [&](int x) {
      mbar_wait_plain(bar + 8 * (CB_U1 + x), 0);
      fence_async_smem();
      if (elect_one()) {
        mbar_expect_tx(bar + 8 * (CB_QC0 + x), 16384);
#pragma unroll 1
        for (int y = 4 * x; y < 4 * x + 4; y++) tma_2d(sm + CV_K + 128 + y * 4096, &pr.m[M_Q], bar + 8 * (CB_QC0 + x), d0, y * 256);
      }
    };
    const int npieces = b < 112 ? 5 : 1;
    const int xr = (mi >> 1) * 8 + (lane & 7);
    const uint32_t xa = sm + CV_X + xr * 64 + (((mi & 1) ^ ((xr >> 1) & 3)) << 4);
    float cs[8][4] = {};
    auto q_stats = [&]() {
      mbar_wait_plain(bar + 8 * CB_QS, 0);
      float sum = 0.f, sq = 0.f;
#pragma unroll
      for (int x = 0; x < 8; x++) { const float2 v = lds_f2(sm + CV_QS + x * 128 + (lane & 15) * 8); sum += v.x; sq += v.y; }
      const float mean = sum * (1.f / DM), rs = rsqrt_fast(fmaxf(fmaf(-mean, mean, sq * (1.f / DM)), 0.f) + LN_EPS);
      const uint32_t rh = pack_bf16(0.f, rs);
      if (lane < 16)
        asm volatile("st.relaxed.gpu.global.v2.b32 [%0], {%1,%2};" :: "l"(g_qstat + b * 16 + lane), "r"(tagged(__uint_as_float(pack_bf16(rs - bf_hi(rh), bf_hi(rh))), ep)),
                     "r"(pack_bf16(-mean * rs, -mean * rs)) : "memory");
      if (lane == 0) { STAMP(47); asm volatile("red.relaxed.gpu.global.add.u32 [%0], 1;" :: "l"(&g_qcnt) : "memory"); }
    };
#pragma unroll 1
    for (int pc = -3; pc < npieces; pc++) {
      if (pc == -2) q_stats();
      if (pc >= 0) {
        mbar_wait_plain(bar + 8 * (CB_X0 + ((pc + 1) & 1)), ((pc + 1) >> 1) & 1);
#pragma unroll 1
        for (int r = 0; r < 16; r += 4) {
#pragma unroll
          for (int x = 0; x < 8; x++) {
            uint32_t a0, a1, a2, a3;
            ldsm_x4_t((xa ^ ((x & 1) << 5)) + ((pc + 1) & 1) * 16384 + (r + (x >> 1)) * 1024, a0, a1, a2, a3);
            mma16816(cs[x], a0, a1, a2, a3, 0x3f803f80u, 0x3f803f80u);
          }
        }
        if (pc == 0 || pc == 4) {
          float t = 0.f;
#pragma unroll
          for (int x = 0; x < 8; x += 2) {
            t += qd & 2 ? (qd & 1 ? cs[x + 1][2] : cs[x + 1][0]) : (qd & 1 ? cs[x][2] : cs[x][0]);
            cs[x][0] = cs[x][2] = cs[x + 1][0] = cs[x + 1][2] = 0.f;
          }
          (pc ? g_cs3 + 32 * b : g_cs1[b & 3] + 32 * (b >> 2))[8 * qd + g] = t;
        }
        __syncwarp();
      }
      if (pc > -3 && pc + 2 < npieces && elect_one()) {
        const uint32_t bx = bar + 8 * (CB_X0 + ((pc + 1) & 1));
        mbar_expect_tx(bx, 16384);
        tma_2d(sm + CV_X + ((pc + 1) & 1) * 16384, &pr.m[pc == -2 ? M_W1C : M_W3C], bx, 32 * (pc == -2 ? b >> 2 : b), 256 * (pc == -2 ? b & 3 : pc + 1));
      }
      if (pc == -3 || pc == min(QC1_AT, npieces - 1)) load_q(pc >= 0);
    }
#pragma unroll 1
    for (int x = 0; x < 4; x++) prefetch_line(reinterpret_cast<const char*>(pr.w2) + (b * 128 + x * 32 + lane) * 128);
    if (lane == 0) STAMP(52);
    return;
  }

  const uint32_t dpair = __ldg(reinterpret_cast<const uint32_t*>(pr.ssm_d + d0 + 2 * qd));
  const int wi = warp - (warp > 8), ti = 32 * wi + lane;
  {
    if (tid < 160) {
      const int x = tid - 128, y = x & 3;
      sts128(tid < 128 ? ub + (tid >> 4) * CV_U_CH + ((tid >> 3) & 1) * CV_U_PLANE + (tid & 7) * 16
                       : y == 3 ? sm + CV_K + (x >> 2) * 16 : kt + (x >> 2) * CV_KT_CH + (y == 2 ? 4128 : y * 16), make_uint4(0, 0, 0, 0));
    }
    uint32_t wp[4];
    {
      const uint4 a = ld_nc_u4(pr.shift_k + (d0 + 2 * qd) * 4);
      wp[0] = __byte_perm(a.x, a.z, 0x5410); wp[1] = __byte_perm(a.x, a.z, 0x7632);
      wp[2] = __byte_perm(a.y, a.w, 0x5410); wp[3] = __byte_perm(a.y, a.w, 0x7632);
    }
    const uint32_t kc = kt + (lane & 7) * CV_KT_CH;
    named_bar(1, 384);
#pragma unroll 1
    for (int x = 0; x < 2; x++) {
      mbar_wait_plain(bar + 8 * (x ? CB_K1 : CB_K0), 0);
#pragma unroll 1
      for (uint32_t a = kc + ((ti >> 3) + (x ? 130 - 32 : 0)) * 16; a < kc + (x ? 258 : 130) * 16; a += x ? 192 : 704) shift_chunk(a);
      __syncwarp();
      mbar_arrive_if(bar + 8 * CB_O1, x && lane == 0);
      if (tid == 0) BSTAMP(54, kt);
#pragma unroll 1
      for (int t0 = warp < 8 ? 32 * wi : 32 * wi + 256; t0 < (x ? SEQ : 512); t0 += x ? 96 : 256) {
        mbar_wait_plain(bar + 8 * (t0 < 256 ? CB_QA : CB_Q0 + (t0 >> 9)), 0);
        if (tid == 0) BSTAMP(56, kt);
        kv_block(sm, t0, wp, lane);
        constexpr int T1 = 128 * CV_JS + 32;
        __syncwarp();
        mbar_arrive_if(bar + 8 * (CB_U1 + (t0 >= T1)), t0 + 96 >= (t0 < T1 ? T1 : SEQ) && lane == 0);
      }
      if (x == 0) named_bar(4, 352);
      if (warp < 8) break;
    }
  }

  if (warp < 8) {
    const int o = 2 * qd - g;
    const uint32_t abase = kt + warp * CV_KT_CH + 32 + ((g & 1) ? CV_KT_O + (o - 1) * 2 : o * 2);
    const uint32_t bbase = ub + warp * CV_U_CH + (mi & 1) * CV_U_PLANE + (8 + (lane >> 4) * 8 + (lane & 7)) * 16;
    const uint32_t ys = sm + CV_V + warp * CV_Y_CH + (mi & 1) * 512 + ((lane >> 4) * 8 + (lane & 7)) * 16;
    auto q_sums = [&]() {
      mbar_wait_plain(bar + 8 * CB_X0, 0);
      float sum[4] = {0.f, 0.f, 0.f, 0.f}, lo[4] = {0.f, 0.f, 0.f, 0.f}, hi[4] = {0.f, 0.f, 0.f, 0.f};
#pragma unroll
      for (int x = 0; x < 8; x++) {
        uint32_t a0, a1, a2, a3;
        ldsm_x4(sm + CV_X + (lane & 15) * CV_XROW + warp * 256 + (lane >> 4) * 16 + x * 32, a0, a1, a2, a3);
        mma16816(sum, a0, a1, a2, a3, 0x3f803f80u, 0x3f803f80u);
        mma16816(lo, a0, a1, a2, a3, a0, a2);
        mma16816(hi, a0, a1, a2, a3, a1, a3);
      }
      if (qd == (g >> 1)) {
        asm volatile("st.shared.v2.f32 [%0], {%1,%2};" :: "r"(sm + CV_QS + warp * 128 + g * 8), "f"(sum[0]), "f"((g & 1) ? lo[1] : lo[0]) : "memory");
        asm volatile("st.shared.v2.f32 [%0], {%1,%2};" :: "r"(sm + CV_QS + warp * 128 + g * 8 + 64), "f"(sum[2]), "f"((g & 1) ? hi[3] : hi[2]) : "memory");
      }
      __syncwarp();
      mbar_arrive_if(bar + 8 * CB_QS, lane == 0);
    };
    if (tid == 0) STAMP(49);
    float acc[16][4];
#pragma unroll
    for (int j = 0; j < 16; j++) { acc[j][0] = acc[j][1] = acc[j][2] = acc[j][3] = 0.f; }
    conv_phase<0, 4, 0, 8, 0, 16>(acc, abase, bbase, hidden_zero(ub));
    stage_y<0, 4>(acc, ys, 0);
    if (tid == 0) STAMP(57);
    if (STATS_EARLY) q_sums();
    mbar_wait_plain(bar + 8 * CB_K1, 0);
    mbar_wait_plain(bar + 8 * CB_O1, 0);
    conv_phase<0, 4, 8, 16, 0, 16>(acc, abase, bbase, hidden_zero(ub));
    if (tid == 0) STAMP(58);
    if (!STATS_EARLY) q_sums();
    mbar_wait_plain(bar + 8 * CB_U1, 0);
    conv_phase<4, CV_JS - 4, 0, CV_JS - 4, 0, CV_JS>(acc, abase, bbase, hidden_zero(ub));
    stage_y<4, CV_JS>(acc, ys, bar + 8 * CB_Y1);
    if (tid == 0) STAMP(59);
    mbar_wait_plain(bar + 8 * CB_U2, 0);
    if (tid == 0) BSTAMP(55, kt);
    conv_phase<4, 12, 0, 12, CV_JS, 16>(acc, abase, bbase, hidden_zero(ub));
    stage_y<CV_JS, 16>(acc, ys, bar + 8 * CB_Y2);
    if (tid == 0) STAMP(50);
    if (tid == 32) STAMP(62);
  }
  {
    const int ch = lane & 7;
    const uint32_t ya = sm + CV_V + ch * CV_Y_CH + (mi & 1) * 512 + (mi >> 1) * 16;
    const uint32_t ua = ub + ch * CV_U_CH + (mi & 1) * CV_U_PLANE + (8 + (mi >> 1)) * 16;
    const uint32_t qa = sm + CV_K + 128 + (16 * (mi >> 1) + 15 - 8 * (mi & 1) - ch) * 16;
    char* xo = reinterpret_cast<char*>(g_x3[0]) + (size_t)b * CB_BYTES + (15 - g) * 16 + qd * 4;
    const uint32_t yo = sm + CV_K + 128 + ((7 - g) * 4 + qd) * 8;
    int budget = SPIN_LIMIT;
    uint32_t ep = 0;
    if (warp > 9) {
      if (tid == 320) STAMP(53);
      ep = ld_relaxed(&g_epoch);
#pragma unroll 1
      while (ld_relaxed(&g_qcnt) - 128 * ep < 128 && --budget > 0) __nanosleep(100);
      if (tid == 320) STAMP(43);
    }
#pragma unroll 1
    for (int part = warp < 8; part < 2; part++) {
      if (warp == 9 && part) break;
      if (warp > 9) {
        uint4 v[8];
#pragma unroll 1
        do {
          uint32_t ok = 1;
#pragma unroll
          for (int y = 0; y < 8; y++) {
            asm volatile("ld.relaxed.gpu.global.v4.u32 {%0,%1,%2,%3}, [%4];" : "=r"(v[y].x), "=r"(v[y].y), "=r"(v[y].z), "=r"(v[y].w)
                         : "l"(g_qstat + 1024 * part + 2 * (tid & 63) + 128 * y) : "memory");
            ok &= both_valid(v[y].x, v[y].z, ep);
          }
          if (__all_sync(0xffffffffu, ok)) break;
        } while (--budget > 0);
#pragma unroll
        for (int y = 0; y < 8; y++) sts128(sm + (part ? CV_ST1 : CV_ST0) + (tid & 63) * 16 + 1024 * y, make_uint4(v[y].x | 1u, v[y].y, v[y].z | 1u, v[y].w));
        __syncwarp();
        mbar_arrive_if(bar + 8 * (CB_ST0 + part), lane == 0);
      }
      mbar_wait_plain(bar + 8 * (CB_ST0 + part), 0);
      mbar_wait_plain(bar + 8 * (CB_QC0 + part), 0);
      if (tid == 288) STAMP(63);
      mbar_wait_plain(bar + 8 * (CB_Y1 + part), 0);
      const uint32_t sa = sm + (part ? CV_ST1 - 8192 : CV_ST0) + (15 - g) * 8;
#pragma unroll 1
      for (int u = part ? 4 * CV_JS + warp - 2 * (warp > 8) : warp - 9; u < (part ? 64 : 4 * CV_JS); u += part ? 10 : 3) {
        uint32_t y[4], uu[4], qq[4];
        ldsm_x4_t(ya + ((u >> 4) * (CV_VQ - 512) + u * 32), y[0], y[1], y[2], y[3]);
        ldsm_x4_t(ua + u * 32, uu[0], uu[1], uu[2], uu[3]);
        ldsm_x4(qa + u * 512, qq[0], qq[1], qq[2], qq[3]);
#pragma unroll
        for (int i = 0; i < 4; i++) {
          const int off = 16 * (i >> 1) - 8 * (i & 1);
          const float2 s = lds_f2(sa + (u * 256 + off * 8));
          y[i] = badd2(y[i], bmul2(uu[i], dpair));
          stg32(xo + (uint32_t)u * 512 + off * 16, gate_pair(qq[i], y[i], __float_as_uint(s.x), __float_as_uint(s.y)));
        }
        asm volatile("st.shared.v2.u32 [%0], {%1,%2};" :: "r"(yo + u * 512), "r"(y[1]), "r"(y[0]) : "memory");
        asm volatile("st.shared.v2.u32 [%0], {%1,%2};" :: "r"(yo + u * 512 + 256), "r"(y[3]), "r"(y[2]) : "memory");
      }
      __syncwarp();
      mbar_arrive_if(bar + 8 * (part ? CB_P2 : CB_P1), lane == 0);
    }
  }
  if (warp == 9) {
    mbar_wait_plain(bar + 8 * CB_P1, 0);
    if (elect_one()) {
      STAMP(61);
      red_release(&g_xcnt[b >> 3]);
      fence_async_smem();
      bulk_store(reinterpret_cast<char*>(g_y) + (size_t)b * CB_BYTES, sm + CV_K + 128, 16384);
      bulk_commit();
      bulk_wait_all();
      mbar_arrive(bar + 8 * CB_YOUT);
    }
  }
  if (tid == 0) STAMP(51);
}

constexpr int NA = 5, A_SLOT = 68 * 128;
constexpr int SM_B = 1024;
constexpr int SM_A = SM_B + 98304;
constexpr int SM_X = SM_A + 2 * NA * A_SLOT;
constexpr int SM_CS1 = CV_END;
constexpr int SM_CS3 = SM_CS1 + 512;
static_assert(SM_X % 1024 == 0 && SM_X + 32768 <= SM_CS1 && SM_B + 2 * 16384 == CV_X && SM_A + NA * A_SLOT == CV_U, "layout");
constexpr int BAR_FULLA = 0, BAR_FULLB = 16, BAR_TURN = 24, BAR_OWN = 26;
constexpr int BAR_EMPTYA = 28, BAR_EMPTYB = BAR_EMPTYA + 18, BAR_CS = BAR_EMPTYB + 9;
constexpr int BAR_PUB = 56;
constexpr int BAR_END = 84;
constexpr int SM_RS = SM_CS3 + 1792;
constexpr int RS_G1 = 2 * 68 * 8;
constexpr int MEGA_SMEM = SM_RS + 2 * RS_G1;
static_assert(MEGA_SMEM <= 232448, "shared memory");
#define LEAD 4
#define Y_AT 6
#define LEAD3 2

template <int N> struct BGeo;
template <> struct BGeo<128> { static constexpr int SLOTS = 6, BYTES = 16384; };
template <> struct BGeo<256> { static constexpr int SLOTS = 3, BYTES = 32768; };
template <> struct BGeo<192> { static constexpr int SLOTS = 4, BYTES = 24576; };
__host__ __device__ constexpr int first_slot(int s) { return s == 0 || s == 2 ? 2 : 0; }
__device__ __forceinline__ bool starts_local(int l, int s) { return s == 2 || s == 1 - l; }
__device__ __forceinline__ int token_shift(int j) { return ((j >> 1) & 1 ? 1 : -1) * (1 + (j >> 2)); }

struct Ctx {
  uint32_t sm;
  uint32_t bar;
  int i, j, r;
  int bid;
  uint32_t ep;
};

struct Pipe {
  uint32_t ko, kp;
  uint32_t po;
  uint32_t a0, a1, ar;
  uint32_t b;
  uint32_t keep;
  uint32_t sh, wide;
  uint32_t turn;
  int budget;
  uint32_t rel;
  bool signals;
  __device__ __forceinline__ void release() const {
    asm volatile("{\n.reg .pred p;\nsetp.ne.b32 p, %1, 0;\n@p mbarrier.arrive.shared::cluster.b64 _, [%0];\n}" :: "r"(rel + po), "r"((uint32_t)signals) : "memory");
  }
  __device__ __forceinline__ void drain() { wg_wait<0>(); release(); po = 64; }
};
__device__ __forceinline__ uint32_t desc_a(const Ctx& c, int off) { return ((c.sm & 0x3FFFFu) >> 4) + 0x400000u + (off >> 4); }
__device__ __forceinline__ uint32_t desc_b(const Ctx& c, int off) { return ((c.sm & 0x3FFFFu) >> 4) + 0x2000000u + ((SM_B + off) >> 4); }

template <int N, bool PRED, bool SHIFT = false, class Extra>
__device__ __forceinline__ void gemm_step(float (&acc)[N / 2], const Ctx& c, int wg, Pipe& p, Extra&& extra) {
  using G = BGeo<N>;
  const uint32_t fa = c.bar + 8 * BAR_FULLA + 64 * wg + p.ko, fb = c.bar + 8 * BAR_FULLB + p.ko;
#pragma unroll 1
  while (true) {
    uint32_t ready;
    asm volatile("{\n.reg .pred p, q;\nmbarrier.try_wait.parity.shared::cta.b64 p, [%1], %3;\nmbarrier.try_wait.parity.shared::cta.b64 q, [%2], %3;\n"
                 "and.pred p, p, q;\nselp.b32 %0, 1, 0, p;\n}" : "=r"(ready) : "r"(fa), "r"(fb), "r"(p.kp) : "memory");
    if (ready || --p.budget <= 0) break;
  }
  wg_fence();
  const uint32_t a = SHIFT ? p.a0 + (p.sh & 3) + (p.wide << 16) : p.a0, ak = SHIFT ? 128 + 2 * p.wide : 128;
  if constexpr (SHIFT) p.sh >>= 2;
  if constexpr (PRED) { Mma<N>::ss(acc, a, p.b, p.keep); p.keep = 1; } else Mma<N>::ss(acc, a, p.b);
#pragma unroll
  for (int kk = 1; kk < 4; kk++) Mma<N>::ss(acc, a + kk * ak, p.b + kk * 128);
  wg_commit();
  extra();
  wg_wait<1>();
  p.release();
  p.po = p.ko;
  p.ko = (p.ko + 8) & 63;
  p.kp ^= p.ko == 0;
  p.a0 = p.a1; p.a1 = p.ar;
  p.ar = p.ar == desc_a(c, SM_A + (NA - 1) * A_SLOT) + wg * NA * (A_SLOT >> 4) ? p.ar - (NA - 1) * (A_SLOT >> 4) : p.ar + (A_SLOT >> 4);
  p.b = p.b == desc_b(c, (G::SLOTS - 1) * G::BYTES) ? desc_b(c, 0) : p.b + (G::BYTES >> 4);
}
template <int N>
__device__ __forceinline__ void gemm_begin(const Ctx& c, int wg, int wq, Pipe& p, int s, bool local) {
  if (local) {
    fence_async_smem();
    named_bar(2 + wg, 128);
    mbar_arrive_if(c.bar + 8 * BAR_FULLA + 64 * wg + 8 * (threadIdx.x & 1), (threadIdx.x & 126) == 96);
    if (wq < 2) {
      mbar_wait(c.bar + 8 * (BAR_EMPTYA + 9 * wg + 8 - NA + wq), p.kp ^ 1, p.budget);
      if (elect_one()) {
        const uint32_t peer = mapa(c.sm, c.r ^ 1), bar = peer + SM_BAR + 8 * (BAR_FULLA + 8 * wg + 2 + wq);
        mbar_expect_tx_cluster(bar, 8192);
        bulk_copy_cluster(peer + (((wq ? p.a1 : p.a0) - desc_a(c, 0)) << 4), c.sm + SM_X + (2 * wg + wq) * 8192, 8192, bar);
      }
      __syncwarp();
    }
  }
  asm volatile("{\n.reg .pred p;\nsetp.ne.b32 p, %3, 0;\nselp.b32 %2, %0, %2, p;\nselp.b32 %0, %4, %0, p;\nselp.b32 %1, %5, %1, p;\n}"
               : "+r"(p.a0), "+r"(p.a1), "+r"(p.ar) : "r"((uint32_t)local), "r"(desc_a(c, SM_X) + wg * 1024), "r"(desc_a(c, SM_X + 8192) + wg * 1024));
  p.b = desc_b(c, first_slot(s) * BGeo<N>::BYTES);
}
template <class Hook>
__device__ __forceinline__ void yield_turn(const Ctx& c, int wg, Pipe& p, Hook&& hook) {
  if (wg == 1) p.drain();
  hook();
  if (wg == 1) mbar_wait(c.bar + 8 * BAR_TURN, p.turn, p.budget);
  p.turn ^= 1;
}
__device__ __forceinline__ void pass_turn(const Ctx& c, bool now) { mbar_arrive_if(c.bar + 8 * BAR_TURN, now && threadIdx.x == 96); }
struct Nop { __device__ __forceinline__ void operator()() const {} };
template <int N, bool PRED, bool SHIFT = false, class Hook>
__device__ __forceinline__ void gemm_steps(float (&acc)[N / 2], const Ctx& c, int wg, Pipe& p, int count, Hook&& hook) {
  constexpr int lead = N == 128 ? LEAD : LEAD3;
  int m = count - lead;
#pragma unroll 1
  do { gemm_step<N, PRED, SHIFT>(acc, c, wg, p, Nop()); } while (--m > 0);
  yield_turn(c, wg, p, hook);
#pragma unroll 1
  for (int n = lead - 1; n >= 0; n--) {
    gemm_step<N, false, SHIFT>(acc, c, wg, p, Nop());
    pass_turn(c, n == 1);
  }
}

__device__ __forceinline__ void put_stat(float2* gdst, float s, float q, bool cond, uint32_t ep) {
  const float m = s * (1.f / 128), v = fmaxf(fmaf(-m, s, q), 0.f);
  asm volatile("{\n.reg .pred p;\nsetp.ne.b32 p, %3, 0;\n@p st.relaxed.gpu.global.v2.b32 [%0], {%1,%2};\n}"
               :: "l"(gdst), "r"(__float_as_uint(m)), "r"(tagged(v, ep)), "r"((uint32_t)cond) : "memory");
}
__device__ __forceinline__ void put_partial(const float (&v)[64], float2* gdst, uint32_t ep) {
  float s[4] = {v[0], v[1], v[2], v[3]}, q[4] = {v[0] * v[0], v[1] * v[1], v[2] * v[2], v[3] * v[3]};
#pragma unroll
  for (int x = 4; x < 64; x++) { s[x & 3] += v[x]; q[x & 3] = fmaf(v[x], v[x], q[x & 3]); }
  const bool odd = threadIdx.x & 1;
  const float s0 = s[0] + s[1], s1 = s[2] + s[3], q0 = q[0] + q[1], q1 = q[2] + q[3];
  float ss = (odd ? s1 : s0) + __shfl_xor_sync(0xffffffffu, odd ? s0 : s1, 1);
  float qq = (odd ? q1 : q0) + __shfl_xor_sync(0xffffffffu, odd ? q0 : q1, 1);
  ss += __shfl_xor_sync(0xffffffffu, ss, 2);
  qq += __shfl_xor_sync(0xffffffffu, qq, 2);
  put_stat(gdst + (odd ? 8 : 0), ss, qq, !(threadIdx.x & 2), ep);
}
struct RowStats {
  float2 p[4];
  __device__ __forceinline__ void load(const float2* r0, const float2* r1) {
#pragma unroll
    for (int x = 0; x < 4; x++)
      asm volatile("ld.relaxed.gpu.global.v2.f32 {%0,%1}, [%2];" : "=f"(p[x].x), "=f"(p[x].y) : "l"((x & 2 ? r1 : r0) + (x & 1) * SEQ) : "memory");
  }
  __device__ __forceinline__ void finish(const float2* r0, const float2* r1, int& budget, float2& s0, float2& s1) {
#pragma unroll 1
    while (!__all_sync(0xffffffffu, both_valid(__float_as_uint(p[0].y), __float_as_uint(p[1].y), 0) & both_valid(__float_as_uint(p[2].y), __float_as_uint(p[3].y), 0) & 1)) {
      if (--budget <= 0) break;
      load(r0, r1);
    }
#pragma unroll
    for (int h = 0; h < 2; h++) {
      const float2 a = p[2 * h], b = p[2 * h + 1];
      float m = a.x + b.x;
      m += __shfl_xor_sync(0xffffffffu, m, 1);
      m += __shfl_xor_sync(0xffffffffu, m, 2);
      m *= 0.125f;
      const float ea = a.x - m, eb = b.x - m;
      float t = fmaf(fmaf(ea, ea, eb * eb), 128.f, a.y + b.y);
      t += __shfl_xor_sync(0xffffffffu, t, 1);
      t += __shfl_xor_sync(0xffffffffu, t, 2);
      (h ? s1 : s0) = make_float2(m, rsqrt_fast(fmaf(t, 1.f / DM, LN_EPS)));
    }
  }
};

__device__ __forceinline__ void emit_panel(const uint32_t* v, char* gp, uint32_t pub) {
#pragma unroll
  for (int t = 0; t < 8; t++) { stg32(gp + t * CB_BYTES, v[2 * t]); stg32(gp + t * CB_BYTES + 128, v[2 * t + 1]); }
  __syncwarp();
  mbar_arrive_if(pub, (threadIdx.x & 31) == 0);
}
template <int NT>
__device__ __forceinline__ void stage_tiles(const uint32_t* v, uint32_t sp) {
#pragma unroll
  for (int t = 0; t < NT; t += 2) stsm_x4(sp + t * 1024, v[2 * t], v[2 * t + 1], v[2 * t + 2], v[2 * t + 3]);
}

__device__ __forceinline__ float late_zero(uint32_t addr) {
  float z; asm volatile("ld.volatile.shared.f32 %0, [%1];" : "=f"(z) : "r"(addr) : "memory"); return z;
}

template <int NT>
__device__ __forceinline__ void fold_tiles(uint32_t* v, const float* acc, const float2* cs_ptr, float2 st0, float2 st1) {
  const float n0 = -st0.x * st0.y, n1 = -st1.x * st1.y;
#pragma unroll
  for (int tile = 0; tile < NT; tile++) {
    const float2 cs = cs_ptr[tile * 4];
    float a = fmaf(acc[4 * tile + 0], st0.y, n0 * cs.x), b = fmaf(acc[4 * tile + 1], st0.y, n0 * cs.y);
    float cc = fmaf(acc[4 * tile + 2], st1.y, n1 * cs.x), d = fmaf(acc[4 * tile + 3], st1.y, n1 * cs.y);
    v[2 * tile] = pack_bf16(gelu_from_half(a), gelu_from_half(b));
    v[2 * tile + 1] = pack_bf16(gelu_from_half(cc), gelu_from_half(d));
  }
}

__device__ __forceinline__ void move_reg(uint32_t& d, uint32_t s) { asm volatile("mov.b32 %0, %1;" : "=r"(d) : "r"(s)); }
__device__ __forceinline__ void move_reg(float& d, float s) { asm volatile("mov.f32 %0, %1;" : "=f"(d) : "f"(s)); }
template <int CH, int LO, int HI, class T, int NR>
__device__ __forceinline__ void pick_group(T (&held)[NR], int idx) {
  if constexpr (HI - LO == 1) {
#pragma unroll
    for (int x = 0; x < CH; x++) move_reg(held[x], held[CH * LO + x]);
  } else {
    constexpr int MID = (LO + HI) / 2;
    if (idx < MID) pick_group<CH, LO, MID>(held, idx); else pick_group<CH, MID, HI>(held, idx);
  }
}
template <int CH>
__device__ __forceinline__ void gelu_chunk(const uint32_t* t, char* gp) {
#pragma unroll
  for (int x = 0; x < CH; x++) stg32(gp + (x >> 1) * CB_BYTES + (x & 1) * 128, gelu_pair_f16(t[x]));
}

#define REG_CONS 216
#define REG_PROD 72
__global__ void __cluster_dims__(2, 1, 1) __launch_bounds__(384, 1)
fused_kernel(const __grid_constant__ Params maps) {
  extern __shared__ __align__(1024) char smem[];
  const int tid = threadIdx.x, lane = tid & 31;
  const int warp = __shfl_sync(0xffffffffu, tid >> 5, 0), wg = warp >> 2;
  if (tid == 0) STAMP(48);
  const uint32_t sm0 = opaque(smem_u32(smem));
  if (elect_one()) {
    if (warp == 8) {
#pragma unroll
      for (int x = 0; x < CB_Q1; x++) mbar_init(sm0 + CV_BAR + 8 * x, 1);
      asm volatile("fence.mbarrier_init.release.cluster;" ::: "memory");
      load_k(maps, sm0, 0);
#pragma unroll
      for (int y = 0; y < 2; y++) {
        mbar_expect_tx(sm0 + CV_BAR + 8 * (CB_QA + y), 8192);
        load_kv(maps, sm0, y, CB_QA + y);
      }
#pragma unroll
      for (int x = CB_Q1; x < CB_ST0; x++) mbar_init(sm0 + CV_BAR + 8 * x, x < CB_QS ? 1 : x == CB_QS ? 8 : 3);
    } else if (warp == 9) {
#pragma unroll
      for (int x = CB_ST0; x < CB_COUNT; x++) mbar_init(sm0 + CV_BAR + 8 * x, x < CB_O1 ? 2 : x < CB_Y1 ? 3 : x < CB_P2 ? 8 : x == CB_P2 ? 10 : x == CB_YOUT ? 5 : x < CB_STAT ? 2 : 1);
    } else if (warp < 2) {
      asm volatile("prefetch.tensormap [%0];" :: "l"(&maps.m[M_K + warp]) : "memory");
    }
#pragma unroll
    for (int x = 0; x < 7; x++) mbar_init(sm0 + SM_BAR + 56 * warp + 8 * x, 1 << wg);
    asm volatile("fence.mbarrier_init.release.cluster;" ::: "memory");
    if (warp == 11) {
      sts32(sm0 + SM_ZERO, 0);
      const uint32_t t = tpc_id();
      if (t < 8 || (t >= 62 && t < 66)) asm volatile("{\n.reg .b32 c;\nmov.u32 c, %%clock;\nst.relaxed.gpu.global.u32 [%0], c;\n}" :: "l"(g_clock + (t < 8 ? t : t - 54)) : "memory");
    }
  }
  static_assert(BAR_END == 84, "start-up work of 12 warps");
  __syncwarp();
  if (warp != 8) asm volatile("barrier.cluster.arrive.relaxed.aligned;" ::: "memory");
  conv_part(maps, sm0, warp);
  __syncwarp();
  asm volatile("barrier.cluster.wait.acquire.aligned;" ::: "memory");
  Ctx c;
  c.sm = sm0;
  c.bar = c.sm + SM_BAR;
  c.r = blockIdx.x & 1;
  {
    uint32_t role;
    asm volatile("ld.shared::cluster.u32 %0, [%1];" : "=r"(role) : "r"(mapa(sm0 + SM_ROLE, 0)) : "memory");
    role = __shfl_sync(0xffffffffu, role, 0);
    c.i = role >> 2; c.j = (role & 3) * 2 + c.r;
    c.bid = c.i * 8 + c.j;
    asm volatile("ld.shared.u32 %0, [%1];" : "=r"(c.ep) : "r"(c.sm + SM_EPOCH) : "memory");
  }

  if (tid == 0) MSTAMP(45);
  if (wg == 2) {
    reg_dealloc<REG_PROD>();
    int budget = SPIN_LIMIT;
    if (warp == 8) {
      const int hh = 16 * c.r + c.i;
      const uint32_t full0 = c.bar + 8 * (BAR_FULLA + c.r * 8), empty0 = c.bar + 8 * (BAR_EMPTYA + c.r * 9), full_peer = mapa(full0, c.r ^ 1);
      const uint32_t ring0 = c.sm + SM_A + c.r * NA * A_SLOT;
      const int nb = hh + (lane & 8 ? (lane & 2) - 1 : 0);
      const uint32_t* lf = g_flag + ((nb >= 0 && nb < 32 ? nb : hh) * 8 + (lane & 7)) * FS;
      const uint32_t* xf = g_xcnt + (hh + ((c.j >> 1) & 1) >= 16 ? 16 : 0) + (lane & 15);
      const uint32_t cb = c.sm + CV_BAR;
      if (lane == 0) mbar_arrive(cb + 8 * CB_XFREE);
      mbar_wait(cb + 8 * CB_Y2, 0, budget);
      if (lane == 0) STAMP(60);
      mbar_wait(cb + 8 * CB_P1, 0, budget);
      fence_async_smem();
      if (lane < 2) mbar_arrive_cluster(mapa(cb + 8 * CB_EARLY, lane));
      int seen = ld_relaxed(xf) - 8 * c.ep;
      mbar_wait(cb + 8 * (CB_EARLY + c.r), 0, budget);
      fence_async_global();
      if (lane == 0) MSTAMP(46);
      uint32_t slot = ring0;
      int k = 0;
#pragma unroll 1
      for (int ph = 0; ph < 10; ph++) {
        const int l = ph >= 5, s = ph - 5 * l;
        const CUtensorMap* m = &maps.m[s == 0 ? M_X3S + l : s == 1 ? M_H + l : s == 4 ? M_HID : M_X1];
        const uint32_t bytes = s == l ? A_SLOT : 8192;
        const bool local = starts_local(l, s);
        const int np = ph == 0 ? 1 : s == 4 ? 7 : 2, cnt = ph == 0 ? 16 : local ? 6 : 8, e0 = ph == 0 ? 2 * (c.j & 6) : (c.j & 6) + (local ? 2 : 0);
        const int need0 = ph == 0 ? 8 : 13 * l + (s == 0 ? 1 : s == 1 ? 3 : s == 4 ? 7 : 5);
        const uint32_t up = ph == 0 ? (c.j & 2 ? 0u : 0xffffu) : ph == 6 ? 0x33u : 0u;
        const uint32_t* fp = ph == 0 ? xf : lf;
        const uint32_t base = ph == 0 ? 8 * c.ep : 32 * c.ep;
        const bool polls = lane < (s == l ? 16 : 8);
        if (ph == 1) seen = 0;
        if (local) {
          k += 4;
          slot += slot >= ring0 + (NA - 2) * A_SLOT ? (2 - NA) * A_SLOT : 2 * A_SLOT;
        }
#pragma unroll 1
        for (int p = 0; p < np; p++) {
          uint32_t ready = __ballot_sync(0xffffffffu, seen >= need0 + p);
          if (ph == 6) ready &= ready >> 8;
#pragma unroll 1
          for (int x = 0; x < cnt; x++) {
            const int e = (e0 + x) & (ph == 0 ? 15 : 7);
            const uint32_t off = 8 * (k & 7);
            mbar_wait(empty0 + 8 * ((k - NA) & 7), ((k - NA) >> 3) & 1, budget);
            if (elect_one()) {
              mbar_expect_tx(full0 + off, bytes);
              mbar_expect_tx_cluster(full_peer + off, bytes);
            }
            if (!((ready >> e) & 1)) {
#pragma unroll 1
              do {
                if (polls) seen = ld_relaxed(fp) - base;
                ready = __ballot_sync(0xffffffffu, seen >= need0 + p);
                if (ph == 6) ready &= ready >> 8;
              } while (!((ready >> e) & 1) && --budget > 0);
              fence_async_global();
            }
            if (elect_one()) tma_2d_mc(slot, m, full0 + off, 128 * hh - 8 * ((up >> e) & 1), (np * e + p) * 8, (uint16_t)3);
            slot += slot == ring0 + (NA - 1) * A_SLOT ? (1 - NA) * A_SLOT : A_SLOT;
            k++;
          }
        }
      }
    } else if (warp == 9) {
      const uint32_t e8 = __funnelshift_r(0x76543210u, 0x76543210u, 4 * (c.j & 6));
      int k = 0;
#pragma unroll 1
      for (int ph = 0; ph < 10; ph++) {
        const int l = ph >= 5, s = ph - 5 * l;
        const uint32_t bytes = s == 2 ? 32768 : s == 3 ? 24576 : 16384, slots = s == 2 ? 3 : s == 3 ? 4 : 6;
        uint32_t dist = s == 2 ? 0x33333345u : s == 3 ? 0x44444333u : s == 4 ? 0x66655544u : 0x66666666u;
        const CUtensorMap* m = &maps.m[M_W1 + s];
        const int np = s == 4 ? 7 : 2;
        const int panel0 = s == 2 ? 7 * c.j : s == 3 ? 7 * c.j + 4 : 2 * c.j;
        const bool local = starts_local(l, s), direct = local || ph == 0;
        uint32_t slot = c.sm + SM_B + first_slot(s) * bytes;
#pragma unroll 1
        for (int o = 0; o < np; o++) {
          uint32_t tab = e8;
          if (local) tab = o ? (e8 >> 24 << 1) | ((e8 << 1) & 0xffffff00u) | 0x11111100u : (0x3210u ^ (c.j * 0x2222u)) | (e8 >> 8 << 17);
          if (ph == 0) tab = (c.j & 2 ? 0xba987654u : 0x76543210u) ^ (((c.j >> 2) ^ o) * 0x88888888u);
          const int mul = direct ? 64 : 64 * np, add = direct ? 0 : 64 * o;
#pragma unroll 1
          for (uint32_t bar = c.bar + 8 * BAR_FULLB; bar < c.bar + 8 * BAR_FULLB + 64; bar += 8) {
            const int last = k - (dist & 15), row = (tab & 15) * mul + add;
            if (last < 0) {
              mbar_wait(c.sm + CV_BAR + 8 * (k < 2 ? CB_XFREE : k < 5 ? CB_EARLY : CB_YOUT), 0, budget);
              fence_async_smem();
            }
            mbar_wait(c.bar + 8 * (BAR_EMPTYB + (last & 7)), (last >> 3) & 1, budget);
            if (elect_one()) {
              mbar_expect_tx(bar, bytes);
              tma_3d(slot, m, bar, 0, row, panel0);
            }
            slot += bytes;
            if (slot == c.sm + SM_B + 98304) slot = c.sm + SM_B;
            dist = __funnelshift_r(dist, slots, 4);
            tab >>= 4;
            k++;
          }
        }
      }
    } else {
      const int w = warp - 10;
      const int row0 = 64 * (16 * w + c.i);
      mbar_wait(c.sm + CV_BAR + 8 * CB_P2, 0, budget);
      if (w == 0) {
        fence_async_smem();
        if (lane < 2) mbar_arrive_cluster(mapa(c.sm + CV_BAR + 8 * CB_LATE, lane));
      } else if (elect_one()) {
        red_release(&g_xcnt[16 + (blockIdx.x >> 3)]);
        mbar_arrive(c.bar + 8 * BAR_REL);
        MSTAMP(44);
      }
      __syncwarp();
      uint32_t* my_flag = g_flag + ((16 * w + c.i) * 8 + c.j) * FS;
#pragma unroll 1
      for (int pc = 1; pc < 26; pc++) {
        const int l = pc >= 13, u = pc - 13 * l;
        if (pc > 1) {
          if (pc == 8) { reinterpret_cast<uint4*>(&g_part[2][c.j][row0])[lane] = make_uint4(0, 0, 0, 0); __syncwarp(); }
          mbar_wait(c.bar + 8 * (BAR_PUB + 13 * w + u), u < 2 ? 0 : l, budget);
          st_release(my_flag, 32 * c.ep + pc + 1);
        }
        float2* part = &g_part[3 * l + (u == 5)][0][0];
#pragma unroll 1
        for (uint32_t jobs = pc == 1 ? 0x453u : u == 5 ? 0x421u : u == 1 ? 4u : 0u; jobs; jobs >>= 4) {
          const int job = jobs & 15;
          if (job < 3) {
            const int r = 32 * (job - 1) + lane;
            float s0 = 0.f, s1 = 0.f, q0 = 0.f, q1 = 0.f;
#pragma unroll 2
            for (int x = 0; x < 16; x++) {
              uint32_t v[4];
              asm volatile("ld.shared.v4.u32 {%0,%1,%2,%3}, [%4];" : "=r"(v[0]), "=r"(v[1]), "=r"(v[2]), "=r"(v[3])
                           : "r"(c.sm + SM_X + w * 16384 + x * 1024 + r * 16) : "memory");
#pragma unroll
              for (int y = 0; y < 4; y++) {
                const float a = bf_lo(v[y]), b = bf_hi(v[y]);
                s0 += a; s1 += b; q0 = fmaf(a, a, q0); q1 = fmaf(b, b, q1);
              }
            }
            put_stat(part + c.j * SEQ + row0 + r, s0 + s1, q0 + q1, true, c.ep);
          } else if (job == 3) {
            if (w == 1) {
              mbar_wait(c.sm + CV_BAR + 8 * CB_YOUT, 0, budget);
              mbar_wait(c.sm + CV_BAR + 8 * CB_EARLY, 0, budget);
              if (lane == 0) red_release(&g_xcnt[32 + (blockIdx.x >> 3)]);
              __syncwarp();
            }
            uint32_t xseen;
#pragma unroll 1
            do {
              asm volatile("ld.acquire.gpu.global.u32 %0, [%1];" : "=r"(xseen) : "l"(g_xcnt + 32 + (lane & 15)) : "memory");
            } while (!__all_sync(0xffffffffu, (int)(xseen - 8 * c.ep) >= 8) && --budget > 0);
            if (w == 0) {
              float4 s = make_float4(0.f, 0.f, 0.f, 0.f);
#pragma unroll
              for (int x = 0; x < 4; x++) {
                const float4 v = __ldcg(reinterpret_cast<const float4*>(&g_cs1[x][c.j * 128]) + lane);
                s.x += v.x; s.y += v.y; s.z += v.z; s.w += v.w;
              }
              reinterpret_cast<float4*>(smem + SM_CS1)[lane] = s;
            } else {
#pragma unroll
              for (int x = 0; x < 4; x++) {
                const int y = min(32 * x + lane, 111);
                const float4 v = __ldcg(reinterpret_cast<const float4*>(g_cs3 + c.j * 448) + y);
                if (x < 2) {
                  uint32_t* d = reinterpret_cast<uint32_t*>(smem + SM_CS3) + (y >> 2) * 8 + (y & 1) * 4 + ((y >> 1) & 1);
                  d[0] = pack_f16(v.x, v.y); d[2] = pack_f16(v.z, v.w);
                } else {
                  reinterpret_cast<float4*>(smem + SM_CS3)[y] = v;
                }
              }
            }
            __syncwarp();
            if (lane == 0) {
              mbar_arrive(c.bar + 8 * BAR_CS);
              if (c.bid == 0 && w == 0) { g_epoch = c.ep + 1; *reinterpret_cast<uint4*>(g_role) = make_uint4(0, 0, 0, 0); }
            }
          } else {
            const int r = job == 4 ? 2 * lane : token_shift(c.j) > 0 ? 64 : -2;
            const float2* src = part + min(max(row0 + r, 0), SEQ - 2);
            float4 v[8];
#pragma unroll 1
            do {
              uint32_t ok = 1;
#pragma unroll
              for (int x = 0; x < 8; x++) {
                asm volatile("ld.relaxed.gpu.global.v4.f32 {%0,%1,%2,%3}, [%4];" : "=f"(v[x].x), "=f"(v[x].y), "=f"(v[x].z), "=f"(v[x].w) : "l"(src + x * SEQ) : "memory");
                ok &= both_valid(__float_as_uint(v[x].y), __float_as_uint(v[x].w), c.ep);
              }
              if (__all_sync(0xffffffffu, ok)) break;
            } while (--budget > 0);
            float ma = 0.f, mb = 0.f, ta = 0.f, tb = 0.f;
#pragma unroll
            for (int x = 0; x < 8; x++) { ma += v[x].x; mb += v[x].z; }
            ma *= 0.125f; mb *= 0.125f;
#pragma unroll
            for (int x = 0; x < 8; x++) {
              const float ea = v[x].x - ma, eb = v[x].z - mb;
              ta += fmaf(128.f * ea, ea, __uint_as_float(__float_as_uint(v[x].y) | 1u));
              tb += fmaf(128.f * eb, eb, __uint_as_float(__float_as_uint(v[x].w) | 1u));
            }
            ta *= 1.f / DM; tb *= 1.f / DM;
            const float ra = rsqrt_fast(ta + LN_EPS), rb = rsqrt_fast(tb + LN_EPS);
            *reinterpret_cast<float4*>(smem + SM_RS + (68 * w + 2 + r) * 8) = make_float4(ma, ra, mb, rb);
            const float in = (uint32_t)(row0 + r) < SEQ ? 0.5f : 0.f;
            *reinterpret_cast<float4*>(smem + SM_RS + RS_G1 + (68 * w + 2 + r) * 8) =
                make_float4(ma, in * ra * rsqrt_fast(fmaf(ta * ra, ra, LN_EPS)), mb, in * rb * rsqrt_fast(fmaf(tb * rb, rb, LN_EPS)));
            __syncwarp();
            if (job == 4 && lane == 0) mbar_arrive(c.sm + CV_BAR + 8 * (CB_STAT + w));
          }
        }
        if (pc == Y_AT) {
          if (elect_one()) {
            const uint32_t bar = c.bar + 8 * (BAR_OWN + w);
            fence_async_global();
            fence_async_smem();
            mbar_expect_tx(bar, 16384);
            tma_2d(c.sm + SM_X + w * 16384, &maps.m[M_Y], bar, 2 * row0, 16 * c.j);
            tma_2d(c.sm + SM_X + w * 16384 + 8192, &maps.m[M_Y], bar, 2 * row0, 16 * c.j + 8);
          }
          __syncwarp();
        }
      }
    }
    cluster_exit_barrier();
  } else {
    reg_alloc<REG_CONS>();
#define WSTAMP(idx) do {} while (0)
    const int t = tid & 127, g = lane >> 2, qd = lane & 3;
    const int wrow = 64 * (16 * wg + c.i) + (t >> 5) * 16, row = wrow + g;
    const uint32_t frag = row * 16 + qd * 4 + c.j * 16 * CB_BYTES;
    const uint32_t stage = c.sm + SM_X + wg * 16384 + (lane >> 4) * 1024 + ((t >> 5) * 16 + (lane & 15)) * 16;
    const uint32_t pub = c.bar + 8 * (BAR_PUB + 13 * wg);
    const uint32_t rstat = c.sm + SM_RS + (68 * wg + 2 + (t >> 5) * 16 + g) * 8;
    Pipe p;
    p.ko = 0; p.kp = 0; p.po = 64; p.turn = 0; p.budget = SPIN_LIMIT;
    p.a0 = desc_a(c, SM_A) + wg * NA * (A_SLOT >> 4); p.a1 = p.a0 + (A_SLOT >> 4); p.ar = p.a1 + (A_SLOT >> 4);
    p.signals = t == 0 || t == 32 || t == 64;
    p.rel = mapa(c.bar + 8 * (t == 64 ? BAR_EMPTYB : BAR_EMPTYA + wg * 9), t == 32 ? c.r ^ 1 : c.r);
    auto fence_sched = [&]() { mbar_wait(c.bar + 8 * BAR_CS, 0, p.budget); };
    uint32_t x3[32];
    float acc[64];
#pragma unroll
    for (int x = 0; x < 64; x++) acc[x] = 0.f;
    pin(acc);
    const uint32_t own = opaque(c.sm + SM_A + (wg * NA + 2 * c.r) * A_SLOT + (lane >> 4) * 1088 + ((c.j & 2 ? 0 : 4) + (t >> 5) * 16 + (lane & 15)) * 16);
    WSTAMP(0);
    if (wg == 1) {
      mbar_wait(c.bar + 8 * BAR_REL, 0, p.budget);
#pragma unroll 2
      for (int x = 0; x < 8; x++)
        reinterpret_cast<uint4*>(g_y)[blockIdx.x * 2048 + 1024 + x * 128 + t] = reinterpret_cast<const uint4*>(smem + CV_K + 128 + 16384)[x * 128 + t];
      __syncwarp();
      mbar_arrive_if(c.sm + CV_BAR + 8 * CB_YOUT, lane == 0);
    }
    {
      mbar_wait(c.bar + 8 * (BAR_FULLA + 8 * wg + 2 * c.r), 0, p.budget);
      mbar_wait(c.bar + 8 * (BAR_FULLA + 8 * wg + 2 * c.r + 1), 0, p.budget);
#pragma unroll
      for (int x = 0; x < 32; x += 4) ldsm_x4(own + x * 544, x3[x], x3[x + 1], x3[x + 2], x3[x + 3]);
    }
    const uint32_t sh_g1 = opaque((token_shift(c.j) & 3) * 0x55555555u), sh_g2 = opaque(__funnelshift_r(0xaa5faa5fu, 0xaa5faa5fu, 2 * (c.j & 6)));
#pragma unroll 1
    for (int ph = 0; ph < 6; ph++) {
      const int l = ph >= 3, s = ph - 3 * l;
      p.keep = s;
      p.wide = s == l ? 4 : 0;
      p.sh = s == l ? (l ? sh_g2 : sh_g1) : 0;
      if (s < 2) {
        gemm_begin<128>(c, wg, warp & 3, p, s, s != l);
        if (s == 0) {
          float sum[2][4] = {}, lo[2][4] = {}, hi[2][4] = {};
#pragma unroll
          for (int x = 0; x < 32; x += 4) {
            mma16816(sum[x >> 4], x3[x], x3[x + 1], x3[x + 2], x3[x + 3], 0x3f803f80u, 0x3f803f80u);
            mma16816(lo[x >> 4], x3[x], x3[x + 1], x3[x + 2], x3[x + 3], x3[x], x3[x + 2]);
            mma16816(hi[x >> 4], x3[x], x3[x + 1], x3[x + 2], x3[x + 3], x3[x + 1], x3[x + 3]);
          }
          put_stat(&g_part[3 * l][c.j][row], sum[0][0] + sum[1][0], (g & 1) ? lo[0][1] + lo[1][1] : lo[0][0] + lo[1][0], qd == (g >> 1), c.ep);
          put_stat(&g_part[3 * l][c.j][row + 8], sum[0][2] + sum[1][2], (g & 1) ? hi[0][3] + hi[1][3] : hi[0][2] + hi[1][2], qd == (g >> 1), c.ep);
          WSTAMP(1 + 16 * l);
        }
      } else {
        char* hp = reinterpret_cast<char*>(g_hid) + frag + c.j * 40 * CB_BYTES;
        uint32_t held[64];
        float acc3[128];
        gemm_step<256, true>(acc3, c, wg, p, Nop());
        float2 s0 = make_float2(0.f, 0.f), s1 = s0;
        gemm_steps<256, false>(acc3, c, wg, p, 15, [&]() {
          mbar_wait(c.sm + CV_BAR + 8 * (CB_STAT + wg), 1, p.budget);
          s0 = lds_f2(rstat); s1 = lds_f2(rstat + 64);
          s0.y *= 0.5f; s1.y *= 0.5f;
        });
        p.drain();
        WSTAMP(6 + 16 * l);
#pragma unroll
        for (int x = 0; x < 64; x++) held[x] = pack_f16(acc3[2 * x] * ((x & 1) ? s1.y : s0.y), acc3[2 * x + 1] * ((x & 1) ? s1.y : s0.y));
        const uint32_t n0 = pack_f16(-s0.x * s0.y, -s0.x * s0.y), n1 = pack_f16(-s1.x * s1.y, -s1.x * s1.y);
        float accb[96];
#pragma unroll
        for (int x = 0; x < 24; x++) {
          const float2 cs = (reinterpret_cast<const float2*>(smem + SM_CS3 + 1024) + qd)[4 * x];
          accb[4 * x] = -s0.x * cs.x; accb[4 * x + 1] = -s0.x * cs.y; accb[4 * x + 2] = -s1.x * cs.x; accb[4 * x + 3] = -s1.x * cs.y;
        }
        pin(accb);
        WSTAMP(7 + 16 * l);
        gemm_begin<192>(c, wg, warp & 3, p, 3, false);
#pragma unroll 1
        for (int pn = 0; pn < 4; pn++) {
#pragma unroll
          for (int u = 0; u < 4; u++)
            gemm_step<192, false>(accb, c, wg, p, [&]() {
              const uint2 cs = reinterpret_cast<const uint2*>(smem + SM_CS3)[16 * pn + 4 * u + qd];
              const uint32_t h[4] = {hfma2(cs.x, n0, held[4 * u]), hfma2(cs.x, n1, held[4 * u + 1]), hfma2(cs.y, n0, held[4 * u + 2]), hfma2(cs.y, n1, held[4 * u + 3])};
              gelu_chunk<4>(h, hp + 2 * u * CB_BYTES);
            });
          hp += 8 * CB_BYTES;
          __syncwarp();
          mbar_arrive_if(pub + 8 * (6 + pn), lane == 0);
          if (pn < 3) pick_group<16, 1, 4>(held, pn + 1);
        }
        WSTAMP(8 + 16 * l);
#pragma unroll
        for (int x = 0; x < 32; x++) { acc[2 * x] = bf_lo(x3[x]); acc[2 * x + 1] = bf_hi(x3[x]); }
        pin(acc);
        WSTAMP(9 + 16 * l);
        gemm_begin<128>(c, wg, warp & 3, p, 4, false);
        gemm_step<128, false>(acc, c, wg, p, Nop());
        pin(accb);
#pragma unroll 1
        for (int hpn = 0; hpn < 6; hpn++) {
#pragma unroll
          for (int u = 0; u < 4; u++)
            gemm_step<128, false>(acc, c, wg, p, [&]() {
              const uint32_t h[2] = {pack_f16(accb[4 * u] * s0.y, accb[4 * u + 1] * s0.y), pack_f16(accb[4 * u + 2] * s1.y, accb[4 * u + 3] * s1.y)};
              gelu_chunk<2>(h, hp + u * CB_BYTES);
            });
          hp += 4 * CB_BYTES;
          __syncwarp();
          mbar_arrive_if(pub + 8 * (10 + (hpn >> 1)), (hpn & 1) && lane == 0);
          if (hpn < 5) pick_group<16, 1, 6>(accb, hpn + 1);
        }
        WSTAMP(12 + 16 * l);
      }
      gemm_steps<128, true, true>(acc, c, wg, p, s == 2 ? 31 : 16, Nop());
      const uint32_t z = hidden_zero(c.sm + SM_ZERO), stg = stage + z;
      char* gp = reinterpret_cast<char*>(s == 0 ? g_h : s == 1 ? g_x1 : g_x3[1]) + (frag + z);
      float2 s0, s1;
      if (s == 0) {
        mbar_wait(c.sm + CV_BAR + 8 * (CB_STAT + wg), 0, p.budget);
        const uint32_t ra = rstat + RS_G1 + (l == 0 ? 8 * token_shift(c.j) : 0);
        s0 = lds_f2(ra); s1 = lds_f2(ra + 64);
        fence_sched();
        p.drain();
        WSTAMP(2 + 16 * l);
#pragma unroll
        for (int pn = 0; pn < 2; pn++) {
          uint32_t v[16];
          if (pn == 0) {
            fold_tiles<4>(v, acc, reinterpret_cast<const float2*>(smem + SM_CS1) + qd, s0, s1);
#pragma unroll
            for (int x = 0; x < 8; x++) stg32(gp + (x >> 1) * CB_BYTES + (x & 1) * 128, v[x]);
            fence_sched();
            fold_tiles<4>(v + 8, acc + 16, reinterpret_cast<const float2*>(smem + SM_CS1) + qd + 16, s0, s1);
#pragma unroll
            for (int x = 8; x < 16; x++) stg32(gp + (x >> 1) * CB_BYTES + (x & 1) * 128, v[x]);
            __syncwarp();
            mbar_arrive_if(pub + 8 * 2, lane == 0);
          } else {
            fold_tiles<8>(v, acc + 32, reinterpret_cast<const float2*>(smem + SM_CS1) + qd + 32, s0, s1);
            emit_panel(v, gp + 8 * CB_BYTES, pub + 8 * 3);
          }
          if (l == 0) stage_tiles<8>(v, stg + pn * 8192);
        }
        s0 = lds_f2(rstat); s1 = lds_f2(rstat + 64);
        const float nb0 = -s0.x * s0.y, nb1 = -s1.x * s1.y;
#pragma unroll
        for (int x = 0; x < 32; x++) {
          acc[2 * x] = fmaf(bf_lo(x3[x]), (x & 1) ? s1.y : s0.y, (x & 1) ? nb1 : nb0);
          acc[2 * x + 1] = fmaf(bf_hi(x3[x]), (x & 1) ? s1.y : s0.y, (x & 1) ? nb1 : nb0);
        }
        WSTAMP(3 + 16 * l);
      } else if (s == 1) {
        fence_sched();
        p.drain();
        WSTAMP(4 + 16 * l);
        uint32_t v[32];
#pragma unroll
        for (int x = 0; x < 32; x++) v[x] = pack_bf16(acc[2 * x], acc[2 * x + 1]);
        emit_panel(v, gp, pub + 8 * 4);
        stage_tiles<16>(v, stg);
        gemm_begin<256>(c, wg, warp & 3, p, 2, true);
        emit_panel(v + 16, gp + 8 * CB_BYTES, pub + 8 * 5);
#pragma unroll
        for (int x = 0; x < 32; x++) x3[x] = badd2(x3[x], v[x]);
        WSTAMP(5 + 16 * l);
      } else if (l == 0) {
        float2* mine = &g_part[2][c.j][row + z];
        const float2* sp = &g_part[2][2 * qd][row + z];
        fence_sched();
        p.drain();
        WSTAMP(10);
        put_partial(acc, mine, 0);
        WSTAMP(11);
        RowStats rs;
        rs.load(sp, sp + 8);
        float yf[64];
        mbar_wait(c.bar + 8 * (BAR_OWN + wg), 0, p.budget);
#pragma unroll
        for (int x = 0; x < 16; x++) {
          uint32_t y0, y1;
          asm volatile("ld.shared.v2.u32 {%0,%1}, [%2];" : "=r"(y0), "=r"(y1) : "r"(c.sm + SM_X + wg * 16384 + x * 1024 + t * 8) : "memory");
          yf[4 * x] = bf_lo(y0); yf[4 * x + 1] = bf_hi(y0); yf[4 * x + 2] = bf_lo(y1); yf[4 * x + 3] = bf_hi(y1);
        }
        pin(yf);
        rs.finish(sp, sp + 8, p.budget, s0, s1);
        WSTAMP(13);
        float nb0 = -s0.x * s0.y, nb1 = -s1.x * s1.y;
#pragma unroll
        for (int pn = 0; pn < 2; pn++) {
          if (pn == 1) { const float z = late_zero(c.sm + SM_ZERO); nb0 += z; nb1 += z; }
#pragma unroll
          for (int x = 16 * pn; x < 16 * pn + 16; x++) {
            const float r = (x & 1) ? s1.y : s0.y, nb = (x & 1) ? nb1 : nb0;
            x3[x] = pack_bf16(fmaf(fmaf(acc[2 * x], r, nb), yf[2 * x], acc[2 * x]), fmaf(fmaf(acc[2 * x + 1], r, nb), yf[2 * x + 1], acc[2 * x + 1]));
          }
          if (pn == 1) stage_tiles<16>(x3, stg);
          emit_panel(x3 + 16 * pn, gp + pn * 8 * CB_BYTES, pub + 8 * pn);
        }
      } else {
        const uint32_t ob = c.sm + SM_X + warp * 4096, oa = ob + (lane & 15) * 128 + (((lane >> 4) ^ (lane & 7)) << 4) + z;
        fence_sched();
        p.drain();
        WSTAMP(26);
#pragma unroll
        for (int pn = 0; pn < 2; pn++) {
#pragma unroll
          for (int x = 0; x < 8; x += 2) {
            const float* a = acc + 32 * pn + 4 * x;
            stsm_x4((oa ^ (x << 4)) + pn * 2048, pack_bf16(a[0], a[1]), pack_bf16(a[2], a[3]), pack_bf16(a[4], a[5]), pack_bf16(a[6], a[7]));
          }
          fence_async_smem();
          __syncwarp();
          if (elect_one()) {
            tma_store_2d(&maps.m[M_OUT], ob + pn * 2048, c.j * 128 + 64 * pn, 64 * (16 * wg + c.i) + 16 * (warp & 3));
            if (pn == 1) {
              bulk_commit();
              asm volatile("cp.async.bulk.wait_group.read 0;" ::: "memory");
            }
          }
        }
        __syncwarp();
      }
    }
    WSTAMP(27);
    cluster_exit_barrier();
    WSTAMP(30);
  }
}

typedef CUresult (*EncodeFn)(CUtensorMap*, CUtensorMapDataType, cuuint32_t, void*, const cuuint64_t*, const cuuint64_t*, const cuuint32_t*,
                             const cuuint32_t*, CUtensorMapInterleave, CUtensorMapSwizzle, CUtensorMapL2promotion, CUtensorMapFloatOOBfill);

void encode(EncodeFn fn, CUtensorMap* m, CUtensorMapDataType type, const void* ptr, int rank, const cuuint64_t* dims, const cuuint64_t* strides,
            const cuuint32_t* box, CUtensorMapSwizzle swizzle, CUtensorMapL2promotion promo = CU_TENSOR_MAP_L2_PROMOTION_L2_128B) {
  const cuuint32_t es[3] = {1, 1, 1};
  fn(m, type, rank, const_cast<void*>(ptr), dims, strides, box, es, CU_TENSOR_MAP_INTERLEAVE_NONE, swizzle, promo, CU_TENSOR_MAP_FLOAT_OOB_FILL_NONE);
}
void map_act(EncodeFn fn, CUtensorMap* m, const void* ptr, int cols, int rows = 64) {
  const cuuint64_t dims[2] = {(cuuint64_t)SEQ * 2, (cuuint64_t)cols / 8}, st[1] = {(cuuint64_t)CB_BYTES};
  const cuuint32_t box[2] = {(cuuint32_t)rows * 2, 8};
  encode(fn, m, CU_TENSOR_MAP_DATA_TYPE_UINT64, ptr, 2, dims, st, box, CU_TENSOR_MAP_SWIZZLE_NONE);
}
void map_rows(EncodeFn fn, CUtensorMap* m, const void* ptr, int rows, int cols, int box_rows, int box_cols, CUtensorMapSwizzle swizzle,
              CUtensorMapL2promotion promo) {
  const cuuint64_t dims[2] = {(cuuint64_t)cols, (cuuint64_t)rows}, st[1] = {(cuuint64_t)cols * 2};
  const cuuint32_t box[2] = {(cuuint32_t)box_cols, (cuuint32_t)box_rows};
  encode(fn, m, CU_TENSOR_MAP_DATA_TYPE_BFLOAT16, ptr, 2, dims, st, box, swizzle, promo);
}
void map_w(EncodeFn fn, CUtensorMap* m, const void* ptr, int rows, int cols, int panels) {
  const cuuint64_t dims[3] = {64, (cuuint64_t)rows, (cuuint64_t)cols / 64}, st[2] = {(cuuint64_t)cols * 2, 128};
  const cuuint32_t box[3] = {64, 64, (cuuint32_t)panels};
  encode(fn, m, CU_TENSOR_MAP_DATA_TYPE_BFLOAT16, ptr, 3, dims, st, box, CU_TENSOR_MAP_SWIZZLE_128B);
}

}

extern "C" void kernel_launch(void* const* d_in, const int* in_sizes, int n_in, void* d_out, int out_size) {
  (void)in_sizes; (void)n_in; (void)out_size;
  const bf16* q = (const bf16*)d_in[0];
  const bf16* k = (const bf16*)d_in[1];
  const bf16* v = (const bf16*)d_in[2];
  const bf16* shift_k = (const bf16*)d_in[3];
  const bf16* ssm_k = (const bf16*)d_in[4];
  const bf16* ssm_d = (const bf16*)d_in[5];
  const bf16* w1 = (const bf16*)d_in[7];
  const bf16* w2 = (const bf16*)d_in[8];
  const bf16* w3 = (const bf16*)d_in[9];
  const bf16* w4 = (const bf16*)d_in[10];

  static EncodeFn fn = nullptr;
  static void *p_x3, *p_h, *p_x1, *p_hid, *p_y;
  if (!fn) {
    void* p = nullptr;
    cudaDriverEntryPointQueryResult qr;
    cudaGetDriverEntryPoint("cuTensorMapEncodeTiled", &p, cudaEnableDefault, &qr);
    fn = (EncodeFn)p;
    cudaGetSymbolAddress(&p_x3, g_x3);
    cudaGetSymbolAddress(&p_h, g_h);
    cudaGetSymbolAddress(&p_x1, g_x1);
    cudaGetSymbolAddress(&p_hid, g_hid);
    cudaGetSymbolAddress(&p_y, g_y);
    cudaFuncSetAttribute(fused_kernel, cudaFuncAttributeMaxDynamicSharedMemorySize, MEGA_SMEM);
  }
  Params maps;
  map_act(fn, &maps.m[M_X3B], (const bf16*)p_x3 + SEQ * DM, DM);
  map_act(fn, &maps.m[M_X3S], p_x3, DM, 68);
  map_act(fn, &maps.m[M_H], p_h, DM);
  map_act(fn, &maps.m[M_HS], p_h, DM, 68);
  map_act(fn, &maps.m[M_X1], p_x1, DM);
  map_act(fn, &maps.m[M_HID], p_hid, FF);
  map_act(fn, &maps.m[M_Y], p_y, DM);
  map_rows(fn, &maps.m[M_OUT], d_out, SEQ, DM, 16, 64, CU_TENSOR_MAP_SWIZZLE_128B, CU_TENSOR_MAP_L2_PROMOTION_L2_128B);
  map_w(fn, &maps.m[M_W1], w1, DM, DM, 2);
  map_w(fn, &maps.m[M_W2], w2, DM, DM, 2);
  map_w(fn, &maps.m[M_W3A], w3, DM, FF, 4);
  map_w(fn, &maps.m[M_W3B], w3, DM, FF, 3);
  map_w(fn, &maps.m[M_W4], w4, FF, DM, 2);

  map_rows(fn, &maps.m[M_K], k, SEQ, DM, 256, 8, CU_TENSOR_MAP_SWIZZLE_NONE, KV_PROMO);
  map_rows(fn, &maps.m[M_V], v, SEQ, DM, 256, 8, CU_TENSOR_MAP_SWIZZLE_NONE, KV_PROMO);
  map_rows(fn, &maps.m[M_Q], q, SEQ, DM, 256, 8, CU_TENSOR_MAP_SWIZZLE_NONE, KV_PROMO);
  map_rows(fn, &maps.m[M_W1C], w1, DM, DM, 256, 32, CU_TENSOR_MAP_SWIZZLE_64B, CU_TENSOR_MAP_L2_PROMOTION_L2_128B);
  map_rows(fn, &maps.m[M_W3C], w3, DM, FF, 256, 32, CU_TENSOR_MAP_SWIZZLE_64B, CU_TENSOR_MAP_L2_PROMOTION_L2_128B);
  maps.q = q; maps.shift_k = shift_k; maps.ssm_k = ssm_k; maps.ssm_d = ssm_d; maps.w2 = w2;
  fused_kernel<<<128, 384, MEGA_SMEM, cudaStreamPerThread>>>(maps);
}
```

```cpp
#include <cuda_runtime.h>
#include <cuda_bf16.h>
#include <cuda.h>
#include <stdint.h>

namespace {

typedef __nv_bfloat16 bf16;
constexpr int SEQ = 2048, DM = 1024, FF = 3584;
constexpr float LN_EPS = 1e-5f;

constexpr int CB_BYTES = SEQ * 16;
__device__ __align__(1024) bf16 g_x3[2][SEQ * DM];
__device__ __align__(1024) bf16 g_h[SEQ * DM];
__device__ __align__(1024) bf16 g_x1[SEQ * DM];
__device__ __align__(1024) bf16 g_hid[SEQ * FF];
__device__ __align__(1024) bf16 g_y[SEQ * DM];
__device__ __align__(128) float g_cs1[4][DM];
__device__ __align__(128) float g_cs3[FF];
__device__ __align__(128) uint32_t g_epoch;
__device__ __align__(128) float2 g_part[5][8][SEQ];
__device__ __align__(128) float2 g_qstat[SEQ];
__device__ __align__(128) uint32_t g_qcnt;
__device__ __align__(128) uint32_t g_xcnt[48];
constexpr int FS = 8;
__device__ __align__(128) uint32_t g_flag[32 * 8 * FS];
__device__ __align__(128) uint32_t g_role[16];

__device__ __forceinline__ uint32_t smem_u32(const void* p) { return (uint32_t)__cvta_generic_to_shared(p); }
__device__ __forceinline__ uint32_t opaque(uint32_t x) { uint32_t y; asm volatile("mov.u32 %0, %1;" : "=r"(y) : "r"(x)); return y; }
__device__ __forceinline__ void mbar_init(uint32_t bar, uint32_t cnt) { asm volatile("mbarrier.init.shared::cta.b64 [%0], %1;" :: "r"(bar), "r"(cnt)); }
__device__ __forceinline__ void mbar_expect_tx(uint32_t bar, uint32_t bytes) {
  asm volatile("mbarrier.arrive.expect_tx.shared::cta.b64 _, [%0], %1;" :: "r"(bar), "r"(bytes) : "memory");
}
__device__ __forceinline__ void mbar_expect_tx_cluster(uint32_t bar, uint32_t bytes) {
  asm volatile("mbarrier.arrive.expect_tx.shared::cluster.b64 _, [%0], %1;" :: "r"(bar), "r"(bytes) : "memory");
}
__device__ __forceinline__ void mbar_arrive_cluster(uint32_t bar) { asm volatile("mbarrier.arrive.shared::cluster.b64 _, [%0];" :: "r"(bar) : "memory"); }
__device__ __forceinline__ void mbar_arrive(uint32_t bar) { asm volatile("mbarrier.arrive.shared::cta.b64 _, [%0];" :: "r"(bar) : "memory"); }
__device__ __forceinline__ void mbar_arrive_if(uint32_t bar, bool cond) {
  asm volatile("{\n.reg .pred p;\nsetp.ne.b32 p, %1, 0;\n@p mbarrier.arrive.shared::cta.b64 _, [%0];\n}" :: "r"(bar), "r"((uint32_t)cond) : "memory");
}
constexpr int SPIN_LIMIT = 1 << 16;
__device__ __forceinline__ bool mbar_try(uint32_t bar, uint32_t parity) {
  uint32_t done;
  asm volatile("{\n.reg .pred p;\nmbarrier.try_wait.parity.shared::cta.b64 p, [%1], %2;\nselp.b32 %0, 1, 0, p;\n}"
               : "=r"(done) : "r"(bar), "r"(parity) : "memory");
  return done != 0;
}
__device__ __forceinline__ void mbar_wait(uint32_t bar, uint32_t parity, int& budget) {
#pragma unroll 1
  while (!mbar_try(bar, parity)) { if (--budget <= 0) break; }
}
__device__ __forceinline__ bool elect_one() {
  uint32_t p;
  asm volatile("{\n.reg .pred P;\nelect.sync _|P, 0xffffffff;\nselp.b32 %0, 1, 0, P;\n}" : "=r"(p));
  return p != 0;
}
__device__ __forceinline__ void fence_async_smem() { asm volatile("fence.proxy.async.shared::cta;" ::: "memory"); }
__device__ __forceinline__ void fence_async_global() { asm volatile("fence.proxy.async.global;" ::: "memory"); }
__device__ __forceinline__ void named_bar(int id, int n) { asm volatile("bar.sync %0, %1;" :: "r"(id), "r"(n) : "memory"); }
__device__ __forceinline__ uint4 ld_nc_u4(const void* p) {
  uint4 v; asm volatile("ld.global.nc.L1::no_allocate.v4.u32 {%0,%1,%2,%3}, [%4];" : "=r"(v.x), "=r"(v.y), "=r"(v.z), "=r"(v.w) : "l"(p)); return v;
}
__device__ __forceinline__ void tma_2d_mc(uint32_t dst, const CUtensorMap* m, uint32_t bar, int c0, int c1, uint16_t mask) {
  asm volatile("cp.async.bulk.tensor.2d.shared::cluster.global.mbarrier::complete_tx::bytes.multicast::cluster [%0], [%1, {%3, %4}], [%2], %5;"
               :: "r"(dst), "l"(m), "r"(bar), "r"(c0), "r"(c1), "h"(mask) : "memory");
}
__device__ __forceinline__ void tma_2d(uint32_t dst, const CUtensorMap* m, uint32_t bar, int c0, int c1) {
  asm volatile("cp.async.bulk.tensor.2d.shared::cluster.global.mbarrier::complete_tx::bytes [%0], [%1, {%3, %4}], [%2];"
               :: "r"(dst), "l"(m), "r"(bar), "r"(c0), "r"(c1) : "memory");
}
__device__ __forceinline__ void bulk_copy_cluster(uint32_t dst, uint32_t src, uint32_t bytes, uint32_t bar) {
  asm volatile("cp.async.bulk.shared::cluster.shared::cta.mbarrier::complete_tx::bytes [%0], [%1], %2, [%3];"
               :: "r"(dst), "r"(src), "r"(bytes), "r"(bar) : "memory");
}
__device__ __forceinline__ uint32_t mapa(uint32_t addr, uint32_t cta) {
  uint32_t r; asm volatile("mapa.shared::cluster.u32 %0, %1, %2;" : "=r"(r) : "r"(addr), "r"(cta)); return r;
}
__device__ __forceinline__ void bulk_store(void* dst, uint32_t src, uint32_t bytes) {
  asm volatile("cp.async.bulk.global.shared::cta.bulk_group [%0], [%1], %2;" :: "l"(dst), "r"(src), "r"(bytes) : "memory");
}
__device__ __forceinline__ void tma_3d(uint32_t dst, const CUtensorMap* m, uint32_t bar, int c0, int c1, int c2) {
  asm volatile("cp.async.bulk.tensor.3d.shared::cluster.global.mbarrier::complete_tx::bytes [%0], [%1, {%3, %4, %5}], [%2];"
               :: "r"(dst), "l"(m), "r"(bar), "r"(c0), "r"(c1), "r"(c2) : "memory");
}
__device__ __forceinline__ void tma_store_2d(const CUtensorMap* m, uint32_t src, int c0, int c1) {
  asm volatile("cp.async.bulk.tensor.2d.global.shared::cta.bulk_group [%0, {%2, %3}], [%1];" :: "l"(m), "r"(src), "r"(c0), "r"(c1) : "memory");
}
__device__ __forceinline__ void bulk_commit() { asm volatile("cp.async.bulk.commit_group;" ::: "memory"); }
__device__ __forceinline__ void bulk_wait_all() { asm volatile("cp.async.bulk.wait_group 0;" ::: "memory"); }
__device__ __forceinline__ void cluster_exit_barrier() {
  __syncwarp();
  asm volatile("barrier.cluster.arrive.relaxed;\nbarrier.cluster.wait;" ::: "memory");
}
__device__ __forceinline__ void wg_fence() { asm volatile("wgmma.fence.sync.aligned;" ::: "memory"); }
__device__ __forceinline__ void wg_commit() { asm volatile("wgmma.commit_group.sync.aligned;" ::: "memory"); }
template <int N> __device__ __forceinline__ void wg_wait() { asm volatile("wgmma.wait_group.sync.aligned %0;" :: "n"(N) : "memory"); }
template <int R> __device__ __forceinline__ void reg_alloc() { asm volatile("setmaxnreg.inc.sync.aligned.u32 %0;" :: "n"(R)); }
template <int R> __device__ __forceinline__ void reg_dealloc() { asm volatile("setmaxnreg.dec.sync.aligned.u32 %0;" :: "n"(R)); }
__device__ __forceinline__ void ldsm_x4(uint32_t addr, uint32_t& r0, uint32_t& r1, uint32_t& r2, uint32_t& r3) {
  asm volatile("ldmatrix.sync.aligned.m8n8.x4.shared.b16 {%0,%1,%2,%3}, [%4];" : "=r"(r0), "=r"(r1), "=r"(r2), "=r"(r3) : "r"(addr));
}
__device__ __forceinline__ void ldsm_x4_t(uint32_t addr, uint32_t& r0, uint32_t& r1, uint32_t& r2, uint32_t& r3) {
  asm volatile("ldmatrix.sync.aligned.m8n8.x4.trans.shared.b16 {%0,%1,%2,%3}, [%4];" : "=r"(r0), "=r"(r1), "=r"(r2), "=r"(r3) : "r"(addr));
}
__device__ __forceinline__ void stsm_x4(uint32_t addr, uint32_t r0, uint32_t r1, uint32_t r2, uint32_t r3) {
  asm volatile("stmatrix.sync.aligned.m8n8.x4.shared.b16 [%0], {%1,%2,%3,%4};" :: "r"(addr), "r"(r0), "r"(r1), "r"(r2), "r"(r3) : "memory");
}
__device__ __forceinline__ float2 lds_f2(uint32_t addr) { float2 v; asm volatile("ld.shared.v2.f32 {%0,%1}, [%2];" : "=f"(v.x), "=f"(v.y) : "r"(addr)); return v; }
__device__ __forceinline__ void sts32(uint32_t addr, uint32_t v) { asm volatile("st.shared.u32 [%0], %1;" :: "r"(addr), "r"(v) : "memory"); }
__device__ __forceinline__ void sts128(uint32_t addr, uint4 v) {
  asm volatile("st.shared.v4.u32 [%0], {%1,%2,%3,%4};" :: "r"(addr), "r"(v.x), "r"(v.y), "r"(v.z), "r"(v.w) : "memory");
}
__device__ __forceinline__ void mma16816(float (&d)[4], uint32_t a0, uint32_t a1, uint32_t a2, uint32_t a3, uint32_t b0, uint32_t b1) {
  asm("mma.sync.aligned.m16n8k16.row.col.f32.bf16.bf16.f32 {%0,%1,%2,%3}, {%4,%5,%6,%7}, {%8,%9}, {%0,%1,%2,%3};"
               : "+f"(d[0]), "+f"(d[1]), "+f"(d[2]), "+f"(d[3]) : "r"(a0), "r"(a1), "r"(a2), "r"(a3), "r"(b0), "r"(b1));
}
__device__ __forceinline__ uint32_t pack_bf16(float lo, float hi) {
  uint32_t r; asm("cvt.rn.bf16x2.f32 %0, %1, %2;" : "=r"(r) : "f"(hi), "f"(lo)); return r;
}
__device__ __forceinline__ float bf_lo(uint32_t v) { return __uint_as_float(v << 16); }
__device__ __forceinline__ float bf_hi(uint32_t v) { return __uint_as_float(v & 0xffff0000u); }
__device__ __forceinline__ uint32_t bmul2(uint32_t a, uint32_t b) { uint32_t r; asm("mul.rn.bf16x2 %0, %1, %2;" : "=r"(r) : "r"(a), "r"(b)); return r; }
__device__ __forceinline__ uint32_t badd2(uint32_t a, uint32_t b) { uint32_t r; asm("add.rn.bf16x2 %0, %1, %2;" : "=r"(r) : "r"(a), "r"(b)); return r; }
#define STAMP(idx) do {} while (0)
#define MSTAMP(idx) do {} while (0)
#define BSTAMP(idx, saddr) do {} while (0)

__device__ __forceinline__ uint32_t pack_f16(float lo, float hi) {
  uint32_t r; asm("cvt.rn.satfinite.f16x2.f32 %0, %1, %2;" : "=r"(r) : "f"(hi), "f"(lo)); return r;
}
__device__ __forceinline__ uint32_t hfma2(uint32_t a, uint32_t b, uint32_t c) { uint32_t r; asm("fma.rn.f16x2 %0, %1, %2, %3;" : "=r"(r) : "r"(a), "r"(b), "r"(c)); return r; }
__device__ __forceinline__ uint32_t gelu_pair_f16(uint32_t h) {
  const uint32_t c0 = 0x3e623e62u, c1 = 0x34913491u;
  uint32_t u, p, z, t, r, o;
  asm("mul.rn.f16x2 %0, %1, %1;" : "=r"(u) : "r"(h));
  asm("fma.rn.f16x2 %0, %1, %2, %3;" : "=r"(p) : "r"(u), "r"(c1), "r"(c0));
  asm("mul.rn.f16x2 %0, %1, %2;" : "=r"(z) : "r"(h), "r"(p));
  asm("tanh.approx.f16x2 %0, %1;" : "=r"(t) : "r"(z));
  asm("fma.rn.f16x2 %0, %1, %2, %1;" : "=r"(r) : "r"(h), "r"(t));
  float lo, hi;
  asm("{\n.reg .f16 a, b;\nmov.b32 {a, b}, %2;\ncvt.f32.f16 %0, a;\ncvt.f32.f16 %1, b;\n}" : "=f"(lo), "=f"(hi) : "r"(r));
  asm("cvt.rn.bf16x2.f32 %0, %1, %2;" : "=r"(o) : "f"(hi), "f"(lo));
  return o;
}
__device__ __forceinline__ float gelu_from_half(float h) {
  const float c0 = 2.f * 0.7978845608028654f, c1 = 8.f * 0.7978845608028654f * 0.044715f;
  float z = h * fmaf(h * h, c1, c0);
  float t; asm("tanh.approx.f32 %0, %1;" : "=f"(t) : "f"(z));
  return fmaf(h, t, h);
}
__device__ __forceinline__ void wgmma_ss_n128(float (&d)[64], uint32_t a_lo, uint32_t b_lo) {
  asm volatile(
    "{\n.reg .b64 da, db;\nmov.b64 da, {%64, 8};\nmov.b64 db, {%65, 0x40000040};\n"
    "wgmma.mma_async.sync.aligned.m64n128k16.f32.bf16.bf16 "
    "{%0, %1, %2, %3, %4, %5, %6, %7, %8, %9, %10, %11, %12, %13, %14, %15, "
    "%16, %17, %18, %19, %20, %21, %22, %23, %24, %25, %26, %27, %28, %29, %30, %31, "
    "%32, %33, %34, %35, %36, %37, %38, %39, %40, %41, %42, %43, %44, %45, %46, %47, "
    "%48, %49, %50, %51, %52, %53, %54, %55, %56, %57, %58, %59, %60, %61, %62, %63}, "
    "da, db, 1, 1, 1, 0, 1;\n}\n"
    : "+f"(d[0]), "+f"(d[1]), "+f"(d[2]), "+f"(d[3]), "+f"(d[4]), "+f"(d[5]), "+f"(d[6]), "+f"(d[7]),
      "+f"(d[8]), "+f"(d[9]), "+f"(d[10]), "+f"(d[11]), "+f"(d[12]), "+f"(d[13]), "+f"(d[14]), "+f"(d[15]),
      "+f"(d[16]), "+f"(d[17]), "+f"(d[18]), "+f"(d[19]), "+f"(d[20]), "+f"(d[21]), "+f"(d[22]), "+f"(d[23]),
      "+f"(d[24]), "+f"(d[25]), "+f"(d[26]), "+f"(d[27]), "+f"(d[28]), "+f"(d[29]), "+f"(d[30]), "+f"(d[31]),
      "+f"(d[32]), "+f"(d[33]), "+f"(d[34]), "+f"(d[35]), "+f"(d[36]), "+f"(d[37]), "+f"(d[38]), "+f"(d[39]),
      "+f"(d[40]), "+f"(d[41]), "+f"(d[42]), "+f"(d[43]), "+f"(d[44]), "+f"(d[45]), "+f"(d[46]), "+f"(d[47]),
      "+f"(d[48]), "+f"(d[49]), "+f"(d[50]), "+f"(d[51]), "+f"(d[52]), "+f"(d[53]), "+f"(d[54]), "+f"(d[55]),
      "+f"(d[56]), "+f"(d[57]), "+f"(d[58]), "+f"(d[59]), "+f"(d[60]), "+f"(d[61]), "+f"(d[62]), "+f"(d[63])
    : "r"(a_lo), "r"(b_lo));
}
__device__ __forceinline__ void wgmma_ss_n192(float (&d)[96], uint32_t a_lo, uint32_t b_lo) {
  asm volatile(
    "{\n.reg .b64 da, db;\nmov.b64 da, {%96, 8};\nmov.b64 db, {%97, 0x40000040};\n"
    "wgmma.mma_async.sync.aligned.m64n192k16.f32.bf16.bf16 "
    "{%0, %1, %2, %3, %4, %5, %6, %7, %8, %9, %10, %11, %12, %13, %14, %15, "
    "%16, %17, %18, %19, %20, %21, %22, %23, %24, %25, %26, %27, %28, %29, %30, %31, "
    "%32, %33, %34, %35, %36, %37, %38, %39, %40, %41, %42, %43, %44, %45, %46, %47, "
    "%48, %49, %50, %51, %52, %53, %54, %55, %56, %57, %58, %59, %60, %61, %62, %63, "
    "%64, %65, %66, %67, %68, %69, %70, %71, %72, %73, %74, %75, %76, %77, %78, %79, "
    "%80, %81, %82, %83, %84, %85, %86, %87, %88, %89, %90, %91, %92, %93, %94, %95}, "
    "da, db, 1, 1, 1, 0, 1;\n}\n"
    : "+f"(d[0]), "+f"(d[1]), "+f"(d[2]), "+f"(d[3]), "+f"(d[4]), "+f"(d[5]), "+f"(d[6]), "+f"(d[7]),
      "+f"(d[8]), "+f"(d[9]), "+f"(d[10]), "+f"(d[11]), "+f"(d[12]), "+f"(d[13]), "+f"(d[14]), "+f"(d[15]),
      "+f"(d[16]), "+f"(d[17]), "+f"(d[18]), "+f"(d[19]), "+f"(d[20]), "+f"(d[21]), "+f"(d[22]), "+f"(d[23]),
      "+f"(d[24]), "+f"(d[25]), "+f"(d[26]), "+f"(d[27]), "+f"(d[28]), "+f"(d[29]), "+f"(d[30]), "+f"(d[31]),
      "+f"(d[32]), "+f"(d[33]), "+f"(d[34]), "+f"(d[35]), "+f"(d[36]), "+f"(d[37]), "+f"(d[38]), "+f"(d[39]),
      "+f"(d[40]), "+f"(d[41]), "+f"(d[42]), "+f"(d[43]), "+f"(d[44]), "+f"(d[45]), "+f"(d[46]), "+f"(d[47]),
      "+f"(d[48]), "+f"(d[49]), "+f"(d[50]), "+f"(d[51]), "+f"(d[52]), "+f"(d[53]), "+f"(d[54]), "+f"(d[55]),
      "+f"(d[56]), "+f"(d[57]), "+f"(d[58]), "+f"(d[59]), "+f"(d[60]), "+f"(d[61]), "+f"(d[62]), "+f"(d[63]),
      "+f"(d[64]), "+f"(d[65]), "+f"(d[66]), "+f"(d[67]), "+f"(d[68]), "+f"(d[69]), "+f"(d[70]), "+f"(d[71]),
      "+f"(d[72]), "+f"(d[73]), "+f"(d[74]), "+f"(d[75]), "+f"(d[76]), "+f"(d[77]), "+f"(d[78]), "+f"(d[79]),
      "+f"(d[80]), "+f"(d[81]), "+f"(d[82]), "+f"(d[83]), "+f"(d[84]), "+f"(d[85]), "+f"(d[86]), "+f"(d[87]),
      "+f"(d[88]), "+f"(d[89]), "+f"(d[90]), "+f"(d[91]), "+f"(d[92]), "+f"(d[93]), "+f"(d[94]), "+f"(d[95])
    : "r"(a_lo), "r"(b_lo));
}
__device__ __forceinline__ void wgmma_ss_n256(float (&d)[128], uint32_t a_lo, uint32_t b_lo) {
  asm volatile(
    "{\n.reg .b64 da, db;\nmov.b64 da, {%128, 8};\nmov.b64 db, {%129, 0x40000040};\n"
    "wgmma.mma_async.sync.aligned.m64n256k16.f32.bf16.bf16 "
    "{%0, %1, %2, %3, %4, %5, %6, %7, %8, %9, %10, %11, %12, %13, %14, %15, "
    "%16, %17, %18, %19, %20, %21, %22, %23, %24, %25, %26, %27, %28, %29, %30, %31, "
    "%32, %33, %34, %35, %36, %37, %38, %39, %40, %41, %42, %43, %44, %45, %46, %47, "
    "%48, %49, %50, %51, %52, %53, %54, %55, %56, %57, %58, %59, %60, %61, %62, %63, "
    "%64, %65, %66, %67, %68, %69, %70, %71, %72, %73, %74, %75, %76, %77, %78, %79, "
    "%80, %81, %82, %83, %84, %85, %86, %87, %88, %89, %90, %91, %92, %93, %94, %95, "
    "%96, %97, %98, %99, %100, %101, %102, %103, %104, %105, %106, %107, %108, %109, %110, %111, "
    "%112, %113, %114, %115, %116, %117, %118, %119, %120, %121, %122, %123, %124, %125, %126, %127}, "
    "da, db, 1, 1, 1, 0, 1;\n}\n"
    : "+f"(d[0]), "+f"(d[1]), "+f"(d[2]), "+f"(d[3]), "+f"(d[4]), "+f"(d[5]), "+f"(d[6]), "+f"(d[7]),
      "+f"(d[8]), "+f"(d[9]), "+f"(d[10]), "+f"(d[11]), "+f"(d[12]), "+f"(d[13]), "+f"(d[14]), "+f"(d[15]),
      "+f"(d[16]), "+f"(d[17]), "+f"(d[18]), "+f"(d[19]), "+f"(d[20]), "+f"(d[21]), "+f"(d[22]), "+f"(d[23]),
      "+f"(d[24]), "+f"(d[25]), "+f"(d[26]), "+f"(d[27]), "+f"(d[28]), "+f"(d[29]), "+f"(d[30]), "+f"(d[31]),
      "+f"(d[32]), "+f"(d[33]), "+f"(d[34]), "+f"(d[35]), "+f"(d[36]), "+f"(d[37]), "+f"(d[38]), "+f"(d[39]),
      "+f"(d[40]), "+f"(d[41]), "+f"(d[42]), "+f"(d[43]), "+f"(d[44]), "+f"(d[45]), "+f"(d[46]), "+f"(d[47]),
      "+f"(d[48]), "+f"(d[49]), "+f"(d[50]), "+f"(d[51]), "+f"(d[52]), "+f"(d[53]), "+f"(d[54]), "+f"(d[55]),
      "+f"(d[56]), "+f"(d[57]), "+f"(d[58]), "+f"(d[59]), "+f"(d[60]), "+f"(d[61]), "+f"(d[62]), "+f"(d[63]),
      "+f"(d[64]), "+f"(d[65]), "+f"(d[66]), "+f"(d[67]), "+f"(d[68]), "+f"(d[69]), "+f"(d[70]), "+f"(d[71]),
      "+f"(d[72]), "+f"(d[73]), "+f"(d[74]), "+f"(d[75]), "+f"(d[76]), "+f"(d[77]), "+f"(d[78]), "+f"(d[79]),
      "+f"(d[80]), "+f"(d[81]), "+f"(d[82]), "+f"(d[83]), "+f"(d[84]), "+f"(d[85]), "+f"(d[86]), "+f"(d[87]),
      "+f"(d[88]), "+f"(d[89]), "+f"(d[90]), "+f"(d[91]), "+f"(d[92]), "+f"(d[93]), "+f"(d[94]), "+f"(d[95]),
      "+f"(d[96]), "+f"(d[97]), "+f"(d[98]), "+f"(d[99]), "+f"(d[100]), "+f"(d[101]), "+f"(d[102]), "+f"(d[103]),
      "+f"(d[104]), "+f"(d[105]), "+f"(d[106]), "+f"(d[107]), "+f"(d[108]), "+f"(d[109]), "+f"(d[110]), "+f"(d[111]),
      "+f"(d[112]), "+f"(d[113]), "+f"(d[114]), "+f"(d[115]), "+f"(d[116]), "+f"(d[117]), "+f"(d[118]), "+f"(d[119]),
      "+f"(d[120]), "+f"(d[121]), "+f"(d[122]), "+f"(d[123]), "+f"(d[124]), "+f"(d[125]), "+f"(d[126]), "+f"(d[127])
    : "r"(a_lo), "r"(b_lo));
}
__device__ __forceinline__ void wgmma_ss_n128_p(float (&d)[64], uint32_t a_lo, uint32_t b_lo, uint32_t keep) {
  asm volatile(
    "{\n.reg .pred p;\nsetp.ne.b32 p, %66, 0;\n"
    "{\n.reg .b64 da, db;\nmov.b64 da, {%64, 8};\nmov.b64 db, {%65, 0x40000040};\n"
    "wgmma.mma_async.sync.aligned.m64n128k16.f32.bf16.bf16 "
    "{%0, %1, %2, %3, %4, %5, %6, %7, %8, %9, %10, %11, %12, %13, %14, %15, "
    "%16, %17, %18, %19, %20, %21, %22, %23, %24, %25, %26, %27, %28, %29, %30, %31, "
    "%32, %33, %34, %35, %36, %37, %38, %39, %40, %41, %42, %43, %44, %45, %46, %47, "
    "%48, %49, %50, %51, %52, %53, %54, %55, %56, %57, %58, %59, %60, %61, %62, %63}, "
    "da, db, p, 1, 1, 0, 1;\n}\n}\n"
    : "+f"(d[0]), "+f"(d[1]), "+f"(d[2]), "+f"(d[3]), "+f"(d[4]), "+f"(d[5]), "+f"(d[6]), "+f"(d[7]),
      "+f"(d[8]), "+f"(d[9]), "+f"(d[10]), "+f"(d[11]), "+f"(d[12]), "+f"(d[13]), "+f"(d[14]), "+f"(d[15]),
      "+f"(d[16]), "+f"(d[17]), "+f"(d[18]), "+f"(d[19]), "+f"(d[20]), "+f"(d[21]), "+f"(d[22]), "+f"(d[23]),
      "+f"(d[24]), "+f"(d[25]), "+f"(d[26]), "+f"(d[27]), "+f"(d[28]), "+f"(d[29]), "+f"(d[30]), "+f"(d[31]),
      "+f"(d[32]), "+f"(d[33]), "+f"(d[34]), "+f"(d[35]), "+f"(d[36]), "+f"(d[37]), "+f"(d[38]), "+f"(d[39]),
      "+f"(d[40]), "+f"(d[41]), "+f"(d[42]), "+f"(d[43]), "+f"(d[44]), "+f"(d[45]), "+f"(d[46]), "+f"(d[47]),
      "+f"(d[48]), "+f"(d[49]), "+f"(d[50]), "+f"(d[51]), "+f"(d[52]), "+f"(d[53]), "+f"(d[54]), "+f"(d[55]),
      "+f"(d[56]), "+f"(d[57]), "+f"(d[58]), "+f"(d[59]), "+f"(d[60]), "+f"(d[61]), "+f"(d[62]), "+f"(d[63])
    : "r"(a_lo), "r"(b_lo), "r"(keep));
}
__device__ __forceinline__ void wgmma_ss_n256_first(float (&d)[128], uint32_t a_lo, uint32_t b_lo) {
  asm volatile(
    "{\n.reg .b64 da, db;\nmov.b64 da, {%128, 8};\nmov.b64 db, {%129, 0x40000040};\n"
    "mov.b32 %0, 0; mov.b32 %1, 0; mov.b32 %2, 0; mov.b32 %3, 0; mov.b32 %4, 0; mov.b32 %5, 0; mov.b32 %6, 0; mov.b32 %7, 0;\n"
    "mov.b32 %8, 0; mov.b32 %9, 0; mov.b32 %10, 0; mov.b32 %11, 0; mov.b32 %12, 0; mov.b32 %13, 0; mov.b32 %14, 0; mov.b32 %15, 0;\n"
    "mov.b32 %16, 0; mov.b32 %17, 0; mov.b32 %18, 0; mov.b32 %19, 0; mov.b32 %20, 0; mov.b32 %21, 0; mov.b32 %22, 0; mov.b32 %23, 0;\n"
    "mov.b32 %24, 0; mov.b32 %25, 0; mov.b32 %26, 0; mov.b32 %27, 0; mov.b32 %28, 0; mov.b32 %29, 0; mov.b32 %30, 0; mov.b32 %31, 0;\n"
    "mov.b32 %32, 0; mov.b32 %33, 0; mov.b32 %34, 0; mov.b32 %35, 0; mov.b32 %36, 0; mov.b32 %37, 0; mov.b32 %38, 0; mov.b32 %39, 0;\n"
    "mov.b32 %40, 0; mov.b32 %41, 0; mov.b32 %42, 0; mov.b32 %43, 0; mov.b32 %44, 0; mov.b32 %45, 0; mov.b32 %46, 0; mov.b32 %47, 0;\n"
    "mov.b32 %48, 0; mov.b32 %49, 0; mov.b32 %50, 0; mov.b32 %51, 0; mov.b32 %52, 0; mov.b32 %53, 0; mov.b32 %54, 0; mov.b32 %55, 0;\n"
    "mov.b32 %56, 0; mov.b32 %57, 0; mov.b32 %58, 0; mov.b32 %59, 0; mov.b32 %60, 0; mov.b32 %61, 0; mov.b32 %62, 0; mov.b32 %63, 0;\n"
    "mov.b32 %64, 0; mov.b32 %65, 0; mov.b32 %66, 0; mov.b32 %67, 0; mov.b32 %68, 0; mov.b32 %69, 0; mov.b32 %70, 0; mov.b32 %71, 0;\n"
    "mov.b32 %72, 0; mov.b32 %73, 0; mov.b32 %74, 0; mov.b32 %75, 0; mov.b32 %76, 0; mov.b32 %77, 0; mov.b32 %78, 0; mov.b32 %79, 0;\n"
    "mov.b32 %80, 0; mov.b32 %81, 0; mov.b32 %82, 0; mov.b32 %83, 0; mov.b32 %84, 0; mov.b32 %85, 0; mov.b32 %86, 0; mov.b32 %87, 0;\n"
    "mov.b32 %88, 0; mov.b32 %89, 0; mov.b32 %90, 0; mov.b32 %91, 0; mov.b32 %92, 0; mov.b32 %93, 0; mov.b32 %94, 0; mov.b32 %95, 0;\n"
    "mov.b32 %96, 0; mov.b32 %97, 0; mov.b32 %98, 0; mov.b32 %99, 0; mov.b32 %100, 0; mov.b32 %101, 0; mov.b32 %102, 0; mov.b32 %103, 0;\n"
    "mov.b32 %104, 0; mov.b32 %105, 0; mov.b32 %106, 0; mov.b32 %107, 0; mov.b32 %108, 0; mov.b32 %109, 0; mov.b32 %110, 0; mov.b32 %111, 0;\n"
    "mov.b32 %112, 0; mov.b32 %113, 0; mov.b32 %114, 0; mov.b32 %115, 0; mov.b32 %116, 0; mov.b32 %117, 0; mov.b32 %118, 0; mov.b32 %119, 0;\n"
    "mov.b32 %120, 0; mov.b32 %121, 0; mov.b32 %122, 0; mov.b32 %123, 0; mov.b32 %124, 0; mov.b32 %125, 0; mov.b32 %126, 0; mov.b32 %127, 0;\n"
    "wgmma.mma_async.sync.aligned.m64n256k16.f32.bf16.bf16 "
    "{%0, %1, %2, %3, %4, %5, %6, %7, %8, %9, %10, %11, %12, %13, %14, %15, "
    "%16, %17, %18, %19, %20, %21, %22, %23, %24, %25, %26, %27, %28, %29, %30, %31, "
    "%32, %33, %34, %35, %36, %37, %38, %39, %40, %41, %42, %43, %44, %45, %46, %47, "
    "%48, %49, %50, %51, %52, %53, %54, %55, %56, %57, %58, %59, %60, %61, %62, %63, "
    "%64, %65, %66, %67, %68, %69, %70, %71, %72, %73, %74, %75, %76, %77, %78, %79, "
    "%80, %81, %82, %83, %84, %85, %86, %87, %88, %89, %90, %91, %92, %93, %94, %95, "
    "%96, %97, %98, %99, %100, %101, %102, %103, %104, %105, %106, %107, %108, %109, %110, %111, "
    "%112, %113, %114, %115, %116, %117, %118, %119, %120, %121, %122, %123, %124, %125, %126, %127}, "
    "da, db, 1, 1, 1, 0, 1;\n}\n"
    : "=f"(d[0]), "=f"(d[1]), "=f"(d[2]), "=f"(d[3]), "=f"(d[4]), "=f"(d[5]), "=f"(d[6]), "=f"(d[7]),
      "=f"(d[8]), "=f"(d[9]), "=f"(d[10]), "=f"(d[11]), "=f"(d[12]), "=f"(d[13]), "=f"(d[14]), "=f"(d[15]),
      "=f"(d[16]), "=f"(d[17]), "=f"(d[18]), "=f"(d[19]), "=f"(d[20]), "=f"(d[21]), "=f"(d[22]), "=f"(d[23]),
      "=f"(d[24]), "=f"(d[25]), "=f"(d[26]), "=f"(d[27]), "=f"(d[28]), "=f"(d[29]), "=f"(d[30]), "=f"(d[31]),
      "=f"(d[32]), "=f"(d[33]), "=f"(d[34]), "=f"(d[35]), "=f"(d[36]), "=f"(d[37]), "=f"(d[38]), "=f"(d[39]),
      "=f"(d[40]), "=f"(d[41]), "=f"(d[42]), "=f"(d[43]), "=f"(d[44]), "=f"(d[45]), "=f"(d[46]), "=f"(d[47]),
      "=f"(d[48]), "=f"(d[49]), "=f"(d[50]), "=f"(d[51]), "=f"(d[52]), "=f"(d[53]), "=f"(d[54]), "=f"(d[55]),
      "=f"(d[56]), "=f"(d[57]), "=f"(d[58]), "=f"(d[59]), "=f"(d[60]), "=f"(d[61]), "=f"(d[62]), "=f"(d[63]),
      "=f"(d[64]), "=f"(d[65]), "=f"(d[66]), "=f"(d[67]), "=f"(d[68]), "=f"(d[69]), "=f"(d[70]), "=f"(d[71]),
      "=f"(d[72]), "=f"(d[73]), "=f"(d[74]), "=f"(d[75]), "=f"(d[76]), "=f"(d[77]), "=f"(d[78]), "=f"(d[79]),
      "=f"(d[80]), "=f"(d[81]), "=f"(d[82]), "=f"(d[83]), "=f"(d[84]), "=f"(d[85]), "=f"(d[86]), "=f"(d[87]),
      "=f"(d[88]), "=f"(d[89]), "=f"(d[90]), "=f"(d[91]), "=f"(d[92]), "=f"(d[93]), "=f"(d[94]), "=f"(d[95]),
      "=f"(d[96]), "=f"(d[97]), "=f"(d[98]), "=f"(d[99]), "=f"(d[100]), "=f"(d[101]), "=f"(d[102]), "=f"(d[103]),
      "=f"(d[104]), "=f"(d[105]), "=f"(d[106]), "=f"(d[107]), "=f"(d[108]), "=f"(d[109]), "=f"(d[110]), "=f"(d[111]),
      "=f"(d[112]), "=f"(d[113]), "=f"(d[114]), "=f"(d[115]), "=f"(d[116]), "=f"(d[117]), "=f"(d[118]), "=f"(d[119]),
      "=f"(d[120]), "=f"(d[121]), "=f"(d[122]), "=f"(d[123]), "=f"(d[124]), "=f"(d[125]), "=f"(d[126]), "=f"(d[127])
    : "r"(a_lo), "r"(b_lo));
}

template <int N> struct Mma;
template <> struct Mma<128> {
  static __device__ __forceinline__ void ss(float (&d)[64], uint32_t a, uint32_t b) { wgmma_ss_n128(d, a, b); }
  static __device__ __forceinline__ void ss(float (&d)[64], uint32_t a, uint32_t b, uint32_t keep) { wgmma_ss_n128_p(d, a, b, keep); }
};
template <> struct Mma<192> {
  static __device__ __forceinline__ void ss(float (&d)[96], uint32_t a, uint32_t b) { wgmma_ss_n192(d, a, b); }
};
template <> struct Mma<256> {
  static __device__ __forceinline__ void ss(float (&d)[128], uint32_t a, uint32_t b) { wgmma_ss_n256(d, a, b); }
  static __device__ __forceinline__ void ss(float (&d)[128], uint32_t a, uint32_t b, uint32_t) { wgmma_ss_n256_first(d, a, b); }
};
template <int R> __device__ __forceinline__ void pin(float (&d)[R]) {
#pragma unroll
  for (int x = 0; x < R; x++) asm volatile("" : "+f"(d[x]));
}

__device__ __forceinline__ uint32_t ld_relaxed(const uint32_t* p) {
  uint32_t v; asm volatile("ld.relaxed.gpu.global.u32 %0, [%1];" : "=r"(v) : "l"(p) : "memory"); return v;
}
__device__ __forceinline__ void red_release(uint32_t* p) { asm volatile("red.release.gpu.global.add.u32 [%0], 1;" :: "l"(p) : "memory"); }
__device__ __forceinline__ uint32_t both_valid(uint32_t a, uint32_t b, uint32_t ep) {
  uint32_t r; asm("lop3.b32 %0, %1, %2, %3, 0x42;" : "=r"(r) : "r"(a), "r"(b), "r"(ep)); return r;
}
__device__ __forceinline__ uint32_t tagged(float v, uint32_t ep) { return (__float_as_uint(v) | 1u) ^ (ep & 1u); }
__device__ __forceinline__ void st_release(uint32_t* p, uint32_t v) { asm volatile("st.release.gpu.global.u32 [%0], %1;" :: "l"(p), "r"(v) : "memory"); }
__device__ __forceinline__ void stg32(void* p, uint32_t v) { asm volatile("st.global.u32 [%0], %1;" :: "l"(p), "r"(v) : "memory"); }
__device__ __forceinline__ float rsqrt_fast(float x) { float r; asm("rsqrt.approx.ftz.f32 %0, %1;" : "=f"(r) : "f"(x)); return r; }
__device__ __forceinline__ uint32_t gate_pair(uint32_t x, uint32_t y, uint32_t r, uint32_t nb) {
  uint32_t o;
  asm("{\n.reg .b16 l, h;\n.reg .b32 ll, hh, t;\nmov.b32 {l, h}, %3;\nmov.b32 ll, {l, l};\nmov.b32 hh, {h, h};\n"
      "fma.rn.bf16x2 t, %1, ll, %4;\nfma.rn.bf16x2 t, %1, hh, t;\nfma.rn.bf16x2 %0, t, %2, %1;\n}" : "=r"(o) : "r"(x), "r"(y), "r"(r), "r"(nb));
  return o;
}

constexpr int CV_KT_O = 4144;
constexpr int CV_KT_CH = 8336;
constexpr int CV_KH = 2064;
constexpr int CV_U_PLANE = 2240;
constexpr int CV_U_CH = 4496;
constexpr int CV_VQ = 8320, CV_Y_CH = 1040, CV_XROW = 2064;
constexpr int SM_BAR = 0;
constexpr int CV_K = 896;
constexpr int CV_X = CV_K + 128 + 32768;
constexpr int CV_ST0 = CV_X + 16 * CV_XROW;
constexpr int CV_KT = CV_ST0 + 8192;
constexpr int CV_QS = CV_KT + 8 * CV_KT_CH;
constexpr int CV_U = 142848;
constexpr int CV_V = CV_U + 8 * CV_U_CH;
constexpr int CV_ST1 = CV_V + 4 * CV_VQ;
constexpr int SM_ZERO = CV_ST1 + 8192, SM_ROLE = SM_ZERO + 4, SM_EPOCH = SM_ZERO + 8;
constexpr int CV_END = SM_ZERO + 16;
static_assert(CV_QS + 1024 <= CV_U && CV_X % 1024 == 0 && CV_V % 128 == 0, "layout");
constexpr int CV_BAR = SM_BAR + 8 * 84, BAR_REL = 25;
enum { CB_K0, CB_QA, CB_Q0, CB_Q1, CB_Q2, CB_Q3, CB_K1, CB_X0, CB_X1, CB_QC0, CB_QC1, CB_QS, CB_U1, CB_U2,
       CB_ST0, CB_ST1, CB_O1, CB_P1, CB_Y1, CB_Y2, CB_P2, CB_EARLY, CB_LATE, CB_YOUT, CB_STAT, CB_XFREE = CB_STAT + 2, CB_COUNT };
static_assert(CV_BAR + 8 * CB_COUNT <= CV_K, "layout");

__device__ __forceinline__ uint32_t lds32_nv(uint32_t addr) { uint32_t v; asm("ld.shared.u32 %0, [%1];" : "=r"(v) : "r"(addr)); return v; }
__device__ __forceinline__ void ldsm_x4_nv(uint32_t addr, uint32_t& r0, uint32_t& r1, uint32_t& r2, uint32_t& r3) {
  asm("ldmatrix.sync.aligned.m8n8.x4.shared.b16 {%0,%1,%2,%3}, [%4];" : "=r"(r0), "=r"(r1), "=r"(r2), "=r"(r3) : "r"(addr));
}
__device__ __forceinline__ void stsm_x4_t(uint32_t addr, uint32_t r0, uint32_t r1, uint32_t r2, uint32_t r3) {
  asm volatile("stmatrix.sync.aligned.m8n8.x4.trans.shared.b16 [%0], {%1,%2,%3,%4};" :: "r"(addr), "r"(r0), "r"(r1), "r"(r2), "r"(r3) : "memory");
}
__device__ __forceinline__ void bulk_load(uint32_t dst, const void* src, uint32_t bytes, uint32_t bar) {
  asm volatile("cp.async.bulk.shared::cluster.global.mbarrier::complete_tx::bytes [%0], [%1], %2, [%3];" :: "r"(dst), "l"(src), "r"(bytes), "r"(bar) : "memory");
}
__device__ __forceinline__ void mbar_wait_plain(uint32_t bar, uint32_t parity) {
#pragma unroll 1
  for (int spins = 0; spins < SPIN_LIMIT && !mbar_try(bar, parity); spins++) {}
}

__device__ __forceinline__ void shift_chunk(uint32_t src) {
  uint4 e;
  uint32_t nx;
  asm volatile("ld.shared.v4.u32 {%0,%1,%2,%3}, [%4];" : "=r"(e.x), "=r"(e.y), "=r"(e.z), "=r"(e.w) : "r"(src));
  asm volatile("ld.shared.u32 %0, [%1];" : "=r"(nx) : "r"(src + 16));
  sts128(src + CV_KT_O, make_uint4(__byte_perm(e.x, e.y, 0x5432), __byte_perm(e.y, e.z, 0x5432), __byte_perm(e.z, e.w, 0x5432), __byte_perm(e.w, nx, 0x5432)));
}
__device__ __forceinline__ void kv_block(uint32_t sm, int t0, const uint32_t (&wp)[4], int lane) {
  const int mi = lane >> 3, rev = 7 - (lane & 7);
  uint32_t vv[4], res[4];
  ldsm_x4(sm + CV_V + (t0 >> 9) * (CV_VQ - 8192) + (t0 + 8 * mi + rev) * 16, vv[0], vv[1], vv[2], vv[3]);
#pragma unroll
  for (int i = 0; i < 4; i++) {
    uint32_t k0, k1, k2, k3;
    ldsm_x4(sm + CV_K + (8 + t0 + 8 * i + rev - mi) * 16, k0, k1, k2, k3);
    res[i] = bmul2(badd2(badd2(badd2(bmul2(k3, wp[3]), bmul2(k2, wp[2])), bmul2(k1, wp[1])), bmul2(k0, wp[0])), vv[i]);
  }
  stsm_x4_t(sm + CV_U + (lane & 7) * CV_U_CH + (1 - (mi & 1)) * CV_U_PLANE + (8 + (t0 >> 4) + (mi >> 1)) * 16, res[0], res[1], res[2], res[3]);
}
template <int T0, int NT, int D0, int D1, int J0, int J1>
__device__ __forceinline__ void conv_phase(float (&acc)[16][4], uint32_t abase, uint32_t bbase, uint32_t zero) {
  abase += zero; bbase += zero;
#pragma unroll 1
  for (int dl = 0; dl < 8; dl++) {
    uint32_t bf[NT][2];
#pragma unroll
    for (int j = 0; j < NT; j += 2) ldsm_x4_nv(bbase + (T0 + j) * 128 - dl * 16, bf[j][0], bf[j][1], bf[j + 1][0], bf[j + 1][1]);
    const uint32_t ap = abase + dl * 32;
#pragma unroll
    for (int dh = D0; dh < D1; dh++) {
      const uint32_t a0 = lds32_nv(ap + dh * 256), a1 = lds32_nv(ap + dh * 256 - 16), a2 = lds32_nv(ap + dh * 256 + 16);
      const uint32_t a3 = a0 + zero;
#pragma unroll
      for (int j = 0; j < NT; j++)
        if (dh + T0 + j >= J0 && dh + T0 + j < J1) mma16816(acc[dh + T0 + j], a0, a1, a2, a3, bf[j][0], bf[j][1]);
    }
  }
}
__device__ __forceinline__ uint32_t hidden_zero(uint32_t addr) {
  uint32_t z; asm volatile("ld.volatile.shared.u32 %0, [%1];" : "=r"(z) : "r"(addr) : "memory"); return z;
}
template <int J0, int J1>
__device__ __forceinline__ void stage_y(const float (&acc)[16][4], uint32_t ys, uint32_t bar) {
#pragma unroll
  for (int j = J0; j < J1; j += 2)
    stsm_x4_t(ys + (j >> 2) * CV_VQ + (j & 3) * 128, pack_bf16(acc[j][0], acc[j][1]), pack_bf16(acc[j][2], acc[j][3]),
              pack_bf16(acc[j + 1][0], acc[j + 1][1]), pack_bf16(acc[j + 1][2], acc[j + 1][3]));
  if (J0) {
    __syncwarp();
    mbar_arrive_if(bar, (threadIdx.x & 31) == 0);
  }
}

constexpr int CV_JS = 8;
enum { M_K, M_V, M_Q, M_W1C, M_W3C, M_X3S, M_X3B, M_H, M_HS, M_X1, M_HID, M_W1, M_W2, M_W3A, M_W3B, M_W4, M_OUT, M_Y, M_COUNT };
struct alignas(64) Params {
  const bf16 *q, *shift_k, *ssm_k, *ssm_d, *w2;
  CUtensorMap m[M_COUNT];
};
__device__ __forceinline__ void prefetch_line(const void* p) { asm volatile("prefetch.global.L2 [%0];" :: "l"(p) : "memory"); }

__device__ __forceinline__ uint32_t tpc_id() { uint32_t smid; asm volatile("mov.u32 %0, %%smid;" : "=r"(smid)); return smid >> 1; }
__device__ __forceinline__ uint32_t pick_role(uint32_t t, int lane) {
  uint32_t gpc = t < 32 ? t & 7 : t < 60 ? 1 + (t - 32) % 7 : t < 62 ? t - 54 : 0;
  const uint32_t d = ld_relaxed(g_role + 12 + (lane >> 3)) - ld_relaxed(g_role + 4 + (lane & 7)) + 4096;
  const uint32_t match = __ballot_sync(0xffffffffu, d < 8192) & 0x3e3e3e3eu;
  const uint32_t nine = (match | match >> 8 | match >> 16 | match >> 24) & 0xff;
  if (t >= 62) gpc = max(__ffs((match >> (8 * t - 496)) & 0xff) - 1, 0);
  const uint32_t below = (1u << gpc) - 1, pos = (nine >> gpc) & 1 ? __popc(nine & below) : __popc(nine) + __popc(~nine & below & 0xfe);
  uint32_t cls = gpc == 0 ? 0 : min(pos, 7 - pos);
  if (pos > 3 && cls < __popc(nine) && t < 8) cls = 0;
  uint32_t role = 0;
  if (lane == 0) {
#pragma unroll 1
    for (uint32_t k = 0; k < 4; k++) {
      const uint32_t p = (cls + k) & 3, ticket = atomicAdd(&g_role[p], 1u);
      if (ticket < 16) { role = ticket * 4 + p; break; }
    }
  }
  return role;
}

__device__ __forceinline__ void load_k(const Params& pr, uint32_t sm, int x) {
  const uint32_t bar = sm + CV_BAR + 8 * (x ? CB_K1 : CB_K0), bytes = x ? 4096 - CV_KH : CV_KH;
  mbar_expect_tx(bar, 8 * bytes);
#pragma unroll 1
  for (int ch = 0; ch < 8; ch++)
    bulk_load(sm + CV_KT + ch * CV_KT_CH + 32 + x * CV_KH, reinterpret_cast<const char*>(pr.ssm_k) + (blockIdx.x * 8 + ch) * 4096 + x * CV_KH, bytes, bar);
}
__device__ __forceinline__ void load_kv(const Params& pr, uint32_t sm, int y, int barrier) {
  tma_2d(sm + CV_K + 128 + y * 4096, &pr.m[M_K], sm + CV_BAR + 8 * barrier, blockIdx.x * 8, y * 256);
  tma_2d(sm + CV_V + (y >> 1) * CV_VQ + (y & 1) * 4096, &pr.m[M_V], sm + CV_BAR + 8 * barrier, blockIdx.x * 8, y * 256);
}

__device__ __forceinline__ void conv_part(const Params& pr, uint32_t sm, int warp) {
  const int tid = threadIdx.x, lane = tid & 31;
  const int b = blockIdx.x, d0 = b * 8;
  const uint32_t kt = sm + CV_KT, ub = sm + CV_U, bar = sm + CV_BAR;
  const int g = lane >> 2, qd = lane & 3, mi = lane >> 3;
  if (warp == 8) {
    asm volatile("bar.arrive 1, 384;" ::: "memory");
    const uint32_t ep = ld_relaxed(&g_epoch);
    if (elect_one()) {
      load_k(pr, sm, 1);
#pragma unroll 1
      for (int y = 2; y < 8; y++) {
        if (y == 6) {
          mbar_expect_tx(bar + 8 * CB_X0, 32768);
#pragma unroll 1
          for (int r = 0; r < 16; r++) bulk_load(sm + CV_X + r * CV_XROW, pr.q + (size_t)(b * 16 + r) * DM, 2048, bar + 8 * CB_X0);
        }
        if (!(y & 1)) mbar_expect_tx(bar + 8 * (CB_Q0 + (y >> 1)), 16384);
        load_kv(pr, sm, y, CB_Q0 + (y >> 1));
      }
#pragma unroll 1
      for (int x = M_Q; x < M_COUNT; x++) asm volatile("prefetch.tensormap [%0];" :: "l"(&pr.m[x]) : "memory");
    }
    __syncwarp();
    const uint32_t role = b & 1 ? 0 : pick_role(tpc_id(), lane);
    if (lane == 0) {
      sts32(sm + SM_EPOCH, ep);
      sts32(sm + SM_ROLE, role);
      asm volatile("fence.release.sync_restrict::shared::cta.cluster;" ::: "memory");
    }
    __syncwarp();
    asm volatile("barrier.cluster.arrive.relaxed.aligned;" ::: "memory");
    auto load_q = [&](int x) {
      mbar_wait_plain(bar + 8 * (CB_U1 + x), 0);
      fence_async_smem();
      if (elect_one()) {
        mbar_expect_tx(bar + 8 * (CB_QC0 + x), 16384);
#pragma unroll 1
        for (int y = 4 * x; y < 4 * x + 4; y++) tma_2d(sm + CV_K + 128 + y * 4096, &pr.m[M_Q], bar + 8 * (CB_QC0 + x), d0, y * 256);
      }
    };
    const int npieces = b < 112 ? 5 : 1;
    const int xr = (mi >> 1) * 8 + (lane & 7);
    const uint32_t xa = sm + CV_X + xr * 64 + (((mi & 1) ^ ((xr >> 1) & 3)) << 4);
    float cs[8][4] = {};
    auto q_stats = [&]() {
      mbar_wait_plain(bar + 8 * CB_QS, 0);
      float sum = 0.f, sq = 0.f;
#pragma unroll
      for (int x = 0; x < 8; x++) { const float2 v = lds_f2(sm + CV_QS + x * 128 + (lane & 15) * 8); sum += v.x; sq += v.y; }
      const float mean = sum * (1.f / DM), rs = rsqrt_fast(fmaxf(fmaf(-mean, mean, sq * (1.f / DM)), 0.f) + LN_EPS);
      const uint32_t rh = pack_bf16(0.f, rs);
      if (lane < 16)
        asm volatile("st.relaxed.gpu.global.v2.b32 [%0], {%1,%2};" :: "l"(g_qstat + b * 16 + lane), "r"(tagged(__uint_as_float(pack_bf16(rs - bf_hi(rh), bf_hi(rh))), ep)),
                     "r"(pack_bf16(-mean * rs, -mean * rs)) : "memory");
      if (lane == 0) { STAMP(47); asm volatile("red.relaxed.gpu.global.add.u32 [%0], 1;" :: "l"(&g_qcnt) : "memory"); }
    };
#pragma unroll 1
    for (int pc = -3; pc < npieces; pc++) {
      if (pc == -2) q_stats();
      if (pc >= 0) {
        mbar_wait_plain(bar + 8 * (CB_X0 + ((pc + 1) & 1)), ((pc + 1) >> 1) & 1);
#pragma unroll 1
        for (int r = 0; r < 16; r += 4) {
#pragma unroll
          for (int x = 0; x < 8; x++) {
            uint32_t a0, a1, a2, a3;
            ldsm_x4_t((xa ^ ((x & 1) << 5)) + ((pc + 1) & 1) * 16384 + (r + (x >> 1)) * 1024, a0, a1, a2, a3);
            mma16816(cs[x], a0, a1, a2, a3, 0x3f803f80u, 0x3f803f80u);
          }
        }
        if (pc == 0 || pc == 4) {
          float t = 0.f;
#pragma unroll
          for (int x = 0; x < 8; x += 2) {
            t += qd & 2 ? (qd & 1 ? cs[x + 1][2] : cs[x + 1][0]) : (qd & 1 ? cs[x][2] : cs[x][0]);
            cs[x][0] = cs[x][2] = cs[x + 1][0] = cs[x + 1][2] = 0.f;
          }
          (pc ? g_cs3 + 32 * b : g_cs1[b & 3] + 32 * (b >> 2))[8 * qd + g] = t;
        }
        __syncwarp();
      }
      if (pc > -3 && pc + 2 < npieces && elect_one()) {
        const uint32_t bx = bar + 8 * (CB_X0 + ((pc + 1) & 1));
        mbar_expect_tx(bx, 16384);
        tma_2d(sm + CV_X + ((pc + 1) & 1) * 16384, &pr.m[pc == -2 ? M_W1C : M_W3C], bx, 32 * (pc == -2 ? b >> 2 : b), 256 * (pc == -2 ? b & 3 : pc + 1));
      }
      if (pc == -3 || pc == min(2, npieces - 1)) load_q(pc >= 0);
    }
#pragma unroll 1
    for (int x = 0; x < 4; x++) prefetch_line(reinterpret_cast<const char*>(pr.w2) + (b * 128 + x * 32 + lane) * 128);
    if (lane == 0) STAMP(52);
    return;
  }

  const uint32_t dpair = __ldg(reinterpret_cast<const uint32_t*>(pr.ssm_d + d0 + 2 * qd));
  const int wi = warp - (warp > 8), ti = 32 * wi + lane;
  {
    if (tid < 160) {
      const int x = tid - 128, y = x & 3;
      sts128(tid < 128 ? ub + (tid >> 4) * CV_U_CH + ((tid >> 3) & 1) * CV_U_PLANE + (tid & 7) * 16
                       : y == 3 ? sm + CV_K + (x >> 2) * 16 : kt + (x >> 2) * CV_KT_CH + (y == 2 ? 4128 : y * 16), make_uint4(0, 0, 0, 0));
    }
    uint32_t wp[4];
    {
      const uint4 a = ld_nc_u4(pr.shift_k + (d0 + 2 * qd) * 4);
      wp[0] = __byte_perm(a.x, a.z, 0x5410); wp[1] = __byte_perm(a.x, a.z, 0x7632);
      wp[2] = __byte_perm(a.y, a.w, 0x5410); wp[3] = __byte_perm(a.y, a.w, 0x7632);
    }
    const uint32_t kc = kt + (lane & 7) * CV_KT_CH;
    named_bar(1, 384);
#pragma unroll 1
    for (int x = 0; x < 2; x++) {
      mbar_wait_plain(bar + 8 * (x ? CB_K1 : CB_K0), 0);
#pragma unroll 1
      for (uint32_t a = kc + ((ti >> 3) + (x ? 130 - 32 : 0)) * 16; a < kc + (x ? 258 : 130) * 16; a += x ? 192 : 704) shift_chunk(a);
      __syncwarp();
      mbar_arrive_if(bar + 8 * CB_O1, x && lane == 0);
      if (tid == 0) BSTAMP(54, kt);
#pragma unroll 1
      for (int t0 = warp < 8 ? 32 * wi : 32 * wi + 256; t0 < (x ? SEQ : 512); t0 += x ? 96 : 256) {
        mbar_wait_plain(bar + 8 * (t0 < 256 ? CB_QA : CB_Q0 + (t0 >> 9)), 0);
        if (tid == 0) BSTAMP(56, kt);
        kv_block(sm, t0, wp, lane);
        constexpr int T1 = 128 * CV_JS + 32;
        __syncwarp();
        mbar_arrive_if(bar + 8 * (CB_U1 + (t0 >= T1)), t0 + 96 >= (t0 < T1 ? T1 : SEQ) && lane == 0);
      }
      if (x == 0) named_bar(4, 352);
      if (warp < 8) break;
    }
  }

  if (warp < 8) {
    const int o = 2 * qd - g;
    const uint32_t abase = kt + warp * CV_KT_CH + 32 + ((g & 1) ? CV_KT_O + (o - 1) * 2 : o * 2);
    const uint32_t bbase = ub + warp * CV_U_CH + (mi & 1) * CV_U_PLANE + (8 + (lane >> 4) * 8 + (lane & 7)) * 16;
    const uint32_t ys = sm + CV_V + warp * CV_Y_CH + (mi & 1) * 512 + ((lane >> 4) * 8 + (lane & 7)) * 16;
    auto q_sums = [&]() {
      mbar_wait_plain(bar + 8 * CB_X0, 0);
      float sum[4] = {0.f, 0.f, 0.f, 0.f}, lo[4] = {0.f, 0.f, 0.f, 0.f}, hi[4] = {0.f, 0.f, 0.f, 0.f};
#pragma unroll
      for (int x = 0; x < 8; x++) {
        uint32_t a0, a1, a2, a3;
        ldsm_x4(sm + CV_X + (lane & 15) * CV_XROW + warp * 256 + (lane >> 4) * 16 + x * 32, a0, a1, a2, a3);
        mma16816(sum, a0, a1, a2, a3, 0x3f803f80u, 0x3f803f80u);
        mma16816(lo, a0, a1, a2, a3, a0, a2);
        mma16816(hi, a0, a1, a2, a3, a1, a3);
      }
      if (qd == (g >> 1)) {
        asm volatile("st.shared.v2.f32 [%0], {%1,%2};" :: "r"(sm + CV_QS + warp * 128 + g * 8), "f"(sum[0]), "f"((g & 1) ? lo[1] : lo[0]) : "memory");
        asm volatile("st.shared.v2.f32 [%0], {%1,%2};" :: "r"(sm + CV_QS + warp * 128 + g * 8 + 64), "f"(sum[2]), "f"((g & 1) ? hi[3] : hi[2]) : "memory");
      }
      __syncwarp();
      mbar_arrive_if(bar + 8 * CB_QS, lane == 0);
    };
    if (tid == 0) STAMP(49);
    float acc[16][4];
#pragma unroll
    for (int j = 0; j < 16; j++) { acc[j][0] = acc[j][1] = acc[j][2] = acc[j][3] = 0.f; }
    conv_phase<0, 4, 0, 8, 0, 16>(acc, abase, bbase, hidden_zero(ub));
    stage_y<0, 4>(acc, ys, 0);
    if (tid == 0) STAMP(57);
    mbar_wait_plain(bar + 8 * CB_K1, 0);
    mbar_wait_plain(bar + 8 * CB_O1, 0);
    conv_phase<0, 4, 8, 16, 0, 16>(acc, abase, bbase, hidden_zero(ub));
    if (tid == 0) STAMP(58);
    q_sums();
    mbar_wait_plain(bar + 8 * CB_U1, 0);
    conv_phase<4, CV_JS - 4, 0, CV_JS - 4, 0, CV_JS>(acc, abase, bbase, hidden_zero(ub));
    stage_y<4, CV_JS>(acc, ys, bar + 8 * CB_Y1);
    if (tid == 0) STAMP(59);
    mbar_wait_plain(bar + 8 * CB_U2, 0);
    if (tid == 0) BSTAMP(55, kt);
    conv_phase<4, 12, 0, 12, CV_JS, 16>(acc, abase, bbase, hidden_zero(ub));
    stage_y<CV_JS, 16>(acc, ys, bar + 8 * CB_Y2);
    if (tid == 0) STAMP(50);
    if (tid == 32) STAMP(62);
  }
  {
    const int ch = lane & 7;
    const uint32_t ya = sm + CV_V + ch * CV_Y_CH + (mi & 1) * 512 + (mi >> 1) * 16;
    const uint32_t ua = ub + ch * CV_U_CH + (mi & 1) * CV_U_PLANE + (8 + (mi >> 1)) * 16;
    const uint32_t qa = sm + CV_K + 128 + (16 * (mi >> 1) + 15 - 8 * (mi & 1) - ch) * 16;
    char* xo = reinterpret_cast<char*>(g_x3[0]) + (size_t)b * CB_BYTES + (15 - g) * 16 + qd * 4;
    const uint32_t yo = sm + CV_K + 128 + ((7 - g) * 4 + qd) * 8;
    int budget = SPIN_LIMIT;
    uint32_t ep = 0;
    if (warp > 9) {
      if (tid == 320) STAMP(53);
      ep = ld_relaxed(&g_epoch);
#pragma unroll 1
      while (ld_relaxed(&g_qcnt) - 128 * ep < 128 && --budget > 0) __nanosleep(100);
      if (tid == 320) STAMP(43);
    }
#pragma unroll 1
    for (int part = warp < 8; part < 2; part++) {
      if (warp == 9 && part) break;
      if (warp > 9) {
        uint4 v[8];
#pragma unroll 1
        do {
          uint32_t ok = 1;
#pragma unroll
          for (int y = 0; y < 8; y++) {
            asm volatile("ld.relaxed.gpu.global.v4.u32 {%0,%1,%2,%3}, [%4];" : "=r"(v[y].x), "=r"(v[y].y), "=r"(v[y].z), "=r"(v[y].w)
                         : "l"(g_qstat + 1024 * part + 2 * (tid & 63) + 128 * y) : "memory");
            ok &= both_valid(v[y].x, v[y].z, ep);
          }
          if (__all_sync(0xffffffffu, ok)) break;
        } while (--budget > 0);
#pragma unroll
        for (int y = 0; y < 8; y++) sts128(sm + (part ? CV_ST1 : CV_ST0) + (tid & 63) * 16 + 1024 * y, make_uint4(v[y].x | 1u, v[y].y, v[y].z | 1u, v[y].w));
        __syncwarp();
        mbar_arrive_if(bar + 8 * (CB_ST0 + part), lane == 0);
      }
      mbar_wait_plain(bar + 8 * (CB_ST0 + part), 0);
      mbar_wait_plain(bar + 8 * (CB_QC0 + part), 0);
      if (tid == 288) STAMP(63);
      mbar_wait_plain(bar + 8 * (CB_Y1 + part), 0);
      const uint32_t sa = sm + (part ? CV_ST1 - 8192 : CV_ST0) + (15 - g) * 8;
#pragma unroll 1
      for (int u = part ? 4 * CV_JS + warp - 2 * (warp > 8) : warp - 9; u < (part ? 64 : 4 * CV_JS); u += part ? 10 : 3) {
        uint32_t y[4], uu[4], qq[4];
        ldsm_x4_t(ya + ((u >> 4) * (CV_VQ - 512) + u * 32), y[0], y[1], y[2], y[3]);
        ldsm_x4_t(ua + u * 32, uu[0], uu[1], uu[2], uu[3]);
        ldsm_x4(qa + u * 512, qq[0], qq[1], qq[2], qq[3]);
#pragma unroll
        for (int i = 0; i < 4; i++) {
          const int off = 16 * (i >> 1) - 8 * (i & 1);
          const float2 s = lds_f2(sa + (u * 256 + off * 8));
          y[i] = badd2(y[i], bmul2(uu[i], dpair));
          stg32(xo + (uint32_t)u * 512 + off * 16, gate_pair(qq[i], y[i], __float_as_uint(s.x), __float_as_uint(s.y)));
        }
        asm volatile("st.shared.v2.u32 [%0], {%1,%2};" :: "r"(yo + u * 512), "r"(y[1]), "r"(y[0]) : "memory");
        asm volatile("st.shared.v2.u32 [%0], {%1,%2};" :: "r"(yo + u * 512 + 256), "r"(y[3]), "r"(y[2]) : "memory");
      }
      __syncwarp();
      mbar_arrive_if(bar + 8 * (part ? CB_P2 : CB_P1), lane == 0);
    }
  }
  if (warp == 9) {
    mbar_wait_plain(bar + 8 * CB_P1, 0);
    if (elect_one()) {
      STAMP(61);
      red_release(&g_xcnt[b >> 3]);
      fence_async_smem();
      bulk_store(reinterpret_cast<char*>(g_y) + (size_t)b * CB_BYTES, sm + CV_K + 128, 16384);
      bulk_commit();
      bulk_wait_all();
      mbar_arrive(bar + 8 * CB_YOUT);
    }
  }
  if (tid == 0) STAMP(51);
}

constexpr int NA = 5, A_SLOT = 68 * 128;
constexpr int SM_B = 1024;
constexpr int SM_A = SM_B + 98304;
constexpr int SM_X = SM_A + 2 * NA * A_SLOT;
constexpr int SM_CS1 = CV_END;
constexpr int SM_CS3 = SM_CS1 + 512;
static_assert(SM_X % 1024 == 0 && SM_X + 32768 <= SM_CS1 && SM_B + 2 * 16384 == CV_X && SM_A + NA * A_SLOT == CV_U, "layout");
constexpr int BAR_FULLA = 0, BAR_FULLB = 16, BAR_TURN = 24, BAR_OWN = 26;
constexpr int BAR_EMPTYA = 28, BAR_EMPTYB = BAR_EMPTYA + 18, BAR_CS = BAR_EMPTYB + 9;
constexpr int BAR_PUB = 56;
constexpr int BAR_END = 84;
constexpr int SM_RS = SM_CS3 + 1792;
constexpr int RS_G1 = 2 * 68 * 8;
constexpr int MEGA_SMEM = SM_RS + 2 * RS_G1;
static_assert(MEGA_SMEM <= 232448, "shared memory");
#define LEAD 4
#define LEAD3 2

template <int N> struct BGeo;
template <> struct BGeo<128> { static constexpr int SLOTS = 6, BYTES = 16384; };
template <> struct BGeo<256> { static constexpr int SLOTS = 3, BYTES = 32768; };
template <> struct BGeo<192> { static constexpr int SLOTS = 4, BYTES = 24576; };
__host__ __device__ constexpr int first_slot(int s) { return s == 0 || s == 2 ? 2 : 0; }
__device__ __forceinline__ bool starts_local(int l, int s) { return s == 2 || s == 1 - l; }
__device__ __forceinline__ int token_shift(int j) { return ((j >> 1) & 1 ? 1 : -1) * (1 + (j >> 2)); }

struct Ctx {
  uint32_t sm;
  uint32_t bar;
  int i, j, r;
  int bid;
  uint32_t ep;
};

struct Pipe {
  uint32_t ko, kp;
  uint32_t po;
  uint32_t a0, a1, ar;
  uint32_t b;
  uint32_t keep;
  uint32_t sh, wide;
  uint32_t turn;
  int budget;
  uint32_t rel;
  bool signals;
  __device__ __forceinline__ void release() const {
    asm volatile("{\n.reg .pred p;\nsetp.ne.b32 p, %1, 0;\n@p mbarrier.arrive.shared::cluster.b64 _, [%0];\n}" :: "r"(rel + po), "r"((uint32_t)signals) : "memory");
  }
  __device__ __forceinline__ void drain() { wg_wait<0>(); release(); po = 64; }
};
__device__ __forceinline__ uint32_t desc_a(const Ctx& c, int off) { return ((c.sm & 0x3FFFFu) >> 4) + 0x400000u + (off >> 4); }
__device__ __forceinline__ uint32_t desc_b(const Ctx& c, int off) { return ((c.sm & 0x3FFFFu) >> 4) + 0x2000000u + ((SM_B + off) >> 4); }

template <int N, bool PRED, bool SHIFT = false, class Extra>
__device__ __forceinline__ void gemm_step(float (&acc)[N / 2], const Ctx& c, int wg, Pipe& p, Extra&& extra) {
  using G = BGeo<N>;
  const uint32_t fa = c.bar + 8 * BAR_FULLA + 64 * wg + p.ko, fb = c.bar + 8 * BAR_FULLB + p.ko;
#pragma unroll 1
  while (true) {
    uint32_t ready;
    asm volatile("{\n.reg .pred p, q;\nmbarrier.try_wait.parity.shared::cta.b64 p, [%1], %3;\nmbarrier.try_wait.parity.shared::cta.b64 q, [%2], %3;\n"
                 "and.pred p, p, q;\nselp.b32 %0, 1, 0, p;\n}" : "=r"(ready) : "r"(fa), "r"(fb), "r"(p.kp) : "memory");
    if (ready || --p.budget <= 0) break;
  }
  wg_fence();
  const uint32_t a = SHIFT ? p.a0 + (p.sh & 3) + (p.wide << 16) : p.a0, ak = SHIFT ? 128 + 2 * p.wide : 128;
  if constexpr (SHIFT) p.sh >>= 2;
  if constexpr (PRED) { Mma<N>::ss(acc, a, p.b, p.keep); p.keep = 1; } else Mma<N>::ss(acc, a, p.b);
#pragma unroll
  for (int kk = 1; kk < 4; kk++) Mma<N>::ss(acc, a + kk * ak, p.b + kk * 128);
  wg_commit();
  extra();
  wg_wait<1>();
  p.release();
  p.po = p.ko;
  p.ko = (p.ko + 8) & 63;
  p.kp ^= p.ko == 0;
  p.a0 = p.a1; p.a1 = p.ar;
  p.ar = p.ar == desc_a(c, SM_A + (NA - 1) * A_SLOT) + wg * NA * (A_SLOT >> 4) ? p.ar - (NA - 1) * (A_SLOT >> 4) : p.ar + (A_SLOT >> 4);
  p.b = p.b == desc_b(c, (G::SLOTS - 1) * G::BYTES) ? desc_b(c, 0) : p.b + (G::BYTES >> 4);
}
template <int N>
__device__ __forceinline__ void gemm_begin(const Ctx& c, int wg, int wq, Pipe& p, int s, bool local) {
  if (local) {
    fence_async_smem();
    named_bar(2 + wg, 128);
    mbar_arrive_if(c.bar + 8 * BAR_FULLA + 64 * wg + 8 * (threadIdx.x & 1), (threadIdx.x & 126) == 96);
    if (wq < 2) {
      mbar_wait(c.bar + 8 * (BAR_EMPTYA + 9 * wg + 8 - NA + wq), p.kp ^ 1, p.budget);
      if (elect_one()) {
        const uint32_t peer = mapa(c.sm, c.r ^ 1), bar = peer + SM_BAR + 8 * (BAR_FULLA + 8 * wg + 2 + wq);
        mbar_expect_tx_cluster(bar, 8192);
        bulk_copy_cluster(peer + (((wq ? p.a1 : p.a0) - desc_a(c, 0)) << 4), c.sm + SM_X + (2 * wg + wq) * 8192, 8192, bar);
      }
      __syncwarp();
    }
  }
  asm volatile("{\n.reg .pred p;\nsetp.ne.b32 p, %3, 0;\nselp.b32 %2, %0, %2, p;\nselp.b32 %0, %4, %0, p;\nselp.b32 %1, %5, %1, p;\n}"
               : "+r"(p.a0), "+r"(p.a1), "+r"(p.ar) : "r"((uint32_t)local), "r"(desc_a(c, SM_X) + wg * 1024), "r"(desc_a(c, SM_X + 8192) + wg * 1024));
  p.b = desc_b(c, first_slot(s) * BGeo<N>::BYTES);
}
template <class Hook>
__device__ __forceinline__ void yield_turn(const Ctx& c, int wg, Pipe& p, Hook&& hook) {
  if (wg == 1) p.drain();
  hook();
  if (wg == 1) mbar_wait(c.bar + 8 * BAR_TURN, p.turn, p.budget);
  p.turn ^= 1;
}
__device__ __forceinline__ void pass_turn(const Ctx& c, bool now) { mbar_arrive_if(c.bar + 8 * BAR_TURN, now && threadIdx.x == 96); }
struct Nop { __device__ __forceinline__ void operator()() const {} };
template <int N, bool PRED, bool SHIFT = false, class Hook>
__device__ __forceinline__ void gemm_steps(float (&acc)[N / 2], const Ctx& c, int wg, Pipe& p, int count, Hook&& hook) {
  constexpr int lead = N == 128 ? LEAD : LEAD3;
  int m = count - lead;
#pragma unroll 1
  do { gemm_step<N, PRED, SHIFT>(acc, c, wg, p, Nop()); } while (--m > 0);
  yield_turn(c, wg, p, hook);
#pragma unroll 1
  for (int n = lead - 1; n >= 0; n--) {
    gemm_step<N, false, SHIFT>(acc, c, wg, p, Nop());
    pass_turn(c, n == 1);
  }
}

__device__ __forceinline__ void put_stat(float2* gdst, float s, float q, bool cond, uint32_t ep) {
  const float m = s * (1.f / 128), v = fmaxf(fmaf(-m, s, q), 0.f);
  asm volatile("{\n.reg .pred p;\nsetp.ne.b32 p, %3, 0;\n@p st.relaxed.gpu.global.v2.b32 [%0], {%1,%2};\n}"
               :: "l"(gdst), "r"(__float_as_uint(m)), "r"(tagged(v, ep)), "r"((uint32_t)cond) : "memory");
}
__device__ __forceinline__ void put_partial(const float (&v)[64], float2* gdst, uint32_t ep) {
  float s[4] = {v[0], v[1], v[2], v[3]}, q[4] = {v[0] * v[0], v[1] * v[1], v[2] * v[2], v[3] * v[3]};
#pragma unroll
  for (int x = 4; x < 64; x++) { s[x & 3] += v[x]; q[x & 3] = fmaf(v[x], v[x], q[x & 3]); }
  const bool odd = threadIdx.x & 1;
  const float s0 = s[0] + s[1], s1 = s[2] + s[3], q0 = q[0] + q[1], q1 = q[2] + q[3];
  float ss = (odd ? s1 : s0) + __shfl_xor_sync(0xffffffffu, odd ? s0 : s1, 1);
  float qq = (odd ? q1 : q0) + __shfl_xor_sync(0xffffffffu, odd ? q0 : q1, 1);
  ss += __shfl_xor_sync(0xffffffffu, ss, 2);
  qq += __shfl_xor_sync(0xffffffffu, qq, 2);
  put_stat(gdst + (odd ? 8 : 0), ss, qq, !(threadIdx.x & 2), ep);
}
struct RowStats {
  float2 p[4];
  __device__ __forceinline__ void load(const float2* r0, const float2* r1) {
#pragma unroll
    for (int x = 0; x < 4; x++)
      asm volatile("ld.relaxed.gpu.global.v2.f32 {%0,%1}, [%2];" : "=f"(p[x].x), "=f"(p[x].y) : "l"((x & 2 ? r1 : r0) + (x & 1) * SEQ) : "memory");
  }
  __device__ __forceinline__ void finish(const float2* r0, const float2* r1, int& budget, float2& s0, float2& s1) {
#pragma unroll 1
    while (!__all_sync(0xffffffffu, both_valid(__float_as_uint(p[0].y), __float_as_uint(p[1].y), 0) & both_valid(__float_as_uint(p[2].y), __float_as_uint(p[3].y), 0) & 1)) {
      if (--budget <= 0) break;
      load(r0, r1);
    }
#pragma unroll
    for (int h = 0; h < 2; h++) {
      const float2 a = p[2 * h], b = p[2 * h + 1];
      float m = a.x + b.x;
      m += __shfl_xor_sync(0xffffffffu, m, 1);
      m += __shfl_xor_sync(0xffffffffu, m, 2);
      m *= 0.125f;
      const float ea = a.x - m, eb = b.x - m;
      float t = fmaf(fmaf(ea, ea, eb * eb), 128.f, a.y + b.y);
      t += __shfl_xor_sync(0xffffffffu, t, 1);
      t += __shfl_xor_sync(0xffffffffu, t, 2);
      (h ? s1 : s0) = make_float2(m, rsqrt_fast(fmaf(t, 1.f / DM, LN_EPS)));
    }
  }
};

__device__ __forceinline__ void emit_panel(const uint32_t* v, char* gp, uint32_t pub) {
#pragma unroll
  for (int t = 0; t < 8; t++) { stg32(gp + t * CB_BYTES, v[2 * t]); stg32(gp + t * CB_BYTES + 128, v[2 * t + 1]); }
  __syncwarp();
  mbar_arrive_if(pub, (threadIdx.x & 31) == 0);
}
template <int NT>
__device__ __forceinline__ void stage_tiles(const uint32_t* v, uint32_t sp) {
#pragma unroll
  for (int t = 0; t < NT; t += 2) stsm_x4(sp + t * 1024, v[2 * t], v[2 * t + 1], v[2 * t + 2], v[2 * t + 3]);
}

__device__ __forceinline__ float late_zero(uint32_t addr) {
  float z; asm volatile("ld.volatile.shared.f32 %0, [%1];" : "=f"(z) : "r"(addr) : "memory"); return z;
}

template <int NT>
__device__ __forceinline__ void fold_tiles(uint32_t* v, const float* acc, const float2* cs_ptr, float2 st0, float2 st1) {
  const float n0 = -st0.x * st0.y, n1 = -st1.x * st1.y;
#pragma unroll
  for (int tile = 0; tile < NT; tile++) {
    const float2 cs = cs_ptr[tile * 4];
    float a = fmaf(acc[4 * tile + 0], st0.y, n0 * cs.x), b = fmaf(acc[4 * tile + 1], st0.y, n0 * cs.y);
    float cc = fmaf(acc[4 * tile + 2], st1.y, n1 * cs.x), d = fmaf(acc[4 * tile + 3], st1.y, n1 * cs.y);
    v[2 * tile] = pack_bf16(gelu_from_half(a), gelu_from_half(b));
    v[2 * tile + 1] = pack_bf16(gelu_from_half(cc), gelu_from_half(d));
  }
}

__device__ __forceinline__ void move_reg(uint32_t& d, uint32_t s) { asm volatile("mov.b32 %0, %1;" : "=r"(d) : "r"(s)); }
__device__ __forceinline__ void move_reg(float& d, float s) { asm volatile("mov.f32 %0, %1;" : "=f"(d) : "f"(s)); }
template <int CH, int LO, int HI, class T, int NR>
__device__ __forceinline__ void pick_group(T (&held)[NR], int idx) {
  if constexpr (HI - LO == 1) {
#pragma unroll
    for (int x = 0; x < CH; x++) move_reg(held[x], held[CH * LO + x]);
  } else {
    constexpr int MID = (LO + HI) / 2;
    if (idx < MID) pick_group<CH, LO, MID>(held, idx); else pick_group<CH, MID, HI>(held, idx);
  }
}
template <int CH>
__device__ __forceinline__ void gelu_chunk(const uint32_t* t, char* gp) {
#pragma unroll
  for (int x = 0; x < CH; x++) stg32(gp + (x >> 1) * CB_BYTES + (x & 1) * 128, gelu_pair_f16(t[x]));
}

#define REG_CONS 216
#define REG_PROD 72
__global__ void __cluster_dims__(2, 1, 1) __launch_bounds__(384, 1)
fused_kernel(const __grid_constant__ Params maps) {
  extern __shared__ __align__(1024) char smem[];
  const int tid = threadIdx.x, lane = tid & 31;
  const int warp = __shfl_sync(0xffffffffu, tid >> 5, 0), wg = warp >> 2;
  if (tid == 0) STAMP(48);
  const uint32_t sm0 = opaque(smem_u32(smem));
  if (elect_one()) {
    if (warp == 8) {
#pragma unroll
      for (int x = 0; x < CB_Q1; x++) mbar_init(sm0 + CV_BAR + 8 * x, 1);
      asm volatile("fence.mbarrier_init.release.cluster;" ::: "memory");
      load_k(maps, sm0, 0);
#pragma unroll
      for (int y = 0; y < 2; y++) {
        mbar_expect_tx(sm0 + CV_BAR + 8 * (CB_QA + y), 8192);
        load_kv(maps, sm0, y, CB_QA + y);
      }
#pragma unroll
      for (int x = CB_Q1; x < CB_ST0; x++) mbar_init(sm0 + CV_BAR + 8 * x, x < CB_QS ? 1 : x == CB_QS ? 8 : 3);
    } else if (warp == 9) {
#pragma unroll
      for (int x = CB_ST0; x < CB_COUNT; x++) mbar_init(sm0 + CV_BAR + 8 * x, x < CB_O1 ? 2 : x < CB_Y1 ? 3 : x < CB_P2 ? 8 : x == CB_P2 ? 10 : x == CB_YOUT ? 5 : x < CB_STAT ? 2 : 1);
    } else if (warp < 2) {
      asm volatile("prefetch.tensormap [%0];" :: "l"(&maps.m[M_K + warp]) : "memory");
    }
#pragma unroll
    for (int x = 0; x < 7; x++) mbar_init(sm0 + SM_BAR + 56 * warp + 8 * x, 1 << wg);
    asm volatile("fence.mbarrier_init.release.cluster;" ::: "memory");
    if (warp == 11) {
      sts32(sm0 + SM_ZERO, 0);
      const uint32_t t = tpc_id();
      if (t < 8 || (t >= 62 && t < 66)) asm volatile("{\n.reg .b32 c;\nmov.u32 c, %%clock;\nst.relaxed.gpu.global.u32 [%0], c;\n}" :: "l"(g_role + (t < 8 ? t + 4 : t - 50)) : "memory");
    }
  }
  static_assert(BAR_END == 84, "start-up work of 12 warps");
  __syncwarp();
  if (warp != 8) asm volatile("barrier.cluster.arrive.relaxed.aligned;" ::: "memory");
  conv_part(maps, sm0, warp);
  __syncwarp();
  asm volatile("barrier.cluster.wait.acquire.aligned;" ::: "memory");
  Ctx c;
  c.sm = sm0;
  c.bar = c.sm + SM_BAR;
  c.r = blockIdx.x & 1;
  {
    uint32_t role;
    asm volatile("ld.shared::cluster.u32 %0, [%1];" : "=r"(role) : "r"(mapa(sm0 + SM_ROLE, 0)) : "memory");
    role = __shfl_sync(0xffffffffu, role, 0);
    c.i = role >> 2; c.j = (role & 3) * 2 + c.r;
    c.bid = c.i * 8 + c.j;
    asm volatile("ld.shared.u32 %0, [%1];" : "=r"(c.ep) : "r"(c.sm + SM_EPOCH) : "memory");
  }

  if (tid == 0) MSTAMP(45);
  if (wg == 2) {
    reg_dealloc<REG_PROD>();
    int budget = SPIN_LIMIT;
    if (warp == 8) {
      const int hh = 16 * c.r + c.i;
      const uint32_t full0 = c.bar + 8 * (BAR_FULLA + c.r * 8), empty0 = c.bar + 8 * (BAR_EMPTYA + c.r * 9), full_peer = mapa(full0, c.r ^ 1);
      const uint32_t ring0 = c.sm + SM_A + c.r * NA * A_SLOT;
      const int nb = hh + (lane & 8 ? (lane & 2) - 1 : 0);
      const uint32_t* lf = g_flag + ((nb >= 0 && nb < 32 ? nb : hh) * 8 + (lane & 7)) * FS;
      const uint32_t* xf = g_xcnt + (hh + ((c.j >> 1) & 1) >= 16 ? 16 : 0) + (lane & 15);
      const uint32_t cb = c.sm + CV_BAR;
      if (lane == 0) mbar_arrive(cb + 8 * CB_XFREE);
      mbar_wait(cb + 8 * CB_Y2, 0, budget);
      if (lane == 0) STAMP(60);
      mbar_wait(cb + 8 * CB_P1, 0, budget);
      fence_async_smem();
      if (lane < 2) mbar_arrive_cluster(mapa(cb + 8 * CB_EARLY, lane));
      int seen = ld_relaxed(xf) - 8 * c.ep;
      mbar_wait(cb + 8 * (CB_EARLY + c.r), 0, budget);
      fence_async_global();
      if (lane == 0) MSTAMP(46);
      uint32_t slot = ring0;
      int k = 0;
#pragma unroll 1
      for (int ph = 0; ph < 10; ph++) {
        const int l = ph >= 5, s = ph - 5 * l;
        const CUtensorMap* m = &maps.m[s == 0 ? M_X3S + l : s == 1 ? M_H + l : s == 4 ? M_HID : M_X1];
        const uint32_t bytes = s == l ? A_SLOT : 8192;
        const bool local = starts_local(l, s);
        const int np = ph == 0 ? 1 : s == 4 ? 7 : 2, cnt = ph == 0 ? 16 : local ? 6 : 8, e0 = ph == 0 ? 2 * (c.j & 6) : (c.j & 6) + (local ? 2 : 0);
        const int need0 = ph == 0 ? 8 : 13 * l + (s == 0 ? 1 : s == 1 ? 3 : s == 4 ? 7 : 5);
        const uint32_t up = ph == 0 ? (c.j & 2 ? 0u : 0xffffu) : ph == 6 ? 0x33u : 0u;
        const uint32_t* fp = ph == 0 ? xf : lf;
        const uint32_t base = ph == 0 ? 8 * c.ep : 32 * c.ep;
        const bool polls = lane < (s == l ? 16 : 8);
        if (ph == 1) seen = 0;
        if (local) {
          k += 4;
          slot += slot >= ring0 + (NA - 2) * A_SLOT ? (2 - NA) * A_SLOT : 2 * A_SLOT;
        }
#pragma unroll 1
        for (int p = 0; p < np; p++) {
          uint32_t ready = __ballot_sync(0xffffffffu, seen >= need0 + p);
          if (ph == 6) ready &= ready >> 8;
#pragma unroll 1
          for (int x = 0; x < cnt; x++) {
            const int e = (e0 + x) & (ph == 0 ? 15 : 7);
            const uint32_t off = 8 * (k & 7);
            mbar_wait(empty0 + 8 * ((k - NA) & 7), ((k - NA) >> 3) & 1, budget);
            if (elect_one()) {
              mbar_expect_tx(full0 + off, bytes);
              mbar_expect_tx_cluster(full_peer + off, bytes);
            }
            if (!((ready >> e) & 1)) {
#pragma unroll 1
              do {
                if (polls) seen = ld_relaxed(fp) - base;
                ready = __ballot_sync(0xffffffffu, seen >= need0 + p);
                if (ph == 6) ready &= ready >> 8;
              } while (!((ready >> e) & 1) && --budget > 0);
              fence_async_global();
            }
            if (elect_one()) tma_2d_mc(slot, m, full0 + off, 128 * hh - 8 * ((up >> e) & 1), (np * e + p) * 8, (uint16_t)3);
            slot += slot == ring0 + (NA - 1) * A_SLOT ? (1 - NA) * A_SLOT : A_SLOT;
            k++;
          }
        }
      }
    } else if (warp == 9) {
      const uint32_t e8 = __funnelshift_r(0x76543210u, 0x76543210u, 4 * (c.j & 6));
      int k = 0;
#pragma unroll 1
      for (int ph = 0; ph < 10; ph++) {
        const int l = ph >= 5, s = ph - 5 * l;
        const uint32_t bytes = s == 2 ? 32768 : s == 3 ? 24576 : 16384, slots = s == 2 ? 3 : s == 3 ? 4 : 6;
        uint32_t dist = s == 2 ? 0x33333345u : s == 3 ? 0x44444333u : s == 4 ? 0x66655544u : 0x66666666u;
        const CUtensorMap* m = &maps.m[M_W1 + s];
        const int np = s == 4 ? 7 : 2;
        const int panel0 = s == 2 ? 7 * c.j : s == 3 ? 7 * c.j + 4 : 2 * c.j;
        const bool local = starts_local(l, s), direct = local || ph == 0;
        uint32_t slot = c.sm + SM_B + first_slot(s) * bytes;
#pragma unroll 1
        for (int o = 0; o < np; o++) {
          uint32_t tab = e8;
          if (local) tab = o ? (e8 >> 24 << 1) | ((e8 << 1) & 0xffffff00u) | 0x11111100u : (0x3210u ^ (c.j * 0x2222u)) | (e8 >> 8 << 17);
          if (ph == 0) tab = (c.j & 2 ? 0xba987654u : 0x76543210u) ^ (((c.j >> 2) ^ o) * 0x88888888u);
          const int mul = direct ? 64 : 64 * np, add = direct ? 0 : 64 * o;
#pragma unroll 1
          for (uint32_t bar = c.bar + 8 * BAR_FULLB; bar < c.bar + 8 * BAR_FULLB + 64; bar += 8) {
            const int last = k - (dist & 15), row = (tab & 15) * mul + add;
            if (last < 0) {
              mbar_wait(c.sm + CV_BAR + 8 * (k < 2 ? CB_XFREE : k < 5 ? CB_EARLY : CB_YOUT), 0, budget);
              fence_async_smem();
            }
            mbar_wait(c.bar + 8 * (BAR_EMPTYB + (last & 7)), (last >> 3) & 1, budget);
            if (elect_one()) {
              mbar_expect_tx(bar, bytes);
              tma_3d(slot, m, bar, 0, row, panel0);
            }
            slot += bytes;
            if (slot == c.sm + SM_B + 98304) slot = c.sm + SM_B;
            dist = __funnelshift_r(dist, slots, 4);
            tab >>= 4;
            k++;
          }
        }
      }
    } else {
      const int w = warp - 10;
      const int row0 = 64 * (16 * w + c.i);
      mbar_wait(c.sm + CV_BAR + 8 * CB_P2, 0, budget);
      if (w == 0) {
        fence_async_smem();
        if (lane < 2) mbar_arrive_cluster(mapa(c.sm + CV_BAR + 8 * CB_LATE, lane));
      } else if (elect_one()) {
        red_release(&g_xcnt[16 + (blockIdx.x >> 3)]);
        mbar_arrive(c.bar + 8 * BAR_REL);
        MSTAMP(44);
      }
      __syncwarp();
      uint32_t* my_flag = g_flag + ((16 * w + c.i) * 8 + c.j) * FS;
#pragma unroll 1
      for (int pc = 1; pc < 26; pc++) {
        const int l = pc >= 13, u = pc - 13 * l;
        if (pc > 1) {
          if (pc == 8) { reinterpret_cast<uint4*>(&g_part[2][c.j][row0])[lane] = make_uint4(0, 0, 0, 0); __syncwarp(); }
          mbar_wait(c.bar + 8 * (BAR_PUB + 13 * w + u), u < 2 ? 0 : l, budget);
          st_release(my_flag, 32 * c.ep + pc + 1);
        }
        float2* part = &g_part[3 * l + (u == 5)][0][0];
#pragma unroll 1
        for (uint32_t jobs = pc == 1 ? 0x453u : u == 5 ? 0x421u : u == 1 ? 4u : 0u; jobs; jobs >>= 4) {
          const int job = jobs & 15;
          if (job < 3) {
            const int r = 32 * (job - 1) + lane;
            float s0 = 0.f, s1 = 0.f, q0 = 0.f, q1 = 0.f;
#pragma unroll 2
            for (int x = 0; x < 16; x++) {
              uint32_t v[4];
              asm volatile("ld.shared.v4.u32 {%0,%1,%2,%3}, [%4];" : "=r"(v[0]), "=r"(v[1]), "=r"(v[2]), "=r"(v[3])
                           : "r"(c.sm + SM_X + w * 16384 + x * 1024 + r * 16) : "memory");
#pragma unroll
              for (int y = 0; y < 4; y++) {
                const float a = bf_lo(v[y]), b = bf_hi(v[y]);
                s0 += a; s1 += b; q0 = fmaf(a, a, q0); q1 = fmaf(b, b, q1);
              }
            }
            put_stat(part + c.j * SEQ + row0 + r, s0 + s1, q0 + q1, true, c.ep);
          } else if (job == 3) {
            if (w == 1) {
              mbar_wait(c.sm + CV_BAR + 8 * CB_YOUT, 0, budget);
              mbar_wait(c.sm + CV_BAR + 8 * CB_EARLY, 0, budget);
              if (lane == 0) red_release(&g_xcnt[32 + (blockIdx.x >> 3)]);
              __syncwarp();
            }
            uint32_t xseen;
#pragma unroll 1
            do {
              asm volatile("ld.acquire.gpu.global.u32 %0, [%1];" : "=r"(xseen) : "l"(g_xcnt + 32 + (lane & 15)) : "memory");
            } while (!__all_sync(0xffffffffu, (int)(xseen - 8 * c.ep) >= 8) && --budget > 0);
            if (w == 0) {
              float4 s = make_float4(0.f, 0.f, 0.f, 0.f);
#pragma unroll
              for (int x = 0; x < 4; x++) {
                const float4 v = __ldcg(reinterpret_cast<const float4*>(&g_cs1[x][c.j * 128]) + lane);
                s.x += v.x; s.y += v.y; s.z += v.z; s.w += v.w;
              }
              reinterpret_cast<float4*>(smem + SM_CS1)[lane] = s;
            } else {
#pragma unroll
              for (int x = 0; x < 4; x++) {
                const int y = min(32 * x + lane, 111);
                const float4 v = __ldcg(reinterpret_cast<const float4*>(g_cs3 + c.j * 448) + y);
                if (x < 2) {
                  uint32_t* d = reinterpret_cast<uint32_t*>(smem + SM_CS3) + (y >> 2) * 8 + (y & 1) * 4 + ((y >> 1) & 1);
                  d[0] = pack_f16(v.x, v.y); d[2] = pack_f16(v.z, v.w);
                } else {
                  reinterpret_cast<float4*>(smem + SM_CS3)[y] = v;
                }
              }
            }
            __syncwarp();
            if (lane == 0) mbar_arrive(c.bar + 8 * BAR_CS);
            if (c.bid == 0 && w == 0 && lane <= 16) *(lane < 16 ? g_role + lane : &g_epoch) = lane < 12 ? 0 : lane < 16 ? 0x80000000u : c.ep + 1;
          } else {
            const int r = job == 4 ? 2 * lane : token_shift(c.j) > 0 ? 64 : -2;
            const float2* src = part + min(max(row0 + r, 0), SEQ - 2);
            float4 v[8];
#pragma unroll 1
            do {
              uint32_t ok = 1;
#pragma unroll
              for (int x = 0; x < 8; x++) {
                asm volatile("ld.relaxed.gpu.global.v4.f32 {%0,%1,%2,%3}, [%4];" : "=f"(v[x].x), "=f"(v[x].y), "=f"(v[x].z), "=f"(v[x].w) : "l"(src + x * SEQ) : "memory");
                ok &= both_valid(__float_as_uint(v[x].y), __float_as_uint(v[x].w), c.ep);
              }
              if (__all_sync(0xffffffffu, ok)) break;
            } while (--budget > 0);
            float ma = 0.f, mb = 0.f, ta = 0.f, tb = 0.f;
#pragma unroll
            for (int x = 0; x < 8; x++) { ma += v[x].x; mb += v[x].z; }
            ma *= 0.125f; mb *= 0.125f;
#pragma unroll
            for (int x = 0; x < 8; x++) {
              const float ea = v[x].x - ma, eb = v[x].z - mb;
              ta += fmaf(128.f * ea, ea, __uint_as_float(__float_as_uint(v[x].y) | 1u));
              tb += fmaf(128.f * eb, eb, __uint_as_float(__float_as_uint(v[x].w) | 1u));
            }
            ta *= 1.f / DM; tb *= 1.f / DM;
            const float ra = rsqrt_fast(ta + LN_EPS), rb = rsqrt_fast(tb + LN_EPS);
            *reinterpret_cast<float4*>(smem + SM_RS + (68 * w + 2 + r) * 8) = make_float4(ma, ra, mb, rb);
            const float in = (uint32_t)(row0 + r) < SEQ ? 0.5f : 0.f;
            *reinterpret_cast<float4*>(smem + SM_RS + RS_G1 + (68 * w + 2 + r) * 8) =
                make_float4(ma, in * ra * rsqrt_fast(fmaf(ta * ra, ra, LN_EPS)), mb, in * rb * rsqrt_fast(fmaf(tb * rb, rb, LN_EPS)));
            __syncwarp();
            if (job == 4 && lane == 0) mbar_arrive(c.sm + CV_BAR + 8 * (CB_STAT + w));
          }
        }
        if (pc == 6) {
          if (elect_one()) {
            const uint32_t bar = c.bar + 8 * (BAR_OWN + w);
            fence_async_global();
            fence_async_smem();
            mbar_expect_tx(bar, 16384);
            tma_2d(c.sm + SM_X + w * 16384, &maps.m[M_Y], bar, 2 * row0, 16 * c.j);
            tma_2d(c.sm + SM_X + w * 16384 + 8192, &maps.m[M_Y], bar, 2 * row0, 16 * c.j + 8);
          }
          __syncwarp();
        }
      }
    }
    cluster_exit_barrier();
  } else {
    reg_alloc<REG_CONS>();
#define WSTAMP(idx) do {} while (0)
    const int t = tid & 127, g = lane >> 2, qd = lane & 3;
    const int wrow = 64 * (16 * wg + c.i) + (t >> 5) * 16, row = wrow + g;
    const uint32_t frag = row * 16 + qd * 4 + c.j * 16 * CB_BYTES;
    const uint32_t stage = c.sm + SM_X + wg * 16384 + (lane >> 4) * 1024 + ((t >> 5) * 16 + (lane & 15)) * 16;
    const uint32_t pub = c.bar + 8 * (BAR_PUB + 13 * wg);
    const uint32_t rstat = c.sm + SM_RS + (68 * wg + 2 + (t >> 5) * 16 + g) * 8;
    Pipe p;
    p.ko = 0; p.kp = 0; p.po = 64; p.turn = 0; p.budget = SPIN_LIMIT;
    p.a0 = desc_a(c, SM_A) + wg * NA * (A_SLOT >> 4); p.a1 = p.a0 + (A_SLOT >> 4); p.ar = p.a1 + (A_SLOT >> 4);
    p.signals = t == 0 || t == 32 || t == 64;
    p.rel = mapa(c.bar + 8 * (t == 64 ? BAR_EMPTYB : BAR_EMPTYA + wg * 9), t == 32 ? c.r ^ 1 : c.r);
    auto fence_sched = [&]() { mbar_wait(c.bar + 8 * BAR_CS, 0, p.budget); };
    uint32_t x3[32];
    float acc[64];
#pragma unroll
    for (int x = 0; x < 64; x++) acc[x] = 0.f;
    pin(acc);
    const uint32_t own = opaque(c.sm + SM_A + (wg * NA + 2 * c.r) * A_SLOT + (lane >> 4) * 1088 + ((c.j & 2 ? 0 : 4) + (t >> 5) * 16 + (lane & 15)) * 16);
    WSTAMP(0);
    if (wg == 1) {
      mbar_wait(c.bar + 8 * BAR_REL, 0, p.budget);
#pragma unroll 2
      for (int x = 0; x < 8; x++)
        reinterpret_cast<uint4*>(g_y)[blockIdx.x * 2048 + 1024 + x * 128 + t] = reinterpret_cast<const uint4*>(smem + CV_K + 128 + 16384)[x * 128 + t];
      __syncwarp();
      mbar_arrive_if(c.sm + CV_BAR + 8 * CB_YOUT, lane == 0);
    }
    {
      mbar_wait(c.bar + 8 * (BAR_FULLA + 8 * wg + 2 * c.r), 0, p.budget);
      mbar_wait(c.bar + 8 * (BAR_FULLA + 8 * wg + 2 * c.r + 1), 0, p.budget);
#pragma unroll
      for (int x = 0; x < 32; x += 4) ldsm_x4(own + x * 544, x3[x], x3[x + 1], x3[x + 2], x3[x + 3]);
    }
    const uint32_t sh_g1 = opaque((token_shift(c.j) & 3) * 0x55555555u), sh_g2 = opaque(__funnelshift_r(0xaa5faa5fu, 0xaa5faa5fu, 2 * (c.j & 6)));
#pragma unroll 1
    for (int ph = 0; ph < 6; ph++) {
      const int l = ph >= 3, s = ph - 3 * l;
      p.keep = s;
      p.wide = s == l ? 4 : 0;
      p.sh = s == l ? (l ? sh_g2 : sh_g1) : 0;
      if (s < 2) {
        gemm_begin<128>(c, wg, warp & 3, p, s, s != l);
        if (s == 0) {
          float sum[2][4] = {}, lo[2][4] = {}, hi[2][4] = {};
#pragma unroll
          for (int x = 0; x < 32; x += 4) {
            mma16816(sum[x >> 4], x3[x], x3[x + 1], x3[x + 2], x3[x + 3], 0x3f803f80u, 0x3f803f80u);
            mma16816(lo[x >> 4], x3[x], x3[x + 1], x3[x + 2], x3[x + 3], x3[x], x3[x + 2]);
            mma16816(hi[x >> 4], x3[x], x3[x + 1], x3[x + 2], x3[x + 3], x3[x + 1], x3[x + 3]);
          }
          put_stat(&g_part[3 * l][c.j][row], sum[0][0] + sum[1][0], (g & 1) ? lo[0][1] + lo[1][1] : lo[0][0] + lo[1][0], qd == (g >> 1), c.ep);
          put_stat(&g_part[3 * l][c.j][row + 8], sum[0][2] + sum[1][2], (g & 1) ? hi[0][3] + hi[1][3] : hi[0][2] + hi[1][2], qd == (g >> 1), c.ep);
          WSTAMP(1 + 16 * l);
        }
      } else {
        char* hp = reinterpret_cast<char*>(g_hid) + frag + c.j * 40 * CB_BYTES;
        uint32_t held[64];
        float acc3[128];
        gemm_step<256, true>(acc3, c, wg, p, Nop());
        float2 s0 = make_float2(0.f, 0.f), s1 = s0;
        gemm_steps<256, false>(acc3, c, wg, p, 15, [&]() {
          mbar_wait(c.sm + CV_BAR + 8 * (CB_STAT + wg), 1, p.budget);
          s0 = lds_f2(rstat); s1 = lds_f2(rstat + 64);
          s0.y *= 0.5f; s1.y *= 0.5f;
        });
        p.drain();
        WSTAMP(6 + 16 * l);
#pragma unroll
        for (int x = 0; x < 64; x++) held[x] = pack_f16(acc3[2 * x] * ((x & 1) ? s1.y : s0.y), acc3[2 * x + 1] * ((x & 1) ? s1.y : s0.y));
        const uint32_t n0 = pack_f16(-s0.x * s0.y, -s0.x * s0.y), n1 = pack_f16(-s1.x * s1.y, -s1.x * s1.y);
        float accb[96];
#pragma unroll
        for (int x = 0; x < 24; x++) {
          const float2 cs = (reinterpret_cast<const float2*>(smem + SM_CS3 + 1024) + qd)[4 * x];
          accb[4 * x] = -s0.x * cs.x; accb[4 * x + 1] = -s0.x * cs.y; accb[4 * x + 2] = -s1.x * cs.x; accb[4 * x + 3] = -s1.x * cs.y;
        }
        pin(accb);
        WSTAMP(7 + 16 * l);
        gemm_begin<192>(c, wg, warp & 3, p, 3, false);
#pragma unroll 1
        for (int pn = 0; pn < 4; pn++) {
#pragma unroll
          for (int u = 0; u < 4; u++)
            gemm_step<192, false>(accb, c, wg, p, [&]() {
              const uint2 cs = reinterpret_cast<const uint2*>(smem + SM_CS3)[16 * pn + 4 * u + qd];
              const uint32_t h[4] = {hfma2(cs.x, n0, held[4 * u]), hfma2(cs.x, n1, held[4 * u + 1]), hfma2(cs.y, n0, held[4 * u + 2]), hfma2(cs.y, n1, held[4 * u + 3])};
              gelu_chunk<4>(h, hp + 2 * u * CB_BYTES);
            });
          hp += 8 * CB_BYTES;
          __syncwarp();
          mbar_arrive_if(pub + 8 * (6 + pn), lane == 0);
          if (pn < 3) pick_group<16, 1, 4>(held, pn + 1);
        }
        WSTAMP(8 + 16 * l);
#pragma unroll
        for (int x = 0; x < 32; x++) { acc[2 * x] = bf_lo(x3[x]); acc[2 * x + 1] = bf_hi(x3[x]); }
        pin(acc);
        WSTAMP(9 + 16 * l);
        gemm_begin<128>(c, wg, warp & 3, p, 4, false);
        gemm_step<128, false>(acc, c, wg, p, Nop());
        pin(accb);
#pragma unroll 1
        for (int hpn = 0; hpn < 6; hpn++) {
#pragma unroll
          for (int u = 0; u < 4; u++)
            gemm_step<128, false>(acc, c, wg, p, [&]() {
              const uint32_t h[2] = {pack_f16(accb[4 * u] * s0.y, accb[4 * u + 1] * s0.y), pack_f16(accb[4 * u + 2] * s1.y, accb[4 * u + 3] * s1.y)};
              gelu_chunk<2>(h, hp + u * CB_BYTES);
            });
          hp += 4 * CB_BYTES;
          __syncwarp();
          mbar_arrive_if(pub + 8 * (10 + (hpn >> 1)), (hpn & 1) && lane == 0);
          if (hpn < 5) pick_group<16, 1, 6>(accb, hpn + 1);
        }
        WSTAMP(12 + 16 * l);
      }
      gemm_steps<128, true, true>(acc, c, wg, p, s == 2 ? 31 : 16, Nop());
      const uint32_t z = hidden_zero(c.sm + SM_ZERO), stg = stage + z;
      char* gp = reinterpret_cast<char*>(s == 0 ? g_h : s == 1 ? g_x1 : g_x3[1]) + (frag + z);
      float2 s0, s1;
      if (s == 0) {
        mbar_wait(c.sm + CV_BAR + 8 * (CB_STAT + wg), 0, p.budget);
        const uint32_t ra = rstat + RS_G1 + (l == 0 ? 8 * token_shift(c.j) : 0);
        s0 = lds_f2(ra); s1 = lds_f2(ra + 64);
        fence_sched();
        p.drain();
        WSTAMP(2 + 16 * l);
#pragma unroll
        for (int pn = 0; pn < 2; pn++) {
          uint32_t v[16];
          if (pn == 0) {
            fold_tiles<4>(v, acc, reinterpret_cast<const float2*>(smem + SM_CS1) + qd, s0, s1);
#pragma unroll
            for (int x = 0; x < 8; x++) stg32(gp + (x >> 1) * CB_BYTES + (x & 1) * 128, v[x]);
            fence_sched();
            fold_tiles<4>(v + 8, acc + 16, reinterpret_cast<const float2*>(smem + SM_CS1) + qd + 16, s0, s1);
#pragma unroll
            for (int x = 8; x < 16; x++) stg32(gp + (x >> 1) * CB_BYTES + (x & 1) * 128, v[x]);
            __syncwarp();
            mbar_arrive_if(pub + 8 * 2, lane == 0);
          } else {
            fold_tiles<8>(v, acc + 32, reinterpret_cast<const float2*>(smem + SM_CS1) + qd + 32, s0, s1);
            emit_panel(v, gp + 8 * CB_BYTES, pub + 8 * 3);
          }
          if (l == 0) stage_tiles<8>(v, stg + pn * 8192);
        }
        s0 = lds_f2(rstat); s1 = lds_f2(rstat + 64);
        const float nb0 = -s0.x * s0.y, nb1 = -s1.x * s1.y;
#pragma unroll
        for (int x = 0; x < 32; x++) {
          acc[2 * x] = fmaf(bf_lo(x3[x]), (x & 1) ? s1.y : s0.y, (x & 1) ? nb1 : nb0);
          acc[2 * x + 1] = fmaf(bf_hi(x3[x]), (x & 1) ? s1.y : s0.y, (x & 1) ? nb1 : nb0);
        }
        WSTAMP(3 + 16 * l);
      } else if (s == 1) {
        fence_sched();
        p.drain();
        WSTAMP(4 + 16 * l);
        uint32_t v[32];
#pragma unroll
        for (int x = 0; x < 32; x++) v[x] = pack_bf16(acc[2 * x], acc[2 * x + 1]);
        emit_panel(v, gp, pub + 8 * 4);
        stage_tiles<16>(v, stg);
        gemm_begin<256>(c, wg, warp & 3, p, 2, true);
        emit_panel(v + 16, gp + 8 * CB_BYTES, pub + 8 * 5);
#pragma unroll
        for (int x = 0; x < 32; x++) x3[x] = badd2(x3[x], v[x]);
        WSTAMP(5 + 16 * l);
      } else if (l == 0) {
        float2* mine = &g_part[2][c.j][row + z];
        const float2* sp = &g_part[2][2 * qd][row + z];
        fence_sched();
        p.drain();
        WSTAMP(10);
        put_partial(acc, mine, 0);
        WSTAMP(11);
        RowStats rs;
        rs.load(sp, sp + 8);
        uint32_t yv[32];
        mbar_wait(c.bar + 8 * (BAR_OWN + wg), 0, p.budget);
#pragma unroll
        for (int x = 0; x < 16; x++)
          asm volatile("ld.shared.v2.u32 {%0,%1}, [%2];" : "=r"(yv[2 * x]), "=r"(yv[2 * x + 1]) : "r"(c.sm + SM_X + wg * 16384 + x * 1024 + t * 8) : "memory");
#pragma unroll
        for (int x = 0; x < 32; x++) asm volatile("cvt.rn.bf16x2.f32 %0, %1, %2;" : "=r"(x3[x]) : "f"(acc[2 * x + 1]), "f"(acc[2 * x]));
        rs.finish(sp, sp + 8, p.budget, s0, s1);
        WSTAMP(13);
        float nb0 = -s0.x * s0.y, nb1 = -s1.x * s1.y;
#pragma unroll
        for (int pn = 0; pn < 2; pn++) {
          if (pn == 1) { const float z = late_zero(c.sm + SM_ZERO); nb0 += z; nb1 += z; }
#pragma unroll
          for (int x = 16 * pn; x < 16 * pn + 16; x++) {
            const float r = (x & 1) ? s1.y : s0.y, nb = (x & 1) ? nb1 : nb0;
            asm("fma.rn.bf16x2 %0, %1, %2, %0;" : "+r"(x3[x]) : "r"(pack_bf16(fmaf(acc[2 * x], r, nb), fmaf(acc[2 * x + 1], r, nb))), "r"(yv[x]));
          }
          if (pn == 1) stage_tiles<16>(x3, stg);
          emit_panel(x3 + 16 * pn, gp + pn * 8 * CB_BYTES, pub + 8 * pn);
        }
      } else {
        const uint32_t ob = c.sm + SM_X + warp * 4096, oa = ob + (lane & 15) * 128 + (((lane >> 4) ^ (lane & 7)) << 4) + z;
        fence_sched();
        p.drain();
        WSTAMP(26);
#pragma unroll
        for (int pn = 0; pn < 2; pn++) {
#pragma unroll
          for (int x = 0; x < 8; x += 2) {
            const float* a = acc + 32 * pn + 4 * x;
            stsm_x4((oa ^ (x << 4)) + pn * 2048, pack_bf16(a[0], a[1]), pack_bf16(a[2], a[3]), pack_bf16(a[4], a[5]), pack_bf16(a[6], a[7]));
          }
          fence_async_smem();
          __syncwarp();
          if (elect_one()) {
            tma_store_2d(&maps.m[M_OUT], ob + pn * 2048, c.j * 128 + 64 * pn, 64 * (16 * wg + c.i) + 16 * (warp & 3));
            if (pn == 1) {
              bulk_commit();
              asm volatile("cp.async.bulk.wait_group.read 0;" ::: "memory");
            }
          }
        }
        __syncwarp();
      }
    }
    WSTAMP(27);
    cluster_exit_barrier();
    WSTAMP(30);
  }
}

typedef CUresult (*EncodeFn)(CUtensorMap*, CUtensorMapDataType, cuuint32_t, void*, const cuuint64_t*, const cuuint64_t*, const cuuint32_t*,
                             const cuuint32_t*, CUtensorMapInterleave, CUtensorMapSwizzle, CUtensorMapL2promotion, CUtensorMapFloatOOBfill);

void encode(EncodeFn fn, CUtensorMap* m, CUtensorMapDataType type, const void* ptr, int rank, const cuuint64_t* dims, const cuuint64_t* strides,
            const cuuint32_t* box, CUtensorMapSwizzle swizzle, CUtensorMapL2promotion promo = CU_TENSOR_MAP_L2_PROMOTION_L2_128B) {
  const cuuint32_t es[3] = {1, 1, 1};
  fn(m, type, rank, const_cast<void*>(ptr), dims, strides, box, es, CU_TENSOR_MAP_INTERLEAVE_NONE, swizzle, promo, CU_TENSOR_MAP_FLOAT_OOB_FILL_NONE);
}
void map_act(EncodeFn fn, CUtensorMap* m, const void* ptr, int cols, int rows = 64) {
  const cuuint64_t dims[2] = {(cuuint64_t)SEQ * 2, (cuuint64_t)cols / 8}, st[1] = {(cuuint64_t)CB_BYTES};
  const cuuint32_t box[2] = {(cuuint32_t)rows * 2, 8};
  encode(fn, m, CU_TENSOR_MAP_DATA_TYPE_UINT64, ptr, 2, dims, st, box, CU_TENSOR_MAP_SWIZZLE_NONE);
}
void map_rows(EncodeFn fn, CUtensorMap* m, const void* ptr, int rows, int cols, int box_rows, int box_cols, CUtensorMapSwizzle swizzle,
              CUtensorMapL2promotion promo) {
  const cuuint64_t dims[2] = {(cuuint64_t)cols, (cuuint64_t)rows}, st[1] = {(cuuint64_t)cols * 2};
  const cuuint32_t box[2] = {(cuuint32_t)box_cols, (cuuint32_t)box_rows};
  encode(fn, m, CU_TENSOR_MAP_DATA_TYPE_BFLOAT16, ptr, 2, dims, st, box, swizzle, promo);
}
void map_w(EncodeFn fn, CUtensorMap* m, const void* ptr, int rows, int cols, int panels) {
  const cuuint64_t dims[3] = {64, (cuuint64_t)rows, (cuuint64_t)cols / 64}, st[2] = {(cuuint64_t)cols * 2, 128};
  const cuuint32_t box[3] = {64, 64, (cuuint32_t)panels};
  encode(fn, m, CU_TENSOR_MAP_DATA_TYPE_BFLOAT16, ptr, 3, dims, st, box, CU_TENSOR_MAP_SWIZZLE_128B);
}

}

extern "C" void kernel_launch(void* const* d_in, const int* in_sizes, int n_in, void* d_out, int out_size) {
  (void)in_sizes; (void)n_in; (void)out_size;
  const bf16* q = (const bf16*)d_in[0];
  const bf16* k = (const bf16*)d_in[1];
  const bf16* v = (const bf16*)d_in[2];
  const bf16* shift_k = (const bf16*)d_in[3];
  const bf16* ssm_k = (const bf16*)d_in[4];
  const bf16* ssm_d = (const bf16*)d_in[5];
  const bf16* w1 = (const bf16*)d_in[7];
  const bf16* w2 = (const bf16*)d_in[8];
  const bf16* w3 = (const bf16*)d_in[9];
  const bf16* w4 = (const bf16*)d_in[10];

  static EncodeFn fn = nullptr;
  static void *p_x3, *p_h, *p_x1, *p_hid, *p_y;
  if (!fn) {
    void* p = nullptr;
    cudaDriverEntryPointQueryResult qr;
    cudaGetDriverEntryPoint("cuTensorMapEncodeTiled", &p, cudaEnableDefault, &qr);
    fn = (EncodeFn)p;
    cudaGetSymbolAddress(&p_x3, g_x3);
    cudaGetSymbolAddress(&p_h, g_h);
    cudaGetSymbolAddress(&p_x1, g_x1);
    cudaGetSymbolAddress(&p_hid, g_hid);
    cudaGetSymbolAddress(&p_y, g_y);
    cudaFuncSetAttribute(fused_kernel, cudaFuncAttributeMaxDynamicSharedMemorySize, MEGA_SMEM);
  }
  Params maps;
  map_act(fn, &maps.m[M_X3B], (const bf16*)p_x3 + SEQ * DM, DM);
  map_act(fn, &maps.m[M_X3S], p_x3, DM, 68);
  map_act(fn, &maps.m[M_H], p_h, DM);
  map_act(fn, &maps.m[M_HS], p_h, DM, 68);
  map_act(fn, &maps.m[M_X1], p_x1, DM);
  map_act(fn, &maps.m[M_HID], p_hid, FF);
  map_act(fn, &maps.m[M_Y], p_y, DM);
  map_rows(fn, &maps.m[M_OUT], d_out, SEQ, DM, 16, 64, CU_TENSOR_MAP_SWIZZLE_128B, CU_TENSOR_MAP_L2_PROMOTION_L2_128B);
  map_w(fn, &maps.m[M_W1], w1, DM, DM, 2);
  map_w(fn, &maps.m[M_W2], w2, DM, DM, 2);
  map_w(fn, &maps.m[M_W3A], w3, DM, FF, 4);
  map_w(fn, &maps.m[M_W3B], w3, DM, FF, 3);
  map_w(fn, &maps.m[M_W4], w4, FF, DM, 2);

  map_rows(fn, &maps.m[M_K], k, SEQ, DM, 256, 8, CU_TENSOR_MAP_SWIZZLE_NONE, CU_TENSOR_MAP_L2_PROMOTION_L2_128B);
  map_rows(fn, &maps.m[M_V], v, SEQ, DM, 256, 8, CU_TENSOR_MAP_SWIZZLE_NONE, CU_TENSOR_MAP_L2_PROMOTION_L2_128B);
  map_rows(fn, &maps.m[M_Q], q, SEQ, DM, 256, 8, CU_TENSOR_MAP_SWIZZLE_NONE, CU_TENSOR_MAP_L2_PROMOTION_L2_128B);
  map_rows(fn, &maps.m[M_W1C], w1, DM, DM, 256, 32, CU_TENSOR_MAP_SWIZZLE_64B, CU_TENSOR_MAP_L2_PROMOTION_L2_128B);
  map_rows(fn, &maps.m[M_W3C], w3, DM, FF, 256, 32, CU_TENSOR_MAP_SWIZZLE_64B, CU_TENSOR_MAP_L2_PROMOTION_L2_128B);
  maps.q = q; maps.shift_k = shift_k; maps.ssm_k = ssm_k; maps.ssm_d = ssm_d; maps.w2 = w2;
  fused_kernel<<<128, 384, MEGA_SMEM, cudaStreamPerThread>>>(maps);
}
```

```cpp
#include <cuda_runtime.h>
#include <cuda_bf16.h>
#include <cuda.h>
#include <stdint.h>

namespace {

typedef __nv_bfloat16 bf16;
constexpr int SEQ = 2048, DM = 1024, FF = 3584;
constexpr float LN_EPS = 1e-5f;

constexpr int CB_BYTES = SEQ * 16;
__device__ __align__(1024) bf16 g_x3[2][SEQ * DM];
__device__ __align__(1024) bf16 g_h[SEQ * DM];
__device__ __align__(1024) bf16 g_x1[SEQ * DM];
__device__ __align__(1024) bf16 g_hid[SEQ * FF];
__device__ __align__(1024) bf16 g_y[SEQ * DM];
__device__ __align__(128) float g_cs1[4][DM];
__device__ __align__(128) float g_cs3[FF];
__device__ __align__(128) uint32_t g_epoch;
__device__ __align__(128) float2 g_part[5][8][SEQ];
__device__ __align__(128) float2 g_qstat[SEQ];
__device__ __align__(128) uint32_t g_qcnt;
__device__ __align__(128) uint32_t g_xcnt[48];
constexpr int FS = 8;
__device__ __align__(128) uint32_t g_flag[32 * 8 * FS];
__device__ __align__(128) uint32_t g_role[16];

__device__ __forceinline__ uint32_t smem_u32(const void* p) { return (uint32_t)__cvta_generic_to_shared(p); }
__device__ __forceinline__ uint32_t opaque(uint32_t x) { uint32_t y; asm volatile("mov.u32 %0, %1;" : "=r"(y) : "r"(x)); return y; }
__device__ __forceinline__ void mbar_init(uint32_t bar, uint32_t cnt) { asm volatile("mbarrier.init.shared::cta.b64 [%0], %1;" :: "r"(bar), "r"(cnt)); }
__device__ __forceinline__ void mbar_expect_tx(uint32_t bar, uint32_t bytes) {
  asm volatile("mbarrier.arrive.expect_tx.shared::cta.b64 _, [%0], %1;" :: "r"(bar), "r"(bytes) : "memory");
}
__device__ __forceinline__ void mbar_expect_tx_cluster(uint32_t bar, uint32_t bytes) {
  asm volatile("mbarrier.arrive.expect_tx.shared::cluster.b64 _, [%0], %1;" :: "r"(bar), "r"(bytes) : "memory");
}
__device__ __forceinline__ void mbar_arrive_cluster(uint32_t bar) { asm volatile("mbarrier.arrive.shared::cluster.b64 _, [%0];" :: "r"(bar) : "memory"); }
__device__ __forceinline__ void mbar_arrive(uint32_t bar) { asm volatile("mbarrier.arrive.shared::cta.b64 _, [%0];" :: "r"(bar) : "memory"); }
__device__ __forceinline__ void mbar_arrive_if(uint32_t bar, bool cond) {
  asm volatile("{\n.reg .pred p;\nsetp.ne.b32 p, %1, 0;\n@p mbarrier.arrive.shared::cta.b64 _, [%0];\n}" :: "r"(bar), "r"((uint32_t)cond) : "memory");
}
constexpr int SPIN_LIMIT = 1 << 16;
__device__ __forceinline__ bool mbar_try(uint32_t bar, uint32_t parity) {
  uint32_t done;
  asm volatile("{\n.reg .pred p;\nmbarrier.try_wait.parity.shared::cta.b64 p, [%1], %2;\nselp.b32 %0, 1, 0, p;\n}"
               : "=r"(done) : "r"(bar), "r"(parity) : "memory");
  return done != 0;
}
__device__ __forceinline__ void mbar_wait(uint32_t bar, uint32_t parity, int& budget) {
#pragma unroll 1
  while (!mbar_try(bar, parity)) { if (--budget <= 0) break; }
}
__device__ __forceinline__ bool elect_one() {
  uint32_t p;
  asm volatile("{\n.reg .pred P;\nelect.sync _|P, 0xffffffff;\nselp.b32 %0, 1, 0, P;\n}" : "=r"(p));
  return p != 0;
}
__device__ __forceinline__ void fence_async_smem() { asm volatile("fence.proxy.async.shared::cta;" ::: "memory"); }
__device__ __forceinline__ void fence_async_global() { asm volatile("fence.proxy.async.global;" ::: "memory"); }
__device__ __forceinline__ void named_bar(int id, int n) { asm volatile("bar.sync %0, %1;" :: "r"(id), "r"(n) : "memory"); }
__device__ __forceinline__ uint4 ld_nc_u4(const void* p) {
  uint4 v; asm volatile("ld.global.nc.L1::no_allocate.v4.u32 {%0,%1,%2,%3}, [%4];" : "=r"(v.x), "=r"(v.y), "=r"(v.z), "=r"(v.w) : "l"(p)); return v;
}
__device__ __forceinline__ void tma_2d_mc(uint32_t dst, const CUtensorMap* m, uint32_t bar, int c0, int c1, uint16_t mask) {
  asm volatile("cp.async.bulk.tensor.2d.shared::cluster.global.mbarrier::complete_tx::bytes.multicast::cluster [%0], [%1, {%3, %4}], [%2], %5;"
               :: "r"(dst), "l"(m), "r"(bar), "r"(c0), "r"(c1), "h"(mask) : "memory");
}
__device__ __forceinline__ void tma_2d(uint32_t dst, const CUtensorMap* m, uint32_t bar, int c0, int c1) {
  asm volatile("cp.async.bulk.tensor.2d.shared::cluster.global.mbarrier::complete_tx::bytes [%0], [%1, {%3, %4}], [%2];"
               :: "r"(dst), "l"(m), "r"(bar), "r"(c0), "r"(c1) : "memory");
}
__device__ __forceinline__ void bulk_copy_cluster(uint32_t dst, uint32_t src, uint32_t bytes, uint32_t bar) {
  asm volatile("cp.async.bulk.shared::cluster.shared::cta.mbarrier::complete_tx::bytes [%0], [%1], %2, [%3];"
               :: "r"(dst), "r"(src), "r"(bytes), "r"(bar) : "memory");
}
__device__ __forceinline__ uint32_t mapa(uint32_t addr, uint32_t cta) {
  uint32_t r; asm volatile("mapa.shared::cluster.u32 %0, %1, %2;" : "=r"(r) : "r"(addr), "r"(cta)); return r;
}
__device__ __forceinline__ void bulk_store(void* dst, uint32_t src, uint32_t bytes) {
  asm volatile("cp.async.bulk.global.shared::cta.bulk_group [%0], [%1], %2;" :: "l"(dst), "r"(src), "r"(bytes) : "memory");
}
__device__ __forceinline__ void tma_3d(uint32_t dst, const CUtensorMap* m, uint32_t bar, int c0, int c1, int c2) {
  asm volatile("cp.async.bulk.tensor.3d.shared::cluster.global.mbarrier::complete_tx::bytes [%0], [%1, {%3, %4, %5}], [%2];"
               :: "r"(dst), "l"(m), "r"(bar), "r"(c0), "r"(c1), "r"(c2) : "memory");
}
__device__ __forceinline__ void tma_store_2d(const CUtensorMap* m, uint32_t src, int c0, int c1) {
  asm volatile("cp.async.bulk.tensor.2d.global.shared::cta.bulk_group [%0, {%2, %3}], [%1];" :: "l"(m), "r"(src), "r"(c0), "r"(c1) : "memory");
}
__device__ __forceinline__ void bulk_commit() { asm volatile("cp.async.bulk.commit_group;" ::: "memory"); }
__device__ __forceinline__ void bulk_wait_all() { asm volatile("cp.async.bulk.wait_group 0;" ::: "memory"); }
__device__ __forceinline__ void cluster_exit_barrier() {
  __syncwarp();
  asm volatile("barrier.cluster.arrive.relaxed;\nbarrier.cluster.wait;" ::: "memory");
}
__device__ __forceinline__ void wg_fence() { asm volatile("wgmma.fence.sync.aligned;" ::: "memory"); }
__device__ __forceinline__ void wg_commit() { asm volatile("wgmma.commit_group.sync.aligned;" ::: "memory"); }
template <int N> __device__ __forceinline__ void wg_wait() { asm volatile("wgmma.wait_group.sync.aligned %0;" :: "n"(N) : "memory"); }
template <int R> __device__ __forceinline__ void reg_alloc() { asm volatile("setmaxnreg.inc.sync.aligned.u32 %0;" :: "n"(R)); }
template <int R> __device__ __forceinline__ void reg_dealloc() { asm volatile("setmaxnreg.dec.sync.aligned.u32 %0;" :: "n"(R)); }
__device__ __forceinline__ void ldsm_x4(uint32_t addr, uint32_t& r0, uint32_t& r1, uint32_t& r2, uint32_t& r3) {
  asm volatile("ldmatrix.sync.aligned.m8n8.x4.shared.b16 {%0,%1,%2,%3}, [%4];" : "=r"(r0), "=r"(r1), "=r"(r2), "=r"(r3) : "r"(addr));
}
__device__ __forceinline__ void ldsm_x4_t(uint32_t addr, uint32_t& r0, uint32_t& r1, uint32_t& r2, uint32_t& r3) {
  asm volatile("ldmatrix.sync.aligned.m8n8.x4.trans.shared.b16 {%0,%1,%2,%3}, [%4];" : "=r"(r0), "=r"(r1), "=r"(r2), "=r"(r3) : "r"(addr));
}
__device__ __forceinline__ void stsm_x4(uint32_t addr, uint32_t r0, uint32_t r1, uint32_t r2, uint32_t r3) {
  asm volatile("stmatrix.sync.aligned.m8n8.x4.shared.b16 [%0], {%1,%2,%3,%4};" :: "r"(addr), "r"(r0), "r"(r1), "r"(r2), "r"(r3) : "memory");
}
__device__ __forceinline__ float2 lds_f2(uint32_t addr) { float2 v; asm volatile("ld.shared.v2.f32 {%0,%1}, [%2];" : "=f"(v.x), "=f"(v.y) : "r"(addr)); return v; }
__device__ __forceinline__ void sts32(uint32_t addr, uint32_t v) { asm volatile("st.shared.u32 [%0], %1;" :: "r"(addr), "r"(v) : "memory"); }
__device__ __forceinline__ void sts128(uint32_t addr, uint4 v) {
  asm volatile("st.shared.v4.u32 [%0], {%1,%2,%3,%4};" :: "r"(addr), "r"(v.x), "r"(v.y), "r"(v.z), "r"(v.w) : "memory");
}
__device__ __forceinline__ void mma16816(float (&d)[4], uint32_t a0, uint32_t a1, uint32_t a2, uint32_t a3, uint32_t b0, uint32_t b1) {
  asm("mma.sync.aligned.m16n8k16.row.col.f32.bf16.bf16.f32 {%0,%1,%2,%3}, {%4,%5,%6,%7}, {%8,%9}, {%0,%1,%2,%3};"
               : "+f"(d[0]), "+f"(d[1]), "+f"(d[2]), "+f"(d[3]) : "r"(a0), "r"(a1), "r"(a2), "r"(a3), "r"(b0), "r"(b1));
}
__device__ __forceinline__ uint32_t pack_bf16(float lo, float hi) {
  uint32_t r; asm("cvt.rn.bf16x2.f32 %0, %1, %2;" : "=r"(r) : "f"(hi), "f"(lo)); return r;
}
__device__ __forceinline__ float bf_lo(uint32_t v) { return __uint_as_float(v << 16); }
__device__ __forceinline__ float bf_hi(uint32_t v) { return __uint_as_float(v & 0xffff0000u); }
__device__ __forceinline__ uint32_t bmul2(uint32_t a, uint32_t b) { uint32_t r; asm("mul.rn.bf16x2 %0, %1, %2;" : "=r"(r) : "r"(a), "r"(b)); return r; }
__device__ __forceinline__ uint32_t badd2(uint32_t a, uint32_t b) { uint32_t r; asm("add.rn.bf16x2 %0, %1, %2;" : "=r"(r) : "r"(a), "r"(b)); return r; }
#define STAMP(idx) do {} while (0)
#define MSTAMP(idx) do {} while (0)
#define BSTAMP(idx, saddr) do {} while (0)

__device__ __forceinline__ uint32_t pack_f16(float lo, float hi) {
  uint32_t r; asm("cvt.rn.satfinite.f16x2.f32 %0, %1, %2;" : "=r"(r) : "f"(hi), "f"(lo)); return r;
}
__device__ __forceinline__ uint32_t hfma2(uint32_t a, uint32_t b, uint32_t c) { uint32_t r; asm("fma.rn.f16x2 %0, %1, %2, %3;" : "=r"(r) : "r"(a), "r"(b), "r"(c)); return r; }
__device__ __forceinline__ uint32_t gelu_pair_f16(uint32_t h) {
  const uint32_t c0 = 0x3e623e62u, c1 = 0x34913491u;
  uint32_t u, p, z, t, r, o;
  asm("mul.rn.f16x2 %0, %1, %1;" : "=r"(u) : "r"(h));
  asm("fma.rn.f16x2 %0, %1, %2, %3;" : "=r"(p) : "r"(u), "r"(c1), "r"(c0));
  asm("mul.rn.f16x2 %0, %1, %2;" : "=r"(z) : "r"(h), "r"(p));
  asm("tanh.approx.f16x2 %0, %1;" : "=r"(t) : "r"(z));
  asm("fma.rn.f16x2 %0, %1, %2, %1;" : "=r"(r) : "r"(h), "r"(t));
  float lo, hi;
  asm("{\n.reg .f16 a, b;\nmov.b32 {a, b}, %2;\ncvt.f32.f16 %0, a;\ncvt.f32.f16 %1, b;\n}" : "=f"(lo), "=f"(hi) : "r"(r));
  asm("cvt.rn.bf16x2.f32 %0, %1, %2;" : "=r"(o) : "f"(hi), "f"(lo));
  return o;
}
__device__ __forceinline__ float gelu_from_half(float h) {
  const float c0 = 2.f * 0.7978845608028654f, c1 = 8.f * 0.7978845608028654f * 0.044715f;
  float z = h * fmaf(h * h, c1, c0);
  float t; asm("tanh.approx.f32 %0, %1;" : "=f"(t) : "f"(z));
  return fmaf(h, t, h);
}
__device__ __forceinline__ void wgmma_ss_n128(float (&d)[64], uint64_t da, uint64_t db) {
  asm volatile(
    "{\n"
    "wgmma.mma_async.sync.aligned.m64n128k16.f32.bf16.bf16 "
    "{%0, %1, %2, %3, %4, %5, %6, %7, %8, %9, %10, %11, %12, %13, %14, %15, "
    "%16, %17, %18, %19, %20, %21, %22, %23, %24, %25, %26, %27, %28, %29, %30, %31, "
    "%32, %33, %34, %35, %36, %37, %38, %39, %40, %41, %42, %43, %44, %45, %46, %47, "
    "%48, %49, %50, %51, %52, %53, %54, %55, %56, %57, %58, %59, %60, %61, %62, %63}, "
    "%64, %65, 1, 1, 1, 0, 1;\n}\n"
    : "+f"(d[0]), "+f"(d[1]), "+f"(d[2]), "+f"(d[3]), "+f"(d[4]), "+f"(d[5]), "+f"(d[6]), "+f"(d[7]),
      "+f"(d[8]), "+f"(d[9]), "+f"(d[10]), "+f"(d[11]), "+f"(d[12]), "+f"(d[13]), "+f"(d[14]), "+f"(d[15]),
      "+f"(d[16]), "+f"(d[17]), "+f"(d[18]), "+f"(d[19]), "+f"(d[20]), "+f"(d[21]), "+f"(d[22]), "+f"(d[23]),
      "+f"(d[24]), "+f"(d[25]), "+f"(d[26]), "+f"(d[27]), "+f"(d[28]), "+f"(d[29]), "+f"(d[30]), "+f"(d[31]),
      "+f"(d[32]), "+f"(d[33]), "+f"(d[34]), "+f"(d[35]), "+f"(d[36]), "+f"(d[37]), "+f"(d[38]), "+f"(d[39]),
      "+f"(d[40]), "+f"(d[41]), "+f"(d[42]), "+f"(d[43]), "+f"(d[44]), "+f"(d[45]), "+f"(d[46]), "+f"(d[47]),
      "+f"(d[48]), "+f"(d[49]), "+f"(d[50]), "+f"(d[51]), "+f"(d[52]), "+f"(d[53]), "+f"(d[54]), "+f"(d[55]),
      "+f"(d[56]), "+f"(d[57]), "+f"(d[58]), "+f"(d[59]), "+f"(d[60]), "+f"(d[61]), "+f"(d[62]), "+f"(d[63])
    : "l"(da), "l"(db));
}
__device__ __forceinline__ void wgmma_ss_n192(float (&d)[96], uint64_t da, uint64_t db) {
  asm volatile(
    "{\n"
    "wgmma.mma_async.sync.aligned.m64n192k16.f32.bf16.bf16 "
    "{%0, %1, %2, %3, %4, %5, %6, %7, %8, %9, %10, %11, %12, %13, %14, %15, "
    "%16, %17, %18, %19, %20, %21, %22, %23, %24, %25, %26, %27, %28, %29, %30, %31, "
    "%32, %33, %34, %35, %36, %37, %38, %39, %40, %41, %42, %43, %44, %45, %46, %47, "
    "%48, %49, %50, %51, %52, %53, %54, %55, %56, %57, %58, %59, %60, %61, %62, %63, "
    "%64, %65, %66, %67, %68, %69, %70, %71, %72, %73, %74, %75, %76, %77, %78, %79, "
    "%80, %81, %82, %83, %84, %85, %86, %87, %88, %89, %90, %91, %92, %93, %94, %95}, "
    "%96, %97, 1, 1, 1, 0, 1;\n}\n"
    : "+f"(d[0]), "+f"(d[1]), "+f"(d[2]), "+f"(d[3]), "+f"(d[4]), "+f"(d[5]), "+f"(d[6]), "+f"(d[7]),
      "+f"(d[8]), "+f"(d[9]), "+f"(d[10]), "+f"(d[11]), "+f"(d[12]), "+f"(d[13]), "+f"(d[14]), "+f"(d[15]),
      "+f"(d[16]), "+f"(d[17]), "+f"(d[18]), "+f"(d[19]), "+f"(d[20]), "+f"(d[21]), "+f"(d[22]), "+f"(d[23]),
      "+f"(d[24]), "+f"(d[25]), "+f"(d[26]), "+f"(d[27]), "+f"(d[28]), "+f"(d[29]), "+f"(d[30]), "+f"(d[31]),
      "+f"(d[32]), "+f"(d[33]), "+f"(d[34]), "+f"(d[35]), "+f"(d[36]), "+f"(d[37]), "+f"(d[38]), "+f"(d[39]),
      "+f"(d[40]), "+f"(d[41]), "+f"(d[42]), "+f"(d[43]), "+f"(d[44]), "+f"(d[45]), "+f"(d[46]), "+f"(d[47]),
      "+f"(d[48]), "+f"(d[49]), "+f"(d[50]), "+f"(d[51]), "+f"(d[52]), "+f"(d[53]), "+f"(d[54]), "+f"(d[55]),
      "+f"(d[56]), "+f"(d[57]), "+f"(d[58]), "+f"(d[59]), "+f"(d[60]), "+f"(d[61]), "+f"(d[62]), "+f"(d[63]),
      "+f"(d[64]), "+f"(d[65]), "+f"(d[66]), "+f"(d[67]), "+f"(d[68]), "+f"(d[69]), "+f"(d[70]), "+f"(d[71]),
      "+f"(d[72]), "+f"(d[73]), "+f"(d[74]), "+f"(d[75]), "+f"(d[76]), "+f"(d[77]), "+f"(d[78]), "+f"(d[79]),
      "+f"(d[80]), "+f"(d[81]), "+f"(d[82]), "+f"(d[83]), "+f"(d[84]), "+f"(d[85]), "+f"(d[86]), "+f"(d[87]),
      "+f"(d[88]), "+f"(d[89]), "+f"(d[90]), "+f"(d[91]), "+f"(d[92]), "+f"(d[93]), "+f"(d[94]), "+f"(d[95])
    : "l"(da), "l"(db));
}
__device__ __forceinline__ void wgmma_ss_n256(float (&d)[128], uint64_t da, uint64_t db) {
  asm volatile(
    "{\n"
    "wgmma.mma_async.sync.aligned.m64n256k16.f32.bf16.bf16 "
    "{%0, %1, %2, %3, %4, %5, %6, %7, %8, %9, %10, %11, %12, %13, %14, %15, "
    "%16, %17, %18, %19, %20, %21, %22, %23, %24, %25, %26, %27, %28, %29, %30, %31, "
    "%32, %33, %34, %35, %36, %37, %38, %39, %40, %41, %42, %43, %44, %45, %46, %47, "
    "%48, %49, %50, %51, %52, %53, %54, %55, %56, %57, %58, %59, %60, %61, %62, %63, "
    "%64, %65, %66, %67, %68, %69, %70, %71, %72, %73, %74, %75, %76, %77, %78, %79, "
    "%80, %81, %82, %83, %84, %85, %86, %87, %88, %89, %90, %91, %92, %93, %94, %95, "
    "%96, %97, %98, %99, %100, %101, %102, %103, %104, %105, %106, %107, %108, %109, %110, %111, "
    "%112, %113, %114, %115, %116, %117, %118, %119, %120, %121, %122, %123, %124, %125, %126, %127}, "
    "%128, %129, 1, 1, 1, 0, 1;\n}\n"
    : "+f"(d[0]), "+f"(d[1]), "+f"(d[2]), "+f"(d[3]), "+f"(d[4]), "+f"(d[5]), "+f"(d[6]), "+f"(d[7]),
      "+f"(d[8]), "+f"(d[9]), "+f"(d[10]), "+f"(d[11]), "+f"(d[12]), "+f"(d[13]), "+f"(d[14]), "+f"(d[15]),
      "+f"(d[16]), "+f"(d[17]), "+f"(d[18]), "+f"(d[19]), "+f"(d[20]), "+f"(d[21]), "+f"(d[22]), "+f"(d[23]),
      "+f"(d[24]), "+f"(d[25]), "+f"(d[26]), "+f"(d[27]), "+f"(d[28]), "+f"(d[29]), "+f"(d[30]), "+f"(d[31]),
      "+f"(d[32]), "+f"(d[33]), "+f"(d[34]), "+f"(d[35]), "+f"(d[36]), "+f"(d[37]), "+f"(d[38]), "+f"(d[39]),
      "+f"(d[40]), "+f"(d[41]), "+f"(d[42]), "+f"(d[43]), "+f"(d[44]), "+f"(d[45]), "+f"(d[46]), "+f"(d[47]),
      "+f"(d[48]), "+f"(d[49]), "+f"(d[50]), "+f"(d[51]), "+f"(d[52]), "+f"(d[53]), "+f"(d[54]), "+f"(d[55]),
      "+f"(d[56]), "+f"(d[57]), "+f"(d[58]), "+f"(d[59]), "+f"(d[60]), "+f"(d[61]), "+f"(d[62]), "+f"(d[63]),
      "+f"(d[64]), "+f"(d[65]), "+f"(d[66]), "+f"(d[67]), "+f"(d[68]), "+f"(d[69]), "+f"(d[70]), "+f"(d[71]),
      "+f"(d[72]), "+f"(d[73]), "+f"(d[74]), "+f"(d[75]), "+f"(d[76]), "+f"(d[77]), "+f"(d[78]), "+f"(d[79]),
      "+f"(d[80]), "+f"(d[81]), "+f"(d[82]), "+f"(d[83]), "+f"(d[84]), "+f"(d[85]), "+f"(d[86]), "+f"(d[87]),
      "+f"(d[88]), "+f"(d[89]), "+f"(d[90]), "+f"(d[91]), "+f"(d[92]), "+f"(d[93]), "+f"(d[94]), "+f"(d[95]),
      "+f"(d[96]), "+f"(d[97]), "+f"(d[98]), "+f"(d[99]), "+f"(d[100]), "+f"(d[101]), "+f"(d[102]), "+f"(d[103]),
      "+f"(d[104]), "+f"(d[105]), "+f"(d[106]), "+f"(d[107]), "+f"(d[108]), "+f"(d[109]), "+f"(d[110]), "+f"(d[111]),
      "+f"(d[112]), "+f"(d[113]), "+f"(d[114]), "+f"(d[115]), "+f"(d[116]), "+f"(d[117]), "+f"(d[118]), "+f"(d[119]),
      "+f"(d[120]), "+f"(d[121]), "+f"(d[122]), "+f"(d[123]), "+f"(d[124]), "+f"(d[125]), "+f"(d[126]), "+f"(d[127])
    : "l"(da), "l"(db));
}
__device__ __forceinline__ void wgmma_ss_n128_p(float (&d)[64], uint64_t da, uint64_t db, uint32_t keep) {
  asm volatile(
    "{\n.reg .pred p;\nsetp.ne.b32 p, %66, 0;\n"
    "{\n"
    "wgmma.mma_async.sync.aligned.m64n128k16.f32.bf16.bf16 "
    "{%0, %1, %2, %3, %4, %5, %6, %7, %8, %9, %10, %11, %12, %13, %14, %15, "
    "%16, %17, %18, %19, %20, %21, %22, %23, %24, %25, %26, %27, %28, %29, %30, %31, "
    "%32, %33, %34, %35, %36, %37, %38, %39, %40, %41, %42, %43, %44, %45, %46, %47, "
    "%48, %49, %50, %51, %52, %53, %54, %55, %56, %57, %58, %59, %60, %61, %62, %63}, "
    "%64, %65, p, 1, 1, 0, 1;\n}\n}\n"
    : "+f"(d[0]), "+f"(d[1]), "+f"(d[2]), "+f"(d[3]), "+f"(d[4]), "+f"(d[5]), "+f"(d[6]), "+f"(d[7]),
      "+f"(d[8]), "+f"(d[9]), "+f"(d[10]), "+f"(d[11]), "+f"(d[12]), "+f"(d[13]), "+f"(d[14]), "+f"(d[15]),
      "+f"(d[16]), "+f"(d[17]), "+f"(d[18]), "+f"(d[19]), "+f"(d[20]), "+f"(d[21]), "+f"(d[22]), "+f"(d[23]),
      "+f"(d[24]), "+f"(d[25]), "+f"(d[26]), "+f"(d[27]), "+f"(d[28]), "+f"(d[29]), "+f"(d[30]), "+f"(d[31]),
      "+f"(d[32]), "+f"(d[33]), "+f"(d[34]), "+f"(d[35]), "+f"(d[36]), "+f"(d[37]), "+f"(d[38]), "+f"(d[39]),
      "+f"(d[40]), "+f"(d[41]), "+f"(d[42]), "+f"(d[43]), "+f"(d[44]), "+f"(d[45]), "+f"(d[46]), "+f"(d[47]),
      "+f"(d[48]), "+f"(d[49]), "+f"(d[50]), "+f"(d[51]), "+f"(d[52]), "+f"(d[53]), "+f"(d[54]), "+f"(d[55]),
      "+f"(d[56]), "+f"(d[57]), "+f"(d[58]), "+f"(d[59]), "+f"(d[60]), "+f"(d[61]), "+f"(d[62]), "+f"(d[63])
    : "l"(da), "l"(db), "r"(keep));
}
__device__ __forceinline__ void wgmma_ss_n256_first(float (&d)[128], uint64_t da, uint64_t db) {
  asm volatile(
    "{\n"
    "mov.b32 %0, 0; mov.b32 %1, 0; mov.b32 %2, 0; mov.b32 %3, 0; mov.b32 %4, 0; mov.b32 %5, 0; mov.b32 %6, 0; mov.b32 %7, 0;\n"
    "mov.b32 %8, 0; mov.b32 %9, 0; mov.b32 %10, 0; mov.b32 %11, 0; mov.b32 %12, 0; mov.b32 %13, 0; mov.b32 %14, 0; mov.b32 %15, 0;\n"
    "mov.b32 %16, 0; mov.b32 %17, 0; mov.b32 %18, 0; mov.b32 %19, 0; mov.b32 %20, 0; mov.b32 %21, 0; mov.b32 %22, 0; mov.b32 %23, 0;\n"
    "mov.b32 %24, 0; mov.b32 %25, 0; mov.b32 %26, 0; mov.b32 %27, 0; mov.b32 %28, 0; mov.b32 %29, 0; mov.b32 %30, 0; mov.b32 %31, 0;\n"
    "mov.b32 %32, 0; mov.b32 %33, 0; mov.b32 %34, 0; mov.b32 %35, 0; mov.b32 %36, 0; mov.b32 %37, 0; mov.b32 %38, 0; mov.b32 %39, 0;\n"
    "mov.b32 %40, 0; mov.b32 %41, 0; mov.b32 %42, 0; mov.b32 %43, 0; mov.b32 %44, 0; mov.b32 %45, 0; mov.b32 %46, 0; mov.b32 %47, 0;\n"
    "mov.b32 %48, 0; mov.b32 %49, 0; mov.b32 %50, 0; mov.b32 %51, 0; mov.b32 %52, 0; mov.b32 %53, 0; mov.b32 %54, 0; mov.b32 %55, 0;\n"
    "mov.b32 %56, 0; mov.b32 %57, 0; mov.b32 %58, 0; mov.b32 %59, 0; mov.b32 %60, 0; mov.b32 %61, 0; mov.b32 %62, 0; mov.b32 %63, 0;\n"
    "mov.b32 %64, 0; mov.b32 %65, 0; mov.b32 %66, 0; mov.b32 %67, 0; mov.b32 %68, 0; mov.b32 %69, 0; mov.b32 %70, 0; mov.b32 %71, 0;\n"
    "mov.b32 %72, 0; mov.b32 %73, 0; mov.b32 %74, 0; mov.b32 %75, 0; mov.b32 %76, 0; mov.b32 %77, 0; mov.b32 %78, 0; mov.b32 %79, 0;\n"
    "mov.b32 %80, 0; mov.b32 %81, 0; mov.b32 %82, 0; mov.b32 %83, 0; mov.b32 %84, 0; mov.b32 %85, 0; mov.b32 %86, 0; mov.b32 %87, 0;\n"
    "mov.b32 %88, 0; mov.b32 %89, 0; mov.b32 %90, 0; mov.b32 %91, 0; mov.b32 %92, 0; mov.b32 %93, 0; mov.b32 %94, 0; mov.b32 %95, 0;\n"
    "mov.b32 %96, 0; mov.b32 %97, 0; mov.b32 %98, 0; mov.b32 %99, 0; mov.b32 %100, 0; mov.b32 %101, 0; mov.b32 %102, 0; mov.b32 %103, 0;\n"
    "mov.b32 %104, 0; mov.b32 %105, 0; mov.b32 %106, 0; mov.b32 %107, 0; mov.b32 %108, 0; mov.b32 %109, 0; mov.b32 %110, 0; mov.b32 %111, 0;\n"
    "mov.b32 %112, 0; mov.b32 %113, 0; mov.b32 %114, 0; mov.b32 %115, 0; mov.b32 %116, 0; mov.b32 %117, 0; mov.b32 %118, 0; mov.b32 %119, 0;\n"
    "mov.b32 %120, 0; mov.b32 %121, 0; mov.b32 %122, 0; mov.b32 %123, 0; mov.b32 %124, 0; mov.b32 %125, 0; mov.b32 %126, 0; mov.b32 %127, 0;\n"
    "wgmma.mma_async.sync.aligned.m64n256k16.f32.bf16.bf16 "
    "{%0, %1, %2, %3, %4, %5, %6, %7, %8, %9, %10, %11, %12, %13, %14, %15, "
    "%16, %17, %18, %19, %20, %21, %22, %23, %24, %25, %26, %27, %28, %29, %30, %31, "
    "%32, %33, %34, %35, %36, %37, %38, %39, %40, %41, %42, %43, %44, %45, %46, %47, "
    "%48, %49, %50, %51, %52, %53, %54, %55, %56, %57, %58, %59, %60, %61, %62, %63, "
    "%64, %65, %66, %67, %68, %69, %70, %71, %72, %73, %74, %75, %76, %77, %78, %79, "
    "%80, %81, %82, %83, %84, %85, %86, %87, %88, %89, %90, %91, %92, %93, %94, %95, "
    "%96, %97, %98, %99, %100, %101, %102, %103, %104, %105, %106, %107, %108, %109, %110, %111, "
    "%112, %113, %114, %115, %116, %117, %118, %119, %120, %121, %122, %123, %124, %125, %126, %127}, "
    "%128, %129, 1, 1, 1, 0, 1;\n}\n"
    : "=f"(d[0]), "=f"(d[1]), "=f"(d[2]), "=f"(d[3]), "=f"(d[4]), "=f"(d[5]), "=f"(d[6]), "=f"(d[7]),
      "=f"(d[8]), "=f"(d[9]), "=f"(d[10]), "=f"(d[11]), "=f"(d[12]), "=f"(d[13]), "=f"(d[14]), "=f"(d[15]),
      "=f"(d[16]), "=f"(d[17]), "=f"(d[18]), "=f"(d[19]), "=f"(d[20]), "=f"(d[21]), "=f"(d[22]), "=f"(d[23]),
      "=f"(d[24]), "=f"(d[25]), "=f"(d[26]), "=f"(d[27]), "=f"(d[28]), "=f"(d[29]), "=f"(d[30]), "=f"(d[31]),
      "=f"(d[32]), "=f"(d[33]), "=f"(d[34]), "=f"(d[35]), "=f"(d[36]), "=f"(d[37]), "=f"(d[38]), "=f"(d[39]),
      "=f"(d[40]), "=f"(d[41]), "=f"(d[42]), "=f"(d[43]), "=f"(d[44]), "=f"(d[45]), "=f"(d[46]), "=f"(d[47]),
      "=f"(d[48]), "=f"(d[49]), "=f"(d[50]), "=f"(d[51]), "=f"(d[52]), "=f"(d[53]), "=f"(d[54]), "=f"(d[55]),
      "=f"(d[56]), "=f"(d[57]), "=f"(d[58]), "=f"(d[59]), "=f"(d[60]), "=f"(d[61]), "=f"(d[62]), "=f"(d[63]),
      "=f"(d[64]), "=f"(d[65]), "=f"(d[66]), "=f"(d[67]), "=f"(d[68]), "=f"(d[69]), "=f"(d[70]), "=f"(d[71]),
      "=f"(d[72]), "=f"(d[73]), "=f"(d[74]), "=f"(d[75]), "=f"(d[76]), "=f"(d[77]), "=f"(d[78]), "=f"(d[79]),
      "=f"(d[80]), "=f"(d[81]), "=f"(d[82]), "=f"(d[83]), "=f"(d[84]), "=f"(d[85]), "=f"(d[86]), "=f"(d[87]),
      "=f"(d[88]), "=f"(d[89]), "=f"(d[90]), "=f"(d[91]), "=f"(d[92]), "=f"(d[93]), "=f"(d[94]), "=f"(d[95]),
      "=f"(d[96]), "=f"(d[97]), "=f"(d[98]), "=f"(d[99]), "=f"(d[100]), "=f"(d[101]), "=f"(d[102]), "=f"(d[103]),
      "=f"(d[104]), "=f"(d[105]), "=f"(d[106]), "=f"(d[107]), "=f"(d[108]), "=f"(d[109]), "=f"(d[110]), "=f"(d[111]),
      "=f"(d[112]), "=f"(d[113]), "=f"(d[114]), "=f"(d[115]), "=f"(d[116]), "=f"(d[117]), "=f"(d[118]), "=f"(d[119]),
      "=f"(d[120]), "=f"(d[121]), "=f"(d[122]), "=f"(d[123]), "=f"(d[124]), "=f"(d[125]), "=f"(d[126]), "=f"(d[127])
    : "l"(da), "l"(db));
}

template <int N> struct Mma;
template <> struct Mma<128> {
  static __device__ __forceinline__ void ss(float (&d)[64], uint64_t a, uint64_t b) { wgmma_ss_n128(d, a, b); }
  static __device__ __forceinline__ void ss(float (&d)[64], uint64_t a, uint64_t b, uint32_t keep) { wgmma_ss_n128_p(d, a, b, keep); }
};
template <> struct Mma<192> {
  static __device__ __forceinline__ void ss(float (&d)[96], uint64_t a, uint64_t b) { wgmma_ss_n192(d, a, b); }
};
template <> struct Mma<256> {
  static __device__ __forceinline__ void ss(float (&d)[128], uint64_t a, uint64_t b) { wgmma_ss_n256(d, a, b); }
  static __device__ __forceinline__ void ss(float (&d)[128], uint64_t a, uint64_t b, uint32_t) { wgmma_ss_n256_first(d, a, b); }
};
template <int R> __device__ __forceinline__ void pin(float (&d)[R]) {
#pragma unroll
  for (int x = 0; x < R; x++) asm volatile("" : "+f"(d[x]));
}

__device__ __forceinline__ uint32_t ld_relaxed(const uint32_t* p) {
  uint32_t v; asm volatile("ld.relaxed.gpu.global.u32 %0, [%1];" : "=r"(v) : "l"(p) : "memory"); return v;
}
__device__ __forceinline__ void red_release(uint32_t* p) { asm volatile("red.release.gpu.global.add.u32 [%0], 1;" :: "l"(p) : "memory"); }
__device__ __forceinline__ uint32_t both_valid(uint32_t a, uint32_t b, uint32_t ep) {
  uint32_t r; asm("lop3.b32 %0, %1, %2, %3, 0x42;" : "=r"(r) : "r"(a), "r"(b), "r"(ep)); return r;
}
__device__ __forceinline__ uint32_t tagged(float v, uint32_t ep) { return (__float_as_uint(v) | 1u) ^ (ep & 1u); }
__device__ __forceinline__ void st_release(uint32_t* p, uint32_t v) { asm volatile("st.release.gpu.global.u32 [%0], %1;" :: "l"(p), "r"(v) : "memory"); }
__device__ __forceinline__ void stg32(void* p, uint32_t v) { asm volatile("st.global.u32 [%0], %1;" :: "l"(p), "r"(v) : "memory"); }
__device__ __forceinline__ float rsqrt_fast(float x) { float r; asm("rsqrt.approx.ftz.f32 %0, %1;" : "=f"(r) : "f"(x)); return r; }
__device__ __forceinline__ uint32_t gate_pair(uint32_t x, uint32_t y, uint32_t r, uint32_t nb) {
  uint32_t o;
  asm("{\n.reg .b16 l, h;\n.reg .b32 ll, hh, t;\nmov.b32 {l, h}, %3;\nmov.b32 ll, {l, l};\nmov.b32 hh, {h, h};\n"
      "fma.rn.bf16x2 t, %1, ll, %4;\nfma.rn.bf16x2 t, %1, hh, t;\nfma.rn.bf16x2 %0, t, %2, %1;\n}" : "=r"(o) : "r"(x), "r"(y), "r"(r), "r"(nb));
  return o;
}

constexpr int CV_KT_O = 4144;
constexpr int CV_KT_CH = 8336;
constexpr int CV_KH = 2064;
constexpr int CV_U_PLANE = 2240;
constexpr int CV_U_CH = 4496;
constexpr int CV_VQ = 8320, CV_Y_CH = 1040, CV_XROW = 2064;
constexpr int SM_BAR = 0;
constexpr int CV_K = 896;
constexpr int CV_X = CV_K + 128 + 32768;
constexpr int CV_ST0 = CV_X + 16 * CV_XROW;
constexpr int CV_KT = CV_ST0 + 8192;
constexpr int CV_QS = CV_KT + 8 * CV_KT_CH;
constexpr int CV_U = 142848;
constexpr int CV_V = CV_U + 8 * CV_U_CH;
constexpr int CV_ST1 = CV_V + 4 * CV_VQ;
constexpr int SM_ZERO = CV_ST1 + 8192, SM_ROLE = SM_ZERO + 4, SM_EPOCH = SM_ZERO + 8;
constexpr int CV_END = SM_ZERO + 16;
static_assert(CV_QS + 1024 <= CV_U && CV_X % 1024 == 0 && CV_V % 128 == 0, "layout");
constexpr int CV_BAR = SM_BAR + 8 * 84, BAR_REL = 25;
enum { CB_K0, CB_QA, CB_Q0, CB_Q1, CB_Q2, CB_Q3, CB_K1, CB_X0, CB_X1, CB_QC0, CB_QC1, CB_QS, CB_U1, CB_U2,
       CB_ST0, CB_ST1, CB_O1, CB_P1, CB_Y1, CB_Y2, CB_P2, CB_EARLY, CB_LATE, CB_YOUT, CB_STAT, CB_XFREE = CB_STAT + 2, CB_COUNT };
static_assert(CV_BAR + 8 * CB_COUNT <= CV_K, "layout");

__device__ __forceinline__ uint32_t lds32_nv(uint32_t addr) { uint32_t v; asm("ld.shared.u32 %0, [%1];" : "=r"(v) : "r"(addr)); return v; }
__device__ __forceinline__ void ldsm_x4_nv(uint32_t addr, uint32_t& r0, uint32_t& r1, uint32_t& r2, uint32_t& r3) {
  asm("ldmatrix.sync.aligned.m8n8.x4.shared.b16 {%0,%1,%2,%3}, [%4];" : "=r"(r0), "=r"(r1), "=r"(r2), "=r"(r3) : "r"(addr));
}
__device__ __forceinline__ void stsm_x4_t(uint32_t addr, uint32_t r0, uint32_t r1, uint32_t r2, uint32_t r3) {
  asm volatile("stmatrix.sync.aligned.m8n8.x4.trans.shared.b16 [%0], {%1,%2,%3,%4};" :: "r"(addr), "r"(r0), "r"(r1), "r"(r2), "r"(r3) : "memory");
}
__device__ __forceinline__ void bulk_load(uint32_t dst, const void* src, uint32_t bytes, uint32_t bar) {
  asm volatile("cp.async.bulk.shared::cluster.global.mbarrier::complete_tx::bytes [%0], [%1], %2, [%3];" :: "r"(dst), "l"(src), "r"(bytes), "r"(bar) : "memory");
}
__device__ __forceinline__ void mbar_wait_plain(uint32_t bar, uint32_t parity) {
#pragma unroll 1
  for (int spins = 0; spins < SPIN_LIMIT && !mbar_try(bar, parity); spins++) {}
}

__device__ __forceinline__ void shift_chunk(uint32_t src) {
  uint4 e;
  uint32_t nx;
  asm volatile("ld.shared.v4.u32 {%0,%1,%2,%3}, [%4];" : "=r"(e.x), "=r"(e.y), "=r"(e.z), "=r"(e.w) : "r"(src));
  asm volatile("ld.shared.u32 %0, [%1];" : "=r"(nx) : "r"(src + 16));
  sts128(src + CV_KT_O, make_uint4(__byte_perm(e.x, e.y, 0x5432), __byte_perm(e.y, e.z, 0x5432), __byte_perm(e.z, e.w, 0x5432), __byte_perm(e.w, nx, 0x5432)));
}
__device__ __forceinline__ void kv_block(uint32_t sm, int t0, const uint32_t (&wp)[4], int lane) {
  const int mi = lane >> 3, rev = 7 - (lane & 7);
  uint32_t vv[4], res[4];
  ldsm_x4(sm + CV_V + (t0 >> 9) * (CV_VQ - 8192) + (t0 + 8 * mi + rev) * 16, vv[0], vv[1], vv[2], vv[3]);
#pragma unroll
  for (int i = 0; i < 4; i++) {
    uint32_t k0, k1, k2, k3;
    ldsm_x4(sm + CV_K + (8 + t0 + 8 * i + rev - mi) * 16, k0, k1, k2, k3);
    res[i] = bmul2(badd2(badd2(badd2(bmul2(k3, wp[3]), bmul2(k2, wp[2])), bmul2(k1, wp[1])), bmul2(k0, wp[0])), vv[i]);
  }
  stsm_x4_t(sm + CV_U + (lane & 7) * CV_U_CH + (1 - (mi & 1)) * CV_U_PLANE + (8 + (t0 >> 4) + (mi >> 1)) * 16, res[0], res[1], res[2], res[3]);
}
template <int T0, int NT, int D0, int D1, int J0, int J1>
__device__ __forceinline__ void conv_phase(float (&acc)[16][4], uint32_t abase, uint32_t bbase, uint32_t zero) {
  abase += zero; bbase += zero;
#pragma unroll 1
  for (int dl = 0; dl < 8; dl++) {
    uint32_t bf[NT][2];
#pragma unroll
    for (int j = 0; j < NT; j += 2) ldsm_x4_nv(bbase + (T0 + j) * 128 - dl * 16, bf[j][0], bf[j][1], bf[j + 1][0], bf[j + 1][1]);
    const uint32_t ap = abase + dl * 32;
#pragma unroll
    for (int dh = D0; dh < D1; dh++) {
      const uint32_t a0 = lds32_nv(ap + dh * 256), a1 = lds32_nv(ap + dh * 256 - 16), a2 = lds32_nv(ap + dh * 256 + 16);
      const uint32_t a3 = a0 + zero;
#pragma unroll
      for (int j = 0; j < NT; j++)
        if (dh + T0 + j >= J0 && dh + T0 + j < J1) mma16816(acc[dh + T0 + j], a0, a1, a2, a3, bf[j][0], bf[j][1]);
    }
  }
}
__device__ __forceinline__ uint32_t hidden_zero(uint32_t addr) {
  uint32_t z; asm volatile("ld.volatile.shared.u32 %0, [%1];" : "=r"(z) : "r"(addr) : "memory"); return z;
}
template <int J0, int J1>
__device__ __forceinline__ void stage_y(const float (&acc)[16][4], uint32_t ys, uint32_t bar) {
#pragma unroll
  for (int j = J0; j < J1; j += 2)
    stsm_x4_t(ys + (j >> 2) * CV_VQ + (j & 3) * 128, pack_bf16(acc[j][0], acc[j][1]), pack_bf16(acc[j][2], acc[j][3]),
              pack_bf16(acc[j + 1][0], acc[j + 1][1]), pack_bf16(acc[j + 1][2], acc[j + 1][3]));
  if (J0) {
    __syncwarp();
    mbar_arrive_if(bar, (threadIdx.x & 31) == 0);
  }
}

constexpr int CV_JS = 8;
enum { M_K, M_V, M_Q, M_W1C, M_W3C, M_X3S, M_X3B, M_H, M_HS, M_X1, M_HID, M_W1, M_W2, M_W3A, M_W3B, M_W4, M_OUT, M_Y, M_COUNT };
struct alignas(64) Params {
  const bf16 *q, *shift_k, *ssm_k, *ssm_d, *w2;
  CUtensorMap m[M_COUNT];
};
__device__ __forceinline__ void prefetch_line(const void* p) { asm volatile("prefetch.global.L2 [%0];" :: "l"(p) : "memory"); }

__device__ __forceinline__ uint32_t tpc_id() { uint32_t smid; asm volatile("mov.u32 %0, %%smid;" : "=r"(smid)); return smid >> 1; }
__device__ __forceinline__ uint32_t pick_role(uint32_t t, int lane) {
  uint32_t gpc = t < 32 ? t & 7 : t < 60 ? 1 + (t - 32) % 7 : t < 62 ? t - 54 : 0;
  const uint32_t d = ld_relaxed(g_role + 12 + (lane >> 3)) - ld_relaxed(g_role + 4 + (lane & 7)) + 4096;
  const uint32_t match = __ballot_sync(0xffffffffu, d < 8192) & 0x3e3e3e3eu;
  const uint32_t nine = (match | match >> 8 | match >> 16 | match >> 24) & 0xff;
  if (t >= 62) gpc = max(__ffs((match >> (8 * t - 496)) & 0xff) - 1, 0);
  const uint32_t below = (1u << gpc) - 1, pos = (nine >> gpc) & 1 ? __popc(nine & below) : __popc(nine) + __popc(~nine & below & 0xfe);
  uint32_t cls = gpc == 0 ? 0 : min(pos, 7 - pos);
  if (pos > 3 && cls < __popc(nine) && t < 8) cls = 0;
  uint32_t role = 0;
  if (lane == 0) {
#pragma unroll 1
    for (uint32_t k = 0; k < 4; k++) {
      const uint32_t p = (cls + k) & 3, ticket = atomicAdd(&g_role[p], 1u);
      if (ticket < 16) { role = ticket * 4 + p; break; }
    }
  }
  return role;
}

__device__ __forceinline__ void load_k(const Params& pr, uint32_t sm, int x) {
  const uint32_t bar = sm + CV_BAR + 8 * (x ? CB_K1 : CB_K0), bytes = x ? 4096 - CV_KH : CV_KH;
  mbar_expect_tx(bar, 8 * bytes);
#pragma unroll 1
  for (int ch = 0; ch < 8; ch++)
    bulk_load(sm + CV_KT + ch * CV_KT_CH + 32 + x * CV_KH, reinterpret_cast<const char*>(pr.ssm_k) + (blockIdx.x * 8 + ch) * 4096 + x * CV_KH, bytes, bar);
}
__device__ __forceinline__ void load_kv(const Params& pr, uint32_t sm, int y, int barrier) {
  tma_2d(sm + CV_K + 128 + y * 4096, &pr.m[M_K], sm + CV_BAR + 8 * barrier, blockIdx.x * 8, y * 256);
  tma_2d(sm + CV_V + (y >> 1) * CV_VQ + (y & 1) * 4096, &pr.m[M_V], sm + CV_BAR + 8 * barrier, blockIdx.x * 8, y * 256);
}

__device__ __forceinline__ void conv_part(const Params& pr, uint32_t sm, int warp) {
  const int tid = threadIdx.x, lane = tid & 31;
  const int b = blockIdx.x, d0 = b * 8;
  const uint32_t kt = sm + CV_KT, ub = sm + CV_U, bar = sm + CV_BAR;
  const int g = lane >> 2, qd = lane & 3, mi = lane >> 3;
  if (warp == 8) {
    asm volatile("bar.arrive 1, 384;" ::: "memory");
    const uint32_t ep = ld_relaxed(&g_epoch);
    if (elect_one()) {
      load_k(pr, sm, 1);
#pragma unroll 1
      for (int y = 2; y < 8; y++) {
        if (y == 6) {
          mbar_expect_tx(bar + 8 * CB_X0, 32768);
#pragma unroll 1
          for (int r = 0; r < 16; r++) bulk_load(sm + CV_X + r * CV_XROW, pr.q + (size_t)(b * 16 + r) * DM, 2048, bar + 8 * CB_X0);
        }
        if (!(y & 1)) mbar_expect_tx(bar + 8 * (CB_Q0 + (y >> 1)), 16384);
        load_kv(pr, sm, y, CB_Q0 + (y >> 1));
      }
#pragma unroll 1
      for (int x = M_Q; x < M_COUNT; x++) asm volatile("prefetch.tensormap [%0];" :: "l"(&pr.m[x]) : "memory");
    }
    __syncwarp();
    const uint32_t role = b & 1 ? 0 : pick_role(tpc_id(), lane);
    if (lane == 0) {
      sts32(sm + SM_EPOCH, ep);
      sts32(sm + SM_ROLE, role);
      asm volatile("fence.release.sync_restrict::shared::cta.cluster;" ::: "memory");
    }
    __syncwarp();
    asm volatile("barrier.cluster.arrive.relaxed.aligned;" ::: "memory");
    auto load_q = [&](int x) {
      mbar_wait_plain(bar + 8 * (CB_U1 + x), 0);
      fence_async_smem();
      if (elect_one()) {
        mbar_expect_tx(bar + 8 * (CB_QC0 + x), 16384);
#pragma unroll 1
        for (int y = 4 * x; y < 4 * x + 4; y++) tma_2d(sm + CV_K + 128 + y * 4096, &pr.m[M_Q], bar + 8 * (CB_QC0 + x), d0, y * 256);
      }
    };
    const int npieces = b < 112 ? 5 : 1;
    const int xr = (mi >> 1) * 8 + (lane & 7);
    const uint32_t xa = sm + CV_X + xr * 64 + (((mi & 1) ^ ((xr >> 1) & 3)) << 4);
    float cs[8][4] = {};
    auto q_stats = [&]() {
      mbar_wait_plain(bar + 8 * CB_QS, 0);
      float sum = 0.f, sq = 0.f;
#pragma unroll
      for (int x = 0; x < 8; x++) { const float2 v = lds_f2(sm + CV_QS + x * 128 + (lane & 15) * 8); sum += v.x; sq += v.y; }
      const float mean = sum * (1.f / DM), rs = rsqrt_fast(fmaxf(fmaf(-mean, mean, sq * (1.f / DM)), 0.f) + LN_EPS);
      const uint32_t rh = pack_bf16(0.f, rs);
      if (lane < 16)
        asm volatile("st.relaxed.gpu.global.v2.b32 [%0], {%1,%2};" :: "l"(g_qstat + b * 16 + lane), "r"(tagged(__uint_as_float(pack_bf16(rs - bf_hi(rh), bf_hi(rh))), ep)),
                     "r"(pack_bf16(-mean * rs, -mean * rs)) : "memory");
      if (lane == 0) { STAMP(47); asm volatile("red.relaxed.gpu.global.add.u32 [%0], 1;" :: "l"(&g_qcnt) : "memory"); }
    };
#pragma unroll 1
    for (int pc = -3; pc < npieces; pc++) {
      if (pc == -2) q_stats();
      if (pc >= 0) {
        mbar_wait_plain(bar + 8 * (CB_X0 + ((pc + 1) & 1)), ((pc + 1) >> 1) & 1);
#pragma unroll 1
        for (int r = 0; r < 16; r += 4) {
#pragma unroll
          for (int x = 0; x < 8; x++) {
            uint32_t a0, a1, a2, a3;
            ldsm_x4_t((xa ^ ((x & 1) << 5)) + ((pc + 1) & 1) * 16384 + (r + (x >> 1)) * 1024, a0, a1, a2, a3);
            mma16816(cs[x], a0, a1, a2, a3, 0x3f803f80u, 0x3f803f80u);
          }
        }
        if (pc == 0 || pc == 4) {
          float t = 0.f;
#pragma unroll
          for (int x = 0; x < 8; x += 2) {
            t += qd & 2 ? (qd & 1 ? cs[x + 1][2] : cs[x + 1][0]) : (qd & 1 ? cs[x][2] : cs[x][0]);
            cs[x][0] = cs[x][2] = cs[x + 1][0] = cs[x + 1][2] = 0.f;
          }
          (pc ? g_cs3 + 32 * b : g_cs1[b & 3] + 32 * (b >> 2))[8 * qd + g] = t;
        }
        __syncwarp();
      }
      if (pc > -3 && pc + 2 < npieces && elect_one()) {
        const uint32_t bx = bar + 8 * (CB_X0 + ((pc + 1) & 1));
        mbar_expect_tx(bx, 16384);
        tma_2d(sm + CV_X + ((pc + 1) & 1) * 16384, &pr.m[pc == -2 ? M_W1C : M_W3C], bx, 32 * (pc == -2 ? b >> 2 : b), 256 * (pc == -2 ? b & 3 : pc + 1));
      }
      if (pc == -3 || pc == min(2, npieces - 1)) load_q(pc >= 0);
    }
#pragma unroll 1
    for (int x = 0; x < 4; x++) prefetch_line(reinterpret_cast<const char*>(pr.w2) + (b * 128 + x * 32 + lane) * 128);
    if (lane == 0) STAMP(52);
    return;
  }

  const uint32_t dpair = __ldg(reinterpret_cast<const uint32_t*>(pr.ssm_d + d0 + 2 * qd));
  const int wi = warp - (warp > 8), ti = 32 * wi + lane;
  {
    if (tid < 160) {
      const int x = tid - 128, y = x & 3;
      sts128(tid < 128 ? ub + (tid >> 4) * CV_U_CH + ((tid >> 3) & 1) * CV_U_PLANE + (tid & 7) * 16
                       : y == 3 ? sm + CV_K + (x >> 2) * 16 : kt + (x >> 2) * CV_KT_CH + (y == 2 ? 4128 : y * 16), make_uint4(0, 0, 0, 0));
    }
    uint32_t wp[4];
    {
      const uint4 a = ld_nc_u4(pr.shift_k + (d0 + 2 * qd) * 4);
      wp[0] = __byte_perm(a.x, a.z, 0x5410); wp[1] = __byte_perm(a.x, a.z, 0x7632);
      wp[2] = __byte_perm(a.y, a.w, 0x5410); wp[3] = __byte_perm(a.y, a.w, 0x7632);
    }
    const uint32_t kc = kt + (lane & 7) * CV_KT_CH;
    named_bar(1, 384);
#pragma unroll 1
    for (int x = 0; x < 2; x++) {
      mbar_wait_plain(bar + 8 * (x ? CB_K1 : CB_K0), 0);
#pragma unroll 1
      for (uint32_t a = kc + ((ti >> 3) + (x ? 130 - 32 : 0)) * 16; a < kc + (x ? 258 : 130) * 16; a += x ? 192 : 704) shift_chunk(a);
      __syncwarp();
      mbar_arrive_if(bar + 8 * CB_O1, x && lane == 0);
      if (tid == 0) BSTAMP(54, kt);
#pragma unroll 1
      for (int t0 = warp < 8 ? 32 * wi : 32 * wi + 256; t0 < (x ? SEQ : 512); t0 += x ? 96 : 256) {
        mbar_wait_plain(bar + 8 * (t0 < 256 ? CB_QA : CB_Q0 + (t0 >> 9)), 0);
        if (tid == 0) BSTAMP(56, kt);
        kv_block(sm, t0, wp, lane);
        constexpr int T1 = 128 * CV_JS + 32;
        __syncwarp();
        mbar_arrive_if(bar + 8 * (CB_U1 + (t0 >= T1)), t0 + 96 >= (t0 < T1 ? T1 : SEQ) && lane == 0);
      }
      if (x == 0) named_bar(4, 352);
      if (warp < 8) break;
    }
  }

  if (warp < 8) {
    const int o = 2 * qd - g;
    const uint32_t abase = kt + warp * CV_KT_CH + 32 + ((g & 1) ? CV_KT_O + (o - 1) * 2 : o * 2);
    const uint32_t bbase = ub + warp * CV_U_CH + (mi & 1) * CV_U_PLANE + (8 + (lane >> 4) * 8 + (lane & 7)) * 16;
    const uint32_t ys = sm + CV_V + warp * CV_Y_CH + (mi & 1) * 512 + ((lane >> 4) * 8 + (lane & 7)) * 16;
    auto q_sums = [&]() {
      mbar_wait_plain(bar + 8 * CB_X0, 0);
      float sum[4] = {0.f, 0.f, 0.f, 0.f}, lo[4] = {0.f, 0.f, 0.f, 0.f}, hi[4] = {0.f, 0.f, 0.f, 0.f};
#pragma unroll
      for (int x = 0; x < 8; x++) {
        uint32_t a0, a1, a2, a3;
        ldsm_x4(sm + CV_X + (lane & 15) * CV_XROW + warp * 256 + (lane >> 4) * 16 + x * 32, a0, a1, a2, a3);
        mma16816(sum, a0, a1, a2, a3, 0x3f803f80u, 0x3f803f80u);
        mma16816(lo, a0, a1, a2, a3, a0, a2);
        mma16816(hi, a0, a1, a2, a3, a1, a3);
      }
      if (qd == (g >> 1)) {
        asm volatile("st.shared.v2.f32 [%0], {%1,%2};" :: "r"(sm + CV_QS + warp * 128 + g * 8), "f"(sum[0]), "f"((g & 1) ? lo[1] : lo[0]) : "memory");
        asm volatile("st.shared.v2.f32 [%0], {%1,%2};" :: "r"(sm + CV_QS + warp * 128 + g * 8 + 64), "f"(sum[2]), "f"((g & 1) ? hi[3] : hi[2]) : "memory");
      }
      __syncwarp();
      mbar_arrive_if(bar + 8 * CB_QS, lane == 0);
    };
    if (tid == 0) STAMP(49);
    float acc[16][4];
#pragma unroll
    for (int j = 0; j < 16; j++) { acc[j][0] = acc[j][1] = acc[j][2] = acc[j][3] = 0.f; }
    conv_phase<0, 4, 0, 8, 0, 16>(acc, abase, bbase, hidden_zero(ub));
    stage_y<0, 4>(acc, ys, 0);
    if (tid == 0) STAMP(57);
    mbar_wait_plain(bar + 8 * CB_K1, 0);
    mbar_wait_plain(bar + 8 * CB_O1, 0);
    conv_phase<0, 4, 8, 16, 0, 16>(acc, abase, bbase, hidden_zero(ub));
    if (tid == 0) STAMP(58);
    q_sums();
    mbar_wait_plain(bar + 8 * CB_U1, 0);
    conv_phase<4, CV_JS - 4, 0, CV_JS - 4, 0, CV_JS>(acc, abase, bbase, hidden_zero(ub));
    stage_y<4, CV_JS>(acc, ys, bar + 8 * CB_Y1);
    if (tid == 0) STAMP(59);
    mbar_wait_plain(bar + 8 * CB_U2, 0);
    if (tid == 0) BSTAMP(55, kt);
    conv_phase<4, 12, 0, 12, CV_JS, 16>(acc, abase, bbase, hidden_zero(ub));
    stage_y<CV_JS, 16>(acc, ys, bar + 8 * CB_Y2);
    if (tid == 0) STAMP(50);
    if (tid == 32) STAMP(62);
  }
  {
    const int ch = lane & 7;
    const uint32_t ya = sm + CV_V + ch * CV_Y_CH + (mi & 1) * 512 + (mi >> 1) * 16;
    const uint32_t ua = ub + ch * CV_U_CH + (mi & 1) * CV_U_PLANE + (8 + (mi >> 1)) * 16;
    const uint32_t qa = sm + CV_K + 128 + (16 * (mi >> 1) + 15 - 8 * (mi & 1) - ch) * 16;
    char* xo = reinterpret_cast<char*>(g_x3[0]) + (size_t)b * CB_BYTES + (15 - g) * 16 + qd * 4;
    const uint32_t yo = sm + CV_K + 128 + ((7 - g) * 4 + qd) * 8;
    int budget = SPIN_LIMIT;
    uint32_t ep = 0;
    if (warp > 9) {
      if (tid == 320) STAMP(53);
      ep = ld_relaxed(&g_epoch);
#pragma unroll 1
      while (ld_relaxed(&g_qcnt) - 128 * ep < 128 && --budget > 0) __nanosleep(100);
      if (tid == 320) STAMP(43);
    }
#pragma unroll 1
    for (int part = warp < 8; part < 2; part++) {
      if (warp == 9 && part) break;
      if (warp > 9) {
        uint4 v[8];
#pragma unroll 1
        do {
          uint32_t ok = 1;
#pragma unroll
          for (int y = 0; y < 8; y++) {
            asm volatile("ld.relaxed.gpu.global.v4.u32 {%0,%1,%2,%3}, [%4];" : "=r"(v[y].x), "=r"(v[y].y), "=r"(v[y].z), "=r"(v[y].w)
                         : "l"(g_qstat + 1024 * part + 2 * (tid & 63) + 128 * y) : "memory");
            ok &= both_valid(v[y].x, v[y].z, ep);
          }
          if (__all_sync(0xffffffffu, ok)) break;
        } while (--budget > 0);
#pragma unroll
        for (int y = 0; y < 8; y++) sts128(sm + (part ? CV_ST1 : CV_ST0) + (tid & 63) * 16 + 1024 * y, make_uint4(v[y].x | 1u, v[y].y, v[y].z | 1u, v[y].w));
        __syncwarp();
        mbar_arrive_if(bar + 8 * (CB_ST0 + part), lane == 0);
      }
      mbar_wait_plain(bar + 8 * (CB_ST0 + part), 0);
      mbar_wait_plain(bar + 8 * (CB_QC0 + part), 0);
      if (tid == 288) STAMP(63);
      mbar_wait_plain(bar + 8 * (CB_Y1 + part), 0);
      const uint32_t sa = sm + (part ? CV_ST1 - 8192 : CV_ST0) + (15 - g) * 8;
#pragma unroll 1
      for (int u = part ? 4 * CV_JS + warp - 2 * (warp > 8) : warp - 9; u < (part ? 64 : 4 * CV_JS); u += part ? 10 : 3) {
        uint32_t y[4], uu[4], qq[4];
        ldsm_x4_t(ya + ((u >> 4) * (CV_VQ - 512) + u * 32), y[0], y[1], y[2], y[3]);
        ldsm_x4_t(ua + u * 32, uu[0], uu[1], uu[2], uu[3]);
        ldsm_x4(qa + u * 512, qq[0], qq[1], qq[2], qq[3]);
#pragma unroll
        for (int i = 0; i < 4; i++) {
          const int off = 16 * (i >> 1) - 8 * (i & 1);
          const float2 s = lds_f2(sa + (u * 256 + off * 8));
          y[i] = badd2(y[i], bmul2(uu[i], dpair));
          stg32(xo + (uint32_t)u * 512 + off * 16, gate_pair(qq[i], y[i], __float_as_uint(s.x), __float_as_uint(s.y)));
        }
        asm volatile("st.shared.v2.u32 [%0], {%1,%2};" :: "r"(yo + u * 512), "r"(y[1]), "r"(y[0]) : "memory");
        asm volatile("st.shared.v2.u32 [%0], {%1,%2};" :: "r"(yo + u * 512 + 256), "r"(y[3]), "r"(y[2]) : "memory");
      }
      __syncwarp();
      mbar_arrive_if(bar + 8 * (part ? CB_P2 : CB_P1), lane == 0);
    }
  }
  if (warp == 9) {
    mbar_wait_plain(bar + 8 * CB_P1, 0);
    if (elect_one()) {
      STAMP(61);
      red_release(&g_xcnt[b >> 3]);
      fence_async_smem();
      bulk_store(reinterpret_cast<char*>(g_y) + (size_t)b * CB_BYTES, sm + CV_K + 128, 16384);
      bulk_commit();
      bulk_wait_all();
      mbar_arrive(bar + 8 * CB_YOUT);
    }
  }
  if (tid == 0) STAMP(51);
}

constexpr int NA = 5, A_SLOT = 68 * 128;
constexpr int SM_B = 1024;
constexpr int SM_A = SM_B + 98304;
constexpr int SM_X = SM_A + 2 * NA * A_SLOT;
constexpr int SM_CS1 = CV_END;
constexpr int SM_CS3 = SM_CS1 + 512;
static_assert(SM_X % 1024 == 0 && SM_X + 32768 <= SM_CS1 && SM_B + 2 * 16384 == CV_X && SM_A + NA * A_SLOT == CV_U, "layout");
constexpr int BAR_FULLA = 0, BAR_FULLB = 16, BAR_TURN = 24, BAR_OWN = 26;
constexpr int BAR_EMPTYA = 28, BAR_EMPTYB = BAR_EMPTYA + 18, BAR_CS = BAR_EMPTYB + 9;
constexpr int BAR_PUB = 56;
constexpr int BAR_END = 84;
constexpr int SM_RS = SM_CS3 + 1792;
constexpr int RS_G1 = 2 * 68 * 8;
constexpr int MEGA_SMEM = SM_RS + 2 * RS_G1;
static_assert(MEGA_SMEM <= 232448, "shared memory");
#define LEAD 4
#define LEAD3 2

template <int N> struct BGeo;
template <> struct BGeo<128> { static constexpr int SLOTS = 6, BYTES = 16384; };
template <> struct BGeo<256> { static constexpr int SLOTS = 3, BYTES = 32768; };
template <> struct BGeo<192> { static constexpr int SLOTS = 4, BYTES = 24576; };
__host__ __device__ constexpr int first_slot(int s) { return s == 0 || s == 2 ? 2 : 0; }
__device__ __forceinline__ bool starts_local(int l, int s) { return s == 2 || s == 1 - l; }
__device__ __forceinline__ int token_shift(int j) { return ((j >> 1) & 1 ? 1 : -1) * (1 + (j >> 2)); }

struct Ctx {
  uint32_t sm;
  uint32_t bar;
  int i, j, r;
  int bid;
  uint32_t ep;
};

struct Pipe {
  uint32_t ko, kp;
  uint32_t po;
  uint32_t a0, a1, ar;
  uint32_t b;
  uint32_t keep;
  uint32_t sh, wide;
  uint64_t ak;
  uint32_t turn;
  int budget;
  uint32_t rel;
  bool signals;
  __device__ __forceinline__ void release() const {
    asm volatile("{\n.reg .pred p;\nsetp.ne.b32 p, %1, 0;\n@p mbarrier.arrive.shared::cluster.b64 _, [%0];\n}" :: "r"(rel + po), "r"((uint32_t)signals) : "memory");
  }
  __device__ __forceinline__ void drain() { wg_wait<0>(); release(); po = 64; }
};
__device__ __forceinline__ uint32_t desc_a(const Ctx& c, int off) { return ((c.sm & 0x3FFFFu) >> 4) + 0x400000u + (off >> 4); }
__device__ __forceinline__ uint32_t desc_b(const Ctx& c, int off) { return ((c.sm & 0x3FFFFu) >> 4) + 0x2000000u + ((SM_B + off) >> 4); }

template <int N, bool PRED, bool SHIFT = false, class Extra>
__device__ __forceinline__ void gemm_step(float (&acc)[N / 2], const Ctx& c, int wg, Pipe& p, Extra&& extra) {
  using G = BGeo<N>;
  const uint32_t fa = c.bar + 8 * BAR_FULLA + 64 * wg + p.ko, fb = c.bar + 8 * BAR_FULLB + p.ko;
#pragma unroll 1
  while (true) {
    uint32_t ready;
    asm volatile("{\n.reg .pred p, q;\nmbarrier.try_wait.parity.shared::cta.b64 p, [%1], %3;\nmbarrier.try_wait.parity.shared::cta.b64 q, [%2], %3;\n"
                 "and.pred p, p, q;\nselp.b32 %0, 1, 0, p;\n}" : "=r"(ready) : "r"(fa), "r"(fb), "r"(p.kp) : "memory");
    if (ready || --p.budget <= 0) break;
  }
  wg_fence();
  uint64_t da = (8ull << 32) | (SHIFT ? p.a0 + (p.sh & 3) + p.wide : p.a0), db = (0x40000040ull << 32) | p.b;
  if constexpr (SHIFT) p.sh >>= 2;
  if constexpr (PRED) { Mma<N>::ss(acc, da, db, p.keep); p.keep = 1; } else Mma<N>::ss(acc, da, db);
#pragma unroll
  for (int kk = 1; kk < 4; kk++) {
    asm volatile("add.s64 %0, %0, %2;\nadd.s64 %1, %1, 128;" : "+l"(da), "+l"(db) : "l"(SHIFT ? p.ak : (uint64_t)128));
    Mma<N>::ss(acc, da, db);
  }
  wg_commit();
  extra();
  wg_wait<1>();
  p.release();
  p.po = p.ko;
  p.ko = (p.ko + 8) & 63;
  p.kp ^= p.ko == 0;
  p.a0 = p.a1; p.a1 = p.ar;
  p.ar = p.ar == desc_a(c, SM_A + (NA - 1) * A_SLOT) + wg * NA * (A_SLOT >> 4) ? p.ar - (NA - 1) * (A_SLOT >> 4) : p.ar + (A_SLOT >> 4);
  p.b = p.b == desc_b(c, (G::SLOTS - 1) * G::BYTES) ? desc_b(c, 0) : p.b + (G::BYTES >> 4);
}
template <int N>
__device__ __forceinline__ void gemm_begin(const Ctx& c, int wg, int wq, Pipe& p, int s, bool local) {
  if (local) {
    fence_async_smem();
    named_bar(2 + wg, 128);
    mbar_arrive_if(c.bar + 8 * BAR_FULLA + 64 * wg + 8 * (threadIdx.x & 1), (threadIdx.x & 126) == 96);
    if (wq < 2) {
      mbar_wait(c.bar + 8 * (BAR_EMPTYA + 9 * wg + 8 - NA + wq), p.kp ^ 1, p.budget);
      if (elect_one()) {
        const uint32_t peer = mapa(c.sm, c.r ^ 1), bar = peer + SM_BAR + 8 * (BAR_FULLA + 8 * wg + 2 + wq);
        mbar_expect_tx_cluster(bar, 8192);
        bulk_copy_cluster(peer + (((wq ? p.a1 : p.a0) - desc_a(c, 0)) << 4), c.sm + SM_X + (2 * wg + wq) * 8192, 8192, bar);
      }
      __syncwarp();
    }
  }
  asm volatile("{\n.reg .pred p;\nsetp.ne.b32 p, %3, 0;\nselp.b32 %2, %0, %2, p;\nselp.b32 %0, %4, %0, p;\nselp.b32 %1, %5, %1, p;\n}"
               : "+r"(p.a0), "+r"(p.a1), "+r"(p.ar) : "r"((uint32_t)local), "r"(desc_a(c, SM_X) + wg * 1024), "r"(desc_a(c, SM_X + 8192) + wg * 1024));
  p.b = desc_b(c, first_slot(s) * BGeo<N>::BYTES);
}
template <class Hook>
__device__ __forceinline__ void yield_turn(const Ctx& c, int wg, Pipe& p, Hook&& hook) {
  if (wg == 1) p.drain();
  hook();
  if (wg == 1) mbar_wait(c.bar + 8 * BAR_TURN, p.turn, p.budget);
  p.turn ^= 1;
}
__device__ __forceinline__ void pass_turn(const Ctx& c, bool now) { mbar_arrive_if(c.bar + 8 * BAR_TURN, now && threadIdx.x == 96); }
struct Nop { __device__ __forceinline__ void operator()() const {} };
template <int N, bool PRED, bool SHIFT = false, class Hook>
__device__ __forceinline__ void gemm_steps(float (&acc)[N / 2], const Ctx& c, int wg, Pipe& p, int count, Hook&& hook) {
  constexpr int lead = N == 128 ? LEAD : LEAD3;
  int m = count - lead;
#pragma unroll 1
  do { gemm_step<N, PRED, SHIFT>(acc, c, wg, p, Nop()); } while (--m > 0);
  yield_turn(c, wg, p, hook);
#pragma unroll 1
  for (int n = lead - 1; n >= 0; n--) {
    gemm_step<N, false, SHIFT>(acc, c, wg, p, Nop());
    pass_turn(c, n == 1);
  }
}

__device__ __forceinline__ void put_stat(float2* gdst, float s, float q, bool cond, uint32_t ep) {
  const float m = s * (1.f / 128), v = fmaxf(fmaf(-m, s, q), 0.f);
  asm volatile("{\n.reg .pred p;\nsetp.ne.b32 p, %3, 0;\n@p st.relaxed.gpu.global.v2.b32 [%0], {%1,%2};\n}"
               :: "l"(gdst), "r"(__float_as_uint(m)), "r"(tagged(v, ep)), "r"((uint32_t)cond) : "memory");
}
__device__ __forceinline__ void put_partial(const float (&v)[64], float2* gdst, uint32_t ep) {
  float s[4] = {v[0], v[1], v[2], v[3]}, q[4] = {v[0] * v[0], v[1] * v[1], v[2] * v[2], v[3] * v[3]};
#pragma unroll
  for (int x = 4; x < 64; x++) { s[x & 3] += v[x]; q[x & 3] = fmaf(v[x], v[x], q[x & 3]); }
  const bool odd = threadIdx.x & 1;
  const float s0 = s[0] + s[1], s1 = s[2] + s[3], q0 = q[0] + q[1], q1 = q[2] + q[3];
  float ss = (odd ? s1 : s0) + __shfl_xor_sync(0xffffffffu, odd ? s0 : s1, 1);
  float qq = (odd ? q1 : q0) + __shfl_xor_sync(0xffffffffu, odd ? q0 : q1, 1);
  ss += __shfl_xor_sync(0xffffffffu, ss, 2);
  qq += __shfl_xor_sync(0xffffffffu, qq, 2);
  put_stat(gdst + (odd ? 8 : 0), ss, qq, !(threadIdx.x & 2), ep);
}
struct RowStats {
  float2 p[4];
  __device__ __forceinline__ void load(const float2* r0, const float2* r1) {
#pragma unroll
    for (int x = 0; x < 4; x++)
      asm volatile("ld.relaxed.gpu.global.v2.f32 {%0,%1}, [%2];" : "=f"(p[x].x), "=f"(p[x].y) : "l"((x & 2 ? r1 : r0) + (x & 1) * SEQ) : "memory");
  }
  __device__ __forceinline__ void finish(const float2* r0, const float2* r1, int& budget, float2& s0, float2& s1) {
#pragma unroll 1
    while (!__all_sync(0xffffffffu, both_valid(__float_as_uint(p[0].y), __float_as_uint(p[1].y), 0) & both_valid(__float_as_uint(p[2].y), __float_as_uint(p[3].y), 0) & 1)) {
      if (--budget <= 0) break;
      load(r0, r1);
    }
#pragma unroll
    for (int h = 0; h < 2; h++) {
      const float2 a = p[2 * h], b = p[2 * h + 1];
      float m = a.x + b.x;
      m += __shfl_xor_sync(0xffffffffu, m, 1);
      m += __shfl_xor_sync(0xffffffffu, m, 2);
      m *= 0.125f;
      const float ea = a.x - m, eb = b.x - m;
      float t = fmaf(fmaf(ea, ea, eb * eb), 128.f, a.y + b.y);
      t += __shfl_xor_sync(0xffffffffu, t, 1);
      t += __shfl_xor_sync(0xffffffffu, t, 2);
      (h ? s1 : s0) = make_float2(m, rsqrt_fast(fmaf(t, 1.f / DM, LN_EPS)));
    }
  }
};

__device__ __forceinline__ void emit_panel(const uint32_t* v, char* gp, uint32_t pub) {
#pragma unroll
  for (int t = 0; t < 8; t++) { stg32(gp + t * CB_BYTES, v[2 * t]); stg32(gp + t * CB_BYTES + 128, v[2 * t + 1]); }
  __syncwarp();
  mbar_arrive_if(pub, (threadIdx.x & 31) == 0);
}
template <int NT>
__device__ __forceinline__ void stage_tiles(const uint32_t* v, uint32_t sp) {
#pragma unroll
  for (int t = 0; t < NT; t += 2) stsm_x4(sp + t * 1024, v[2 * t], v[2 * t + 1], v[2 * t + 2], v[2 * t + 3]);
}

__device__ __forceinline__ float late_zero(uint32_t addr) {
  float z; asm volatile("ld.volatile.shared.f32 %0, [%1];" : "=f"(z) : "r"(addr) : "memory"); return z;
}

template <int NT>
__device__ __forceinline__ void fold_tiles(uint32_t* v, const float* acc, const float2* cs_ptr, float2 st0, float2 st1) {
  const float n0 = -st0.x * st0.y, n1 = -st1.x * st1.y;
#pragma unroll
  for (int tile = 0; tile < NT; tile++) {
    const float2 cs = cs_ptr[tile * 4];
    float a = fmaf(acc[4 * tile + 0], st0.y, n0 * cs.x), b = fmaf(acc[4 * tile + 1], st0.y, n0 * cs.y);
    float cc = fmaf(acc[4 * tile + 2], st1.y, n1 * cs.x), d = fmaf(acc[4 * tile + 3], st1.y, n1 * cs.y);
    v[2 * tile] = pack_bf16(gelu_from_half(a), gelu_from_half(b));
    v[2 * tile + 1] = pack_bf16(gelu_from_half(cc), gelu_from_half(d));
  }
}

__device__ __forceinline__ void move_reg(uint32_t& d, uint32_t s) { asm volatile("mov.b32 %0, %1;" : "=r"(d) : "r"(s)); }
__device__ __forceinline__ void move_reg(float& d, float s) { asm volatile("mov.f32 %0, %1;" : "=f"(d) : "f"(s)); }
template <int CH, int LO, int HI, class T, int NR>
__device__ __forceinline__ void pick_group(T (&held)[NR], int idx) {
  if constexpr (HI - LO == 1) {
#pragma unroll
    for (int x = 0; x < CH; x++) move_reg(held[x], held[CH * LO + x]);
  } else {
    constexpr int MID = (LO + HI) / 2;
    if (idx < MID) pick_group<CH, LO, MID>(held, idx); else pick_group<CH, MID, HI>(held, idx);
  }
}
template <int CH>
__device__ __forceinline__ void gelu_chunk(const uint32_t* t, char* gp) {
#pragma unroll
  for (int x = 0; x < CH; x++) stg32(gp + (x >> 1) * CB_BYTES + (x & 1) * 128, gelu_pair_f16(t[x]));
}

#define REG_CONS 216
#define REG_PROD 72
__global__ void __cluster_dims__(2, 1, 1) __launch_bounds__(384, 1)
fused_kernel(const __grid_constant__ Params maps) {
  extern __shared__ __align__(1024) char smem[];
  const int tid = threadIdx.x, lane = tid & 31;
  const int warp = __shfl_sync(0xffffffffu, tid >> 5, 0), wg = warp >> 2;
  if (tid == 0) STAMP(48);
  const uint32_t sm0 = opaque(smem_u32(smem));
  if (elect_one()) {
    if (warp == 8) {
#pragma unroll
      for (int x = 0; x < CB_Q1; x++) mbar_init(sm0 + CV_BAR + 8 * x, 1);
      asm volatile("fence.mbarrier_init.release.cluster;" ::: "memory");
      load_k(maps, sm0, 0);
#pragma unroll
      for (int y = 0; y < 2; y++) {
        mbar_expect_tx(sm0 + CV_BAR + 8 * (CB_QA + y), 8192);
        load_kv(maps, sm0, y, CB_QA + y);
      }
#pragma unroll
      for (int x = CB_Q1; x < CB_ST0; x++) mbar_init(sm0 + CV_BAR + 8 * x, x < CB_QS ? 1 : x == CB_QS ? 8 : 3);
    } else if (warp == 9) {
#pragma unroll
      for (int x = CB_ST0; x < CB_COUNT; x++) mbar_init(sm0 + CV_BAR + 8 * x, x < CB_O1 ? 2 : x < CB_Y1 ? 3 : x < CB_P2 ? 8 : x == CB_P2 ? 10 : x == CB_YOUT ? 5 : x < CB_STAT ? 2 : 1);
    } else if (warp < 2) {
      asm volatile("prefetch.tensormap [%0];" :: "l"(&maps.m[M_K + warp]) : "memory");
    }
#pragma unroll
    for (int x = 0; x < 7; x++) mbar_init(sm0 + SM_BAR + 56 * warp + 8 * x, 1 << wg);
    asm volatile("fence.mbarrier_init.release.cluster;" ::: "memory");
    if (warp == 11) {
      sts32(sm0 + SM_ZERO, 0);
      const uint32_t t = tpc_id();
      if (t < 8 || (t >= 62 && t < 66)) asm volatile("{\n.reg .b32 c;\nmov.u32 c, %%clock;\nst.relaxed.gpu.global.u32 [%0], c;\n}" :: "l"(g_role + (t < 8 ? t + 4 : t - 50)) : "memory");
    }
  }
  static_assert(BAR_END == 84, "start-up work of 12 warps");
  __syncwarp();
  if (warp != 8) asm volatile("barrier.cluster.arrive.relaxed.aligned;" ::: "memory");
  conv_part(maps, sm0, warp);
  __syncwarp();
  asm volatile("barrier.cluster.wait.acquire.aligned;" ::: "memory");
  Ctx c;
  c.sm = sm0;
  c.bar = c.sm + SM_BAR;
  c.r = blockIdx.x & 1;
  {
    uint32_t role;
    asm volatile("ld.shared::cluster.u32 %0, [%1];" : "=r"(role) : "r"(mapa(sm0 + SM_ROLE, 0)) : "memory");
    role = __shfl_sync(0xffffffffu, role, 0);
    c.i = role >> 2; c.j = (role & 3) * 2 + c.r;
    c.bid = c.i * 8 + c.j;
    asm volatile("ld.shared.u32 %0, [%1];" : "=r"(c.ep) : "r"(c.sm + SM_EPOCH) : "memory");
  }

  if (tid == 0) MSTAMP(45);
  if (wg == 2) {
    reg_dealloc<REG_PROD>();
    int budget = SPIN_LIMIT;
    if (warp == 8) {
      const int hh = 16 * c.r + c.i;
      const uint32_t full0 = c.bar + 8 * (BAR_FULLA + c.r * 8), empty0 = c.bar + 8 * (BAR_EMPTYA + c.r * 9), full_peer = mapa(full0, c.r ^ 1);
      const uint32_t ring0 = c.sm + SM_A + c.r * NA * A_SLOT;
      const int nb = hh + (lane & 8 ? (lane & 2) - 1 : 0);
      const uint32_t* lf = g_flag + ((nb >= 0 && nb < 32 ? nb : hh) * 8 + (lane & 7)) * FS;
      const uint32_t* xf = g_xcnt + (hh + ((c.j >> 1) & 1) >= 16 ? 16 : 0) + (lane & 15);
      const uint32_t cb = c.sm + CV_BAR;
      if (lane == 0) mbar_arrive(cb + 8 * CB_XFREE);
      mbar_wait(cb + 8 * CB_Y2, 0, budget);
      if (lane == 0) STAMP(60);
      mbar_wait(cb + 8 * CB_P1, 0, budget);
      fence_async_smem();
      if (lane < 2) mbar_arrive_cluster(mapa(cb + 8 * CB_EARLY, lane));
      int seen = ld_relaxed(xf) - 8 * c.ep;
      mbar_wait(cb + 8 * (CB_EARLY + c.r), 0, budget);
      fence_async_global();
      if (lane == 0) MSTAMP(46);
      uint32_t slot = ring0;
      int k = 0;
#pragma unroll 1
      for (int ph = 0; ph < 10; ph++) {
        const int l = ph >= 5, s = ph - 5 * l;
        const CUtensorMap* m = &maps.m[s == 0 ? M_X3S + l : s == 1 ? M_H + l : s == 4 ? M_HID : M_X1];
        const uint32_t bytes = s == l ? A_SLOT : 8192;
        const bool local = starts_local(l, s);
        const int np = ph == 0 ? 1 : s == 4 ? 7 : 2, cnt = ph == 0 ? 16 : local ? 6 : 8, e0 = ph == 0 ? 2 * (c.j & 6) : (c.j & 6) + (local ? 2 : 0);
        const int need0 = ph == 0 ? 8 : 13 * l + (s == 0 ? 1 : s == 1 ? 3 : s == 4 ? 7 : 5);
        const uint32_t up = ph == 0 ? (c.j & 2 ? 0u : 0xffffu) : ph == 6 ? 0x33u : 0u;
        const uint32_t* fp = ph == 0 ? xf : lf;
        const uint32_t base = ph == 0 ? 8 * c.ep : 32 * c.ep;
        const bool polls = lane < (s == l ? 16 : 8);
        if (ph == 1) seen = 0;
        if (local) {
          k += 4;
          slot += slot >= ring0 + (NA - 2) * A_SLOT ? (2 - NA) * A_SLOT : 2 * A_SLOT;
        }
#pragma unroll 1
        for (int p = 0; p < np; p++) {
          uint32_t ready = __ballot_sync(0xffffffffu, seen >= need0 + p);
          if (ph == 6) ready &= ready >> 8;
#pragma unroll 1
          for (int x = 0; x < cnt; x++) {
            const int e = (e0 + x) & (ph == 0 ? 15 : 7);
            const uint32_t off = 8 * (k & 7);
            mbar_wait(empty0 + 8 * ((k - NA) & 7), ((k - NA) >> 3) & 1, budget);
            if (elect_one()) {
              mbar_expect_tx(full0 + off, bytes);
              mbar_expect_tx_cluster(full_peer + off, bytes);
            }
            if (!((ready >> e) & 1)) {
#pragma unroll 1
              do {
                if (polls) seen = ld_relaxed(fp) - base;
                ready = __ballot_sync(0xffffffffu, seen >= need0 + p);
                if (ph == 6) ready &= ready >> 8;
              } while (!((ready >> e) & 1) && --budget > 0);
              fence_async_global();
            }
            if (elect_one()) tma_2d_mc(slot, m, full0 + off, 128 * hh - 8 * ((up >> e) & 1), (np * e + p) * 8, (uint16_t)3);
            slot += slot == ring0 + (NA - 1) * A_SLOT ? (1 - NA) * A_SLOT : A_SLOT;
            k++;
          }
        }
      }
    } else if (warp == 9) {
      const uint32_t e8 = __funnelshift_r(0x76543210u, 0x76543210u, 4 * (c.j & 6));
      int k = 0;
#pragma unroll 1
      for (int ph = 0; ph < 10; ph++) {
        const int l = ph >= 5, s = ph - 5 * l;
        const uint32_t bytes = s == 2 ? 32768 : s == 3 ? 24576 : 16384, slots = s == 2 ? 3 : s == 3 ? 4 : 6;
        uint32_t dist = s == 2 ? 0x33333345u : s == 3 ? 0x44444333u : s == 4 ? 0x66655544u : 0x66666666u;
        const CUtensorMap* m = &maps.m[M_W1 + s];
        const int np = s == 4 ? 7 : 2;
        const int panel0 = s == 2 ? 7 * c.j : s == 3 ? 7 * c.j + 4 : 2 * c.j;
        const bool local = starts_local(l, s), direct = local || ph == 0;
        uint32_t slot = c.sm + SM_B + first_slot(s) * bytes;
#pragma unroll 1
        for (int o = 0; o < np; o++) {
          uint32_t tab = e8;
          if (local) tab = o ? (e8 >> 24 << 1) | ((e8 << 1) & 0xffffff00u) | 0x11111100u : (0x3210u ^ (c.j * 0x2222u)) | (e8 >> 8 << 17);
          if (ph == 0) tab = (c.j & 2 ? 0xba987654u : 0x76543210u) ^ (((c.j >> 2) ^ o) * 0x88888888u);
          const int mul = direct ? 64 : 64 * np, add = direct ? 0 : 64 * o;
#pragma unroll 1
          for (uint32_t bar = c.bar + 8 * BAR_FULLB; bar < c.bar + 8 * BAR_FULLB + 64; bar += 8) {
            const int last = k - (dist & 15), row = (tab & 15) * mul + add;
            if (last < 0) {
              mbar_wait(c.sm + CV_BAR + 8 * (k < 2 ? CB_XFREE : k < 5 ? CB_EARLY : CB_YOUT), 0, budget);
              fence_async_smem();
            }
            mbar_wait(c.bar + 8 * (BAR_EMPTYB + (last & 7)), (last >> 3) & 1, budget);
            if (elect_one()) {
              mbar_expect_tx(bar, bytes);
              tma_3d(slot, m, bar, 0, row, panel0);
            }
            slot += bytes;
            if (slot == c.sm + SM_B + 98304) slot = c.sm + SM_B;
            dist = __funnelshift_r(dist, slots, 4);
            tab >>= 4;
            k++;
          }
        }
      }
    } else {
      const int w = warp - 10;
      const int row0 = 64 * (16 * w + c.i);
      mbar_wait(c.sm + CV_BAR + 8 * CB_P2, 0, budget);
      if (w == 0) {
        fence_async_smem();
        if (lane < 2) mbar_arrive_cluster(mapa(c.sm + CV_BAR + 8 * CB_LATE, lane));
      } else if (elect_one()) {
        red_release(&g_xcnt[16 + (blockIdx.x >> 3)]);
        mbar_arrive(c.bar + 8 * BAR_REL);
        MSTAMP(44);
      }
      __syncwarp();
      uint32_t* my_flag = g_flag + ((16 * w + c.i) * 8 + c.j) * FS;
#pragma unroll 1
      for (int pc = 1; pc < 26; pc++) {
        const int l = pc >= 13, u = pc - 13 * l;
        if (pc > 1) {
          if (pc == 8) { reinterpret_cast<uint4*>(&g_part[2][c.j][row0])[lane] = make_uint4(0, 0, 0, 0); __syncwarp(); }
          mbar_wait(c.bar + 8 * (BAR_PUB + 13 * w + u), u < 2 ? 0 : l, budget);
          st_release(my_flag, 32 * c.ep + pc + 1);
        }
        float2* part = &g_part[3 * l + (u == 5)][0][0];
#pragma unroll 1
        for (uint32_t jobs = pc == 1 ? 0x453u : u == 5 ? 0x421u : u == 1 ? 4u : 0u; jobs; jobs >>= 4) {
          const int job = jobs & 15;
          if (job < 3) {
            const int r = 32 * (job - 1) + lane;
            float s0 = 0.f, s1 = 0.f, q0 = 0.f, q1 = 0.f;
#pragma unroll 2
            for (int x = 0; x < 16; x++) {
              uint32_t v[4];
              asm volatile("ld.shared.v4.u32 {%0,%1,%2,%3}, [%4];" : "=r"(v[0]), "=r"(v[1]), "=r"(v[2]), "=r"(v[3])
                           : "r"(c.sm + SM_X + w * 16384 + x * 1024 + r * 16) : "memory");
#pragma unroll
              for (int y = 0; y < 4; y++) {
                const float a = bf_lo(v[y]), b = bf_hi(v[y]);
                s0 += a; s1 += b; q0 = fmaf(a, a, q0); q1 = fmaf(b, b, q1);
              }
            }
            put_stat(part + c.j * SEQ + row0 + r, s0 + s1, q0 + q1, true, c.ep);
          } else if (job == 3) {
            if (w == 1) {
              mbar_wait(c.sm + CV_BAR + 8 * CB_YOUT, 0, budget);
              mbar_wait(c.sm + CV_BAR + 8 * CB_EARLY, 0, budget);
              if (lane == 0) red_release(&g_xcnt[32 + (blockIdx.x >> 3)]);
              __syncwarp();
            }
            uint32_t xseen;
#pragma unroll 1
            do {
              asm volatile("ld.acquire.gpu.global.u32 %0, [%1];" : "=r"(xseen) : "l"(g_xcnt + 32 + (lane & 15)) : "memory");
            } while (!__all_sync(0xffffffffu, (int)(xseen - 8 * c.ep) >= 8) && --budget > 0);
            if (w == 0) {
              float4 s = make_float4(0.f, 0.f, 0.f, 0.f);
#pragma unroll
              for (int x = 0; x < 4; x++) {
                const float4 v = __ldcg(reinterpret_cast<const float4*>(&g_cs1[x][c.j * 128]) + lane);
                s.x += v.x; s.y += v.y; s.z += v.z; s.w += v.w;
              }
              reinterpret_cast<float4*>(smem + SM_CS1)[lane] = s;
            } else {
#pragma unroll
              for (int x = 0; x < 4; x++) {
                const int y = min(32 * x + lane, 111);
                const float4 v = __ldcg(reinterpret_cast<const float4*>(g_cs3 + c.j * 448) + y);
                if (x < 2) {
                  uint32_t* d = reinterpret_cast<uint32_t*>(smem + SM_CS3) + (y >> 2) * 8 + (y & 1) * 4 + ((y >> 1) & 1);
                  d[0] = pack_f16(v.x, v.y); d[2] = pack_f16(v.z, v.w);
                } else {
                  reinterpret_cast<float4*>(smem + SM_CS3)[y] = v;
                }
              }
            }
            __syncwarp();
            if (lane == 0) mbar_arrive(c.bar + 8 * BAR_CS);
            if (c.bid == 0 && w == 0 && lane <= 16) *(lane < 16 ? g_role + lane : &g_epoch) = lane < 12 ? 0 : lane < 16 ? 0x80000000u : c.ep + 1;
          } else {
            const int r = job == 4 ? 2 * lane : token_shift(c.j) > 0 ? 64 : -2;
            const float2* src = part + min(max(row0 + r, 0), SEQ - 2);
            float4 v[8];
#pragma unroll 1
            do {
              uint32_t ok = 1;
#pragma unroll
              for (int x = 0; x < 8; x++) {
                asm volatile("ld.relaxed.gpu.global.v4.f32 {%0,%1,%2,%3}, [%4];" : "=f"(v[x].x), "=f"(v[x].y), "=f"(v[x].z), "=f"(v[x].w) : "l"(src + x * SEQ) : "memory");
                ok &= both_valid(__float_as_uint(v[x].y), __float_as_uint(v[x].w), c.ep);
              }
              if (__all_sync(0xffffffffu, ok)) break;
            } while (--budget > 0);
            float ma = 0.f, mb = 0.f, ta = 0.f, tb = 0.f;
#pragma unroll
            for (int x = 0; x < 8; x++) { ma += v[x].x; mb += v[x].z; }
            ma *= 0.125f; mb *= 0.125f;
#pragma unroll
            for (int x = 0; x < 8; x++) {
              const float ea = v[x].x - ma, eb = v[x].z - mb;
              ta += fmaf(128.f * ea, ea, __uint_as_float(__float_as_uint(v[x].y) | 1u));
              tb += fmaf(128.f * eb, eb, __uint_as_float(__float_as_uint(v[x].w) | 1u));
            }
            ta *= 1.f / DM; tb *= 1.f / DM;
            const float ra = rsqrt_fast(ta + LN_EPS), rb = rsqrt_fast(tb + LN_EPS);
            *reinterpret_cast<float4*>(smem + SM_RS + (68 * w + 2 + r) * 8) = make_float4(ma, ra, mb, rb);
            const float in = (uint32_t)(row0 + r) < SEQ ? 0.5f : 0.f;
            *reinterpret_cast<float4*>(smem + SM_RS + RS_G1 + (68 * w + 2 + r) * 8) =
                make_float4(ma, in * ra * rsqrt_fast(fmaf(ta * ra, ra, LN_EPS)), mb, in * rb * rsqrt_fast(fmaf(tb * rb, rb, LN_EPS)));
            __syncwarp();
            if (job == 4 && lane == 0) mbar_arrive(c.sm + CV_BAR + 8 * (CB_STAT + w));
          }
        }
        if (pc == 6) {
          if (elect_one()) {
            const uint32_t bar = c.bar + 8 * (BAR_OWN + w);
            fence_async_global();
            fence_async_smem();
            mbar_expect_tx(bar, 16384);
            tma_2d(c.sm + SM_X + w * 16384, &maps.m[M_Y], bar, 2 * row0, 16 * c.j);
            tma_2d(c.sm + SM_X + w * 16384 + 8192, &maps.m[M_Y], bar, 2 * row0, 16 * c.j + 8);
          }
          __syncwarp();
        }
      }
    }
    cluster_exit_barrier();
  } else {
    reg_alloc<REG_CONS>();
#define WSTAMP(idx) do {} while (0)
    const int t = tid & 127, g = lane >> 2, qd = lane & 3;
    const int wrow = 64 * (16 * wg + c.i) + (t >> 5) * 16, row = wrow + g;
    const uint32_t frag = row * 16 + qd * 4 + c.j * 16 * CB_BYTES;
    const uint32_t stage = c.sm + SM_X + wg * 16384 + (lane >> 4) * 1024 + ((t >> 5) * 16 + (lane & 15)) * 16;
    const uint32_t pub = c.bar + 8 * (BAR_PUB + 13 * wg);
    const uint32_t rstat = c.sm + SM_RS + (68 * wg + 2 + (t >> 5) * 16 + g) * 8;
    Pipe p;
    p.ko = 0; p.kp = 0; p.po = 64; p.turn = 0; p.budget = SPIN_LIMIT;
    p.a0 = desc_a(c, SM_A) + wg * NA * (A_SLOT >> 4); p.a1 = p.a0 + (A_SLOT >> 4); p.ar = p.a1 + (A_SLOT >> 4);
    p.signals = t == 0 || t == 32 || t == 64;
    p.rel = mapa(c.bar + 8 * (t == 64 ? BAR_EMPTYB : BAR_EMPTYA + wg * 9), t == 32 ? c.r ^ 1 : c.r);
    auto fence_sched = [&]() { mbar_wait(c.bar + 8 * BAR_CS, 0, p.budget); };
    uint32_t x3[32];
    float acc[64];
#pragma unroll
    for (int x = 0; x < 64; x++) acc[x] = 0.f;
    pin(acc);
    const uint32_t own = opaque(c.sm + SM_A + (wg * NA + 2 * c.r) * A_SLOT + (lane >> 4) * 1088 + ((c.j & 2 ? 0 : 4) + (t >> 5) * 16 + (lane & 15)) * 16);
    WSTAMP(0);
    if (wg == 1) {
      mbar_wait(c.bar + 8 * BAR_REL, 0, p.budget);
#pragma unroll 2
      for (int x = 0; x < 8; x++)
        reinterpret_cast<uint4*>(g_y)[blockIdx.x * 2048 + 1024 + x * 128 + t] = reinterpret_cast<const uint4*>(smem + CV_K + 128 + 16384)[x * 128 + t];
      __syncwarp();
      mbar_arrive_if(c.sm + CV_BAR + 8 * CB_YOUT, lane == 0);
    }
    {
      mbar_wait(c.bar + 8 * (BAR_FULLA + 8 * wg + 2 * c.r), 0, p.budget);
      mbar_wait(c.bar + 8 * (BAR_FULLA + 8 * wg + 2 * c.r + 1), 0, p.budget);
#pragma unroll
      for (int x = 0; x < 32; x += 4) ldsm_x4(own + x * 544, x3[x], x3[x + 1], x3[x + 2], x3[x + 3]);
    }
    const uint32_t sh_g1 = opaque((token_shift(c.j) & 3) * 0x55555555u), sh_g2 = opaque(__funnelshift_r(0xaa5faa5fu, 0xaa5faa5fu, 2 * (c.j & 6)));
    const uint64_t ak0 = 128 + ((uint64_t)__shfl_sync(0xffffffffu, hidden_zero(c.sm + SM_ZERO), 0) << 32);
#pragma unroll 1
    for (int ph = 0; ph < 6; ph++) {
      const int l = ph >= 3, s = ph - 3 * l;
      p.keep = s;
      p.wide = s == l ? 4 << 16 : 0;
      p.ak = ak0 + (s == l ? 8 : 0);
      p.sh = s == l ? (l ? sh_g2 : sh_g1) : 0;
      if (s < 2) {
        gemm_begin<128>(c, wg, warp & 3, p, s, s != l);
        if (s == 0) {
          float sum[2][4] = {}, lo[2][4] = {}, hi[2][4] = {};
#pragma unroll
          for (int x = 0; x < 32; x += 4) {
            mma16816(sum[x >> 4], x3[x], x3[x + 1], x3[x + 2], x3[x + 3], 0x3f803f80u, 0x3f803f80u);
            mma16816(lo[x >> 4], x3[x], x3[x + 1], x3[x + 2], x3[x + 3], x3[x], x3[x + 2]);
            mma16816(hi[x >> 4], x3[x], x3[x + 1], x3[x + 2], x3[x + 3], x3[x + 1], x3[x + 3]);
          }
          put_stat(&g_part[3 * l][c.j][row], sum[0][0] + sum[1][0], (g & 1) ? lo[0][1] + lo[1][1] : lo[0][0] + lo[1][0], qd == (g >> 1), c.ep);
          put_stat(&g_part[3 * l][c.j][row + 8], sum[0][2] + sum[1][2], (g & 1) ? hi[0][3] + hi[1][3] : hi[0][2] + hi[1][2], qd == (g >> 1), c.ep);
          WSTAMP(1 + 16 * l);
        }
      } else {
        char* hp = reinterpret_cast<char*>(g_hid) + frag + c.j * 40 * CB_BYTES;
        uint32_t held[64];
        float acc3[128];
        gemm_step<256, true>(acc3, c, wg, p, Nop());
        float2 s0 = make_float2(0.f, 0.f), s1 = s0;
        gemm_steps<256, false>(acc3, c, wg, p, 15, [&]() {
          mbar_wait(c.sm + CV_BAR + 8 * (CB_STAT + wg), 1, p.budget);
          s0 = lds_f2(rstat); s1 = lds_f2(rstat + 64);
          s0.y *= 0.5f; s1.y *= 0.5f;
        });
        p.drain();
        WSTAMP(6 + 16 * l);
#pragma unroll
        for (int x = 0; x < 64; x++) held[x] = pack_f16(acc3[2 * x] * ((x & 1) ? s1.y : s0.y), acc3[2 * x + 1] * ((x & 1) ? s1.y : s0.y));
        const uint32_t n0 = pack_f16(-s0.x * s0.y, -s0.x * s0.y), n1 = pack_f16(-s1.x * s1.y, -s1.x * s1.y);
        float accb[96];
#pragma unroll
        for (int x = 0; x < 24; x++) {
          const float2 cs = (reinterpret_cast<const float2*>(smem + SM_CS3 + 1024) + qd)[4 * x];
          accb[4 * x] = -s0.x * cs.x; accb[4 * x + 1] = -s0.x * cs.y; accb[4 * x + 2] = -s1.x * cs.x; accb[4 * x + 3] = -s1.x * cs.y;
        }
        pin(accb);
        WSTAMP(7 + 16 * l);
        gemm_begin<192>(c, wg, warp & 3, p, 3, false);
#pragma unroll 1
        for (int pn = 0; pn < 4; pn++) {
#pragma unroll
          for (int u = 0; u < 4; u++)
            gemm_step<192, false>(accb, c, wg, p, [&]() {
              const uint2 cs = reinterpret_cast<const uint2*>(smem + SM_CS3)[16 * pn + 4 * u + qd];
              const uint32_t h[4] = {hfma2(cs.x, n0, held[4 * u]), hfma2(cs.x, n1, held[4 * u + 1]), hfma2(cs.y, n0, held[4 * u + 2]), hfma2(cs.y, n1, held[4 * u + 3])};
              gelu_chunk<4>(h, hp + 2 * u * CB_BYTES);
            });
          hp += 8 * CB_BYTES;
          __syncwarp();
          mbar_arrive_if(pub + 8 * (6 + pn), lane == 0);
          if (pn < 3) pick_group<16, 1, 4>(held, pn + 1);
        }
        WSTAMP(8 + 16 * l);
#pragma unroll
        for (int x = 0; x < 32; x++) { acc[2 * x] = bf_lo(x3[x]); acc[2 * x + 1] = bf_hi(x3[x]); }
        pin(acc);
        WSTAMP(9 + 16 * l);
        gemm_begin<128>(c, wg, warp & 3, p, 4, false);
        gemm_step<128, false>(acc, c, wg, p, Nop());
        pin(accb);
#pragma unroll 1
        for (int hpn = 0; hpn < 6; hpn++) {
#pragma unroll
          for (int u = 0; u < 4; u++)
            gemm_step<128, false>(acc, c, wg, p, [&]() {
              const uint32_t h[2] = {pack_f16(accb[4 * u] * s0.y, accb[4 * u + 1] * s0.y), pack_f16(accb[4 * u + 2] * s1.y, accb[4 * u + 3] * s1.y)};
              gelu_chunk<2>(h, hp + u * CB_BYTES);
            });
          hp += 4 * CB_BYTES;
          __syncwarp();
          mbar_arrive_if(pub + 8 * (10 + (hpn >> 1)), (hpn & 1) && lane == 0);
          if (hpn < 5) pick_group<16, 1, 6>(accb, hpn + 1);
        }
        WSTAMP(12 + 16 * l);
      }
      gemm_steps<128, true, true>(acc, c, wg, p, s == 2 ? 31 : 16, Nop());
      const uint32_t z = hidden_zero(c.sm + SM_ZERO), stg = stage + z;
      char* gp = reinterpret_cast<char*>(s == 0 ? g_h : s == 1 ? g_x1 : g_x3[1]) + (frag + z);
      float2 s0, s1;
      if (s == 0) {
        mbar_wait(c.sm + CV_BAR + 8 * (CB_STAT + wg), 0, p.budget);
        const uint32_t ra = rstat + RS_G1 + (l == 0 ? 8 * token_shift(c.j) : 0);
        s0 = lds_f2(ra); s1 = lds_f2(ra + 64);
        fence_sched();
        p.drain();
        WSTAMP(2 + 16 * l);
#pragma unroll
        for (int pn = 0; pn < 2; pn++) {
          uint32_t v[16];
          if (pn == 0) {
            fold_tiles<4>(v, acc, reinterpret_cast<const float2*>(smem + SM_CS1) + qd, s0, s1);
#pragma unroll
            for (int x = 0; x < 8; x++) stg32(gp + (x >> 1) * CB_BYTES + (x & 1) * 128, v[x]);
            fence_sched();
            fold_tiles<4>(v + 8, acc + 16, reinterpret_cast<const float2*>(smem + SM_CS1) + qd + 16, s0, s1);
#pragma unroll
            for (int x = 8; x < 16; x++) stg32(gp + (x >> 1) * CB_BYTES + (x & 1) * 128, v[x]);
            __syncwarp();
            mbar_arrive_if(pub + 8 * 2, lane == 0);
          } else {
            fold_tiles<8>(v, acc + 32, reinterpret_cast<const float2*>(smem + SM_CS1) + qd + 32, s0, s1);
            emit_panel(v, gp + 8 * CB_BYTES, pub + 8 * 3);
          }
          if (l == 0) stage_tiles<8>(v, stg + pn * 8192);
        }
        s0 = lds_f2(rstat); s1 = lds_f2(rstat + 64);
        const float nb0 = -s0.x * s0.y, nb1 = -s1.x * s1.y;
#pragma unroll
        for (int x = 0; x < 32; x++) {
          acc[2 * x] = fmaf(bf_lo(x3[x]), (x & 1) ? s1.y : s0.y, (x & 1) ? nb1 : nb0);
          acc[2 * x + 1] = fmaf(bf_hi(x3[x]), (x & 1) ? s1.y : s0.y, (x & 1) ? nb1 : nb0);
        }
        WSTAMP(3 + 16 * l);
      } else if (s == 1) {
        fence_sched();
        p.drain();
        WSTAMP(4 + 16 * l);
        uint32_t v[32];
#pragma unroll
        for (int x = 0; x < 32; x++) v[x] = pack_bf16(acc[2 * x], acc[2 * x + 1]);
        emit_panel(v, gp, pub + 8 * 4);
        stage_tiles<16>(v, stg);
        gemm_begin<256>(c, wg, warp & 3, p, 2, true);
        emit_panel(v + 16, gp + 8 * CB_BYTES, pub + 8 * 5);
#pragma unroll
        for (int x = 0; x < 32; x++) x3[x] = badd2(x3[x], v[x]);
        WSTAMP(5 + 16 * l);
      } else if (l == 0) {
        float2* mine = &g_part[2][c.j][row + z];
        const float2* sp = &g_part[2][2 * qd][row + z];
        fence_sched();
        p.drain();
        WSTAMP(10);
        put_partial(acc, mine, 0);
        WSTAMP(11);
        RowStats rs;
        rs.load(sp, sp + 8);
        uint32_t yv[32];
        mbar_wait(c.bar + 8 * (BAR_OWN + wg), 0, p.budget);
#pragma unroll
        for (int x = 0; x < 16; x++)
          asm volatile("ld.shared.v2.u32 {%0,%1}, [%2];" : "=r"(yv[2 * x]), "=r"(yv[2 * x + 1]) : "r"(c.sm + SM_X + wg * 16384 + x * 1024 + t * 8) : "memory");
#pragma unroll
        for (int x = 0; x < 32; x++) asm volatile("cvt.rn.bf16x2.f32 %0, %1, %2;" : "=r"(x3[x]) : "f"(acc[2 * x + 1]), "f"(acc[2 * x]));
        rs.finish(sp, sp + 8, p.budget, s0, s1);
        WSTAMP(13);
        float nb0 = -s0.x * s0.y, nb1 = -s1.x * s1.y;
#pragma unroll
        for (int pn = 0; pn < 2; pn++) {
          if (pn == 1) { const float z = late_zero(c.sm + SM_ZERO); nb0 += z; nb1 += z; }
#pragma unroll
          for (int x = 16 * pn; x < 16 * pn + 16; x++) {
            const float r = (x & 1) ? s1.y : s0.y, nb = (x & 1) ? nb1 : nb0;
            asm("fma.rn.bf16x2 %0, %1, %2, %0;" : "+r"(x3[x]) : "r"(pack_bf16(fmaf(acc[2 * x], r, nb), fmaf(acc[2 * x + 1], r, nb))), "r"(yv[x]));
          }
          if (pn == 1) stage_tiles<16>(x3, stg);
          emit_panel(x3 + 16 * pn, gp + pn * 8 * CB_BYTES, pub + 8 * pn);
        }
      } else {
        const uint32_t ob = c.sm + SM_X + warp * 4096, oa = ob + (lane & 15) * 128 + (((lane >> 4) ^ (lane & 7)) << 4) + z;
        fence_sched();
        p.drain();
        WSTAMP(26);
#pragma unroll
        for (int pn = 0; pn < 2; pn++) {
#pragma unroll
          for (int x = 0; x < 8; x += 2) {
            const float* a = acc + 32 * pn + 4 * x;
            stsm_x4((oa ^ (x << 4)) + pn * 2048, pack_bf16(a[0], a[1]), pack_bf16(a[2], a[3]), pack_bf16(a[4], a[5]), pack_bf16(a[6], a[7]));
          }
          fence_async_smem();
          __syncwarp();
          if (elect_one()) {
            tma_store_2d(&maps.m[M_OUT], ob + pn * 2048, c.j * 128 + 64 * pn, 64 * (16 * wg + c.i) + 16 * (warp & 3));
            if (pn == 1) {
              bulk_commit();
              asm volatile("cp.async.bulk.wait_group.read 0;" ::: "memory");
            }
          }
        }
        __syncwarp();
      }
    }
    WSTAMP(27);
    cluster_exit_barrier();
    WSTAMP(30);
  }
}

typedef CUresult (*EncodeFn)(CUtensorMap*, CUtensorMapDataType, cuuint32_t, void*, const cuuint64_t*, const cuuint64_t*, const cuuint32_t*,
                             const cuuint32_t*, CUtensorMapInterleave, CUtensorMapSwizzle, CUtensorMapL2promotion, CUtensorMapFloatOOBfill);

void encode(EncodeFn fn, CUtensorMap* m, CUtensorMapDataType type, const void* ptr, int rank, const cuuint64_t* dims, const cuuint64_t* strides,
            const cuuint32_t* box, CUtensorMapSwizzle swizzle, CUtensorMapL2promotion promo = CU_TENSOR_MAP_L2_PROMOTION_L2_128B) {
  const cuuint32_t es[3] = {1, 1, 1};
  fn(m, type, rank, const_cast<void*>(ptr), dims, strides, box, es, CU_TENSOR_MAP_INTERLEAVE_NONE, swizzle, promo, CU_TENSOR_MAP_FLOAT_OOB_FILL_NONE);
}
void map_act(EncodeFn fn, CUtensorMap* m, const void* ptr, int cols, int rows = 64) {
  const cuuint64_t dims[2] = {(cuuint64_t)SEQ * 2, (cuuint64_t)cols / 8}, st[1] = {(cuuint64_t)CB_BYTES};
  const cuuint32_t box[2] = {(cuuint32_t)rows * 2, 8};
  encode(fn, m, CU_TENSOR_MAP_DATA_TYPE_UINT64, ptr, 2, dims, st, box, CU_TENSOR_MAP_SWIZZLE_NONE);
}
void map_rows(EncodeFn fn, CUtensorMap* m, const void* ptr, int rows, int cols, int box_rows, int box_cols, CUtensorMapSwizzle swizzle,
              CUtensorMapL2promotion promo) {
  const cuuint64_t dims[2] = {(cuuint64_t)cols, (cuuint64_t)rows}, st[1] = {(cuuint64_t)cols * 2};
  const cuuint32_t box[2] = {(cuuint32_t)box_cols, (cuuint32_t)box_rows};
  encode(fn, m, CU_TENSOR_MAP_DATA_TYPE_BFLOAT16, ptr, 2, dims, st, box, swizzle, promo);
}
void map_w(EncodeFn fn, CUtensorMap* m, const void* ptr, int rows, int cols, int panels) {
  const cuuint64_t dims[3] = {64, (cuuint64_t)rows, (cuuint64_t)cols / 64}, st[2] = {(cuuint64_t)cols * 2, 128};
  const cuuint32_t box[3] = {64, 64, (cuuint32_t)panels};
  encode(fn, m, CU_TENSOR_MAP_DATA_TYPE_BFLOAT16, ptr, 3, dims, st, box, CU_TENSOR_MAP_SWIZZLE_128B);
}

}

extern "C" void kernel_launch(void* const* d_in, const int* in_sizes, int n_in, void* d_out, int out_size) {
  (void)in_sizes; (void)n_in; (void)out_size;
  const bf16* q = (const bf16*)d_in[0];
  const bf16* k = (const bf16*)d_in[1];
  const bf16* v = (const bf16*)d_in[2];
  const bf16* shift_k = (const bf16*)d_in[3];
  const bf16* ssm_k = (const bf16*)d_in[4];
  const bf16* ssm_d = (const bf16*)d_in[5];
  const bf16* w1 = (const bf16*)d_in[7];
  const bf16* w2 = (const bf16*)d_in[8];
  const bf16* w3 = (const bf16*)d_in[9];
  const bf16* w4 = (const bf16*)d_in[10];

  static EncodeFn fn = nullptr;
  static void *p_x3, *p_h, *p_x1, *p_hid, *p_y;
  if (!fn) {
    void* p = nullptr;
    cudaDriverEntryPointQueryResult qr;
    cudaGetDriverEntryPoint("cuTensorMapEncodeTiled", &p, cudaEnableDefault, &qr);
    fn = (EncodeFn)p;
    cudaGetSymbolAddress(&p_x3, g_x3);
    cudaGetSymbolAddress(&p_h, g_h);
    cudaGetSymbolAddress(&p_x1, g_x1);
    cudaGetSymbolAddress(&p_hid, g_hid);
    cudaGetSymbolAddress(&p_y, g_y);
    cudaFuncSetAttribute(fused_kernel, cudaFuncAttributeMaxDynamicSharedMemorySize, MEGA_SMEM);
  }
  Params maps;
  map_act(fn, &maps.m[M_X3B], (const bf16*)p_x3 + SEQ * DM, DM);
  map_act(fn, &maps.m[M_X3S], p_x3, DM, 68);
  map_act(fn, &maps.m[M_H], p_h, DM);
  map_act(fn, &maps.m[M_HS], p_h, DM, 68);
  map_act(fn, &maps.m[M_X1], p_x1, DM);
  map_act(fn, &maps.m[M_HID], p_hid, FF);
  map_act(fn, &maps.m[M_Y], p_y, DM);
  map_rows(fn, &maps.m[M_OUT], d_out, SEQ, DM, 16, 64, CU_TENSOR_MAP_SWIZZLE_128B, CU_TENSOR_MAP_L2_PROMOTION_L2_128B);
  map_w(fn, &maps.m[M_W1], w1, DM, DM, 2);
  map_w(fn, &maps.m[M_W2], w2, DM, DM, 2);
  map_w(fn, &maps.m[M_W3A], w3, DM, FF, 4);
  map_w(fn, &maps.m[M_W3B], w3, DM, FF, 3);
  map_w(fn, &maps.m[M_W4], w4, FF, DM, 2);

  map_rows(fn, &maps.m[M_K], k, SEQ, DM, 256, 8, CU_TENSOR_MAP_SWIZZLE_NONE, CU_TENSOR_MAP_L2_PROMOTION_L2_128B);
  map_rows(fn, &maps.m[M_V], v, SEQ, DM, 256, 8, CU_TENSOR_MAP_SWIZZLE_NONE, CU_TENSOR_MAP_L2_PROMOTION_L2_128B);
  map_rows(fn, &maps.m[M_Q], q, SEQ, DM, 256, 8, CU_TENSOR_MAP_SWIZZLE_NONE, CU_TENSOR_MAP_L2_PROMOTION_L2_128B);
  map_rows(fn, &maps.m[M_W1C], w1, DM, DM, 256, 32, CU_TENSOR_MAP_SWIZZLE_64B, CU_TENSOR_MAP_L2_PROMOTION_L2_128B);
  map_rows(fn, &maps.m[M_W3C], w3, DM, FF, 256, 32, CU_TENSOR_MAP_SWIZZLE_64B, CU_TENSOR_MAP_L2_PROMOTION_L2_128B);
  maps.q = q; maps.shift_k = shift_k; maps.ssm_k = ssm_k; maps.ssm_d = ssm_d; maps.w2 = w2;
  fused_kernel<<<128, 384, MEGA_SMEM, cudaStreamPerThread>>>(maps);
}
```

```cpp
#include <cuda_runtime.h>
#include <cuda_bf16.h>
#include <cuda.h>
#include <stdint.h>

namespace {

typedef __nv_bfloat16 bf16;
constexpr int SEQ = 2048, DM = 1024, FF = 3584;
constexpr float LN_EPS = 1e-5f;

constexpr int CB_BYTES = SEQ * 16;
__device__ __align__(1024) bf16 g_x3[2][SEQ * DM];
__device__ __align__(1024) bf16 g_h[SEQ * DM];
__device__ __align__(1024) bf16 g_x1[SEQ * DM];
__device__ __align__(1024) bf16 g_hid[SEQ * FF];
__device__ __align__(1024) bf16 g_y[SEQ * DM];
__device__ __align__(128) float g_cs1[4][DM];
__device__ __align__(128) float g_cs3[FF];
__device__ __align__(128) uint32_t g_epoch;
__device__ __align__(128) float2 g_part[5][8][SEQ];
__device__ __align__(128) float2 g_qstat[SEQ];
__device__ __align__(128) uint32_t g_qcnt;
__device__ __align__(128) uint32_t g_xcnt[48];
constexpr int FS = 8;
__device__ __align__(128) uint32_t g_flag[32 * 8 * FS];
__device__ __align__(128) uint32_t g_role[16];

__device__ __forceinline__ uint32_t smem_u32(const void* p) { return (uint32_t)__cvta_generic_to_shared(p); }
__device__ __forceinline__ uint32_t opaque(uint32_t x) { uint32_t y; asm volatile("mov.u32 %0, %1;" : "=r"(y) : "r"(x)); return y; }
__device__ __forceinline__ void mbar_init(uint32_t bar, uint32_t cnt) { asm volatile("mbarrier.init.shared::cta.b64 [%0], %1;" :: "r"(bar), "r"(cnt)); }
__device__ __forceinline__ void mbar_expect_tx(uint32_t bar, uint32_t bytes) {
  asm volatile("mbarrier.arrive.expect_tx.shared::cta.b64 _, [%0], %1;" :: "r"(bar), "r"(bytes) : "memory");
}
__device__ __forceinline__ void mbar_expect_tx_cluster(uint32_t bar, uint32_t bytes) {
  asm volatile("mbarrier.arrive.expect_tx.shared::cluster.b64 _, [%0], %1;" :: "r"(bar), "r"(bytes) : "memory");
}
__device__ __forceinline__ void mbar_arrive_cluster(uint32_t bar) { asm volatile("mbarrier.arrive.shared::cluster.b64 _, [%0];" :: "r"(bar) : "memory"); }
__device__ __forceinline__ void mbar_arrive(uint32_t bar) { asm volatile("mbarrier.arrive.shared::cta.b64 _, [%0];" :: "r"(bar) : "memory"); }
__device__ __forceinline__ void mbar_arrive_if(uint32_t bar, bool cond) {
  asm volatile("{\n.reg .pred p;\nsetp.ne.b32 p, %1, 0;\n@p mbarrier.arrive.shared::cta.b64 _, [%0];\n}" :: "r"(bar), "r"((uint32_t)cond) : "memory");
}
constexpr int SPIN_LIMIT = 1 << 16;
__device__ __forceinline__ bool mbar_try(uint32_t bar, uint32_t parity) {
  uint32_t done;
  asm volatile("{\n.reg .pred p;\nmbarrier.try_wait.parity.shared::cta.b64 p, [%1], %2;\nselp.b32 %0, 1, 0, p;\n}"
               : "=r"(done) : "r"(bar), "r"(parity) : "memory");
  return done != 0;
}
__device__ __forceinline__ void mbar_wait(uint32_t bar, uint32_t parity, int& budget) {
#pragma unroll 1
  while (!mbar_try(bar, parity)) { if (--budget <= 0) break; }
}
__device__ __forceinline__ bool elect_one() {
  uint32_t p;
  asm volatile("{\n.reg .pred P;\nelect.sync _|P, 0xffffffff;\nselp.b32 %0, 1, 0, P;\n}" : "=r"(p));
  return p != 0;
}
__device__ __forceinline__ void fence_async_smem() { asm volatile("fence.proxy.async.shared::cta;" ::: "memory"); }
__device__ __forceinline__ void fence_async_global() { asm volatile("fence.proxy.async.global;" ::: "memory"); }
__device__ __forceinline__ void named_bar(int id, int n) { asm volatile("bar.sync %0, %1;" :: "r"(id), "r"(n) : "memory"); }
__device__ __forceinline__ uint4 ld_nc_u4(const void* p) {
  uint4 v; asm volatile("ld.global.nc.L1::no_allocate.v4.u32 {%0,%1,%2,%3}, [%4];" : "=r"(v.x), "=r"(v.y), "=r"(v.z), "=r"(v.w) : "l"(p)); return v;
}
__device__ __forceinline__ void tma_2d_mc(uint32_t dst, const CUtensorMap* m, uint32_t bar, int c0, int c1, uint16_t mask) {
  asm volatile("cp.async.bulk.tensor.2d.shared::cluster.global.mbarrier::complete_tx::bytes.multicast::cluster [%0], [%1, {%3, %4}], [%2], %5;"
               :: "r"(dst), "l"(m), "r"(bar), "r"(c0), "r"(c1), "h"(mask) : "memory");
}
__device__ __forceinline__ void tma_2d(uint32_t dst, const CUtensorMap* m, uint32_t bar, int c0, int c1) {
  asm volatile("cp.async.bulk.tensor.2d.shared::cluster.global.mbarrier::complete_tx::bytes [%0], [%1, {%3, %4}], [%2];"
               :: "r"(dst), "l"(m), "r"(bar), "r"(c0), "r"(c1) : "memory");
}
__device__ __forceinline__ void bulk_copy_cluster(uint32_t dst, uint32_t src, uint32_t bytes, uint32_t bar) {
  asm volatile("cp.async.bulk.shared::cluster.shared::cta.mbarrier::complete_tx::bytes [%0], [%1], %2, [%3];"
               :: "r"(dst), "r"(src), "r"(bytes), "r"(bar) : "memory");
}
__device__ __forceinline__ uint32_t mapa(uint32_t addr, uint32_t cta) {
  uint32_t r; asm volatile("mapa.shared::cluster.u32 %0, %1, %2;" : "=r"(r) : "r"(addr), "r"(cta)); return r;
}
__device__ __forceinline__ void bulk_store(void* dst, uint32_t src, uint32_t bytes) {
  asm volatile("cp.async.bulk.global.shared::cta.bulk_group [%0], [%1], %2;" :: "l"(dst), "r"(src), "r"(bytes) : "memory");
}
__device__ __forceinline__ void tma_3d(uint32_t dst, const CUtensorMap* m, uint32_t bar, int c0, int c1, int c2) {
  asm volatile("cp.async.bulk.tensor.3d.shared::cluster.global.mbarrier::complete_tx::bytes [%0], [%1, {%3, %4, %5}], [%2];"
               :: "r"(dst), "l"(m), "r"(bar), "r"(c0), "r"(c1), "r"(c2) : "memory");
}
__device__ __forceinline__ void tma_store_2d(const CUtensorMap* m, uint32_t src, int c0, int c1) {
  asm volatile("cp.async.bulk.tensor.2d.global.shared::cta.bulk_group [%0, {%2, %3}], [%1];" :: "l"(m), "r"(src), "r"(c0), "r"(c1) : "memory");
}
__device__ __forceinline__ void bulk_commit() { asm volatile("cp.async.bulk.commit_group;" ::: "memory"); }
__device__ __forceinline__ void bulk_wait_all() { asm volatile("cp.async.bulk.wait_group 0;" ::: "memory"); }
__device__ __forceinline__ void cluster_exit_barrier() {
  __syncwarp();
  asm volatile("barrier.cluster.arrive.relaxed;\nbarrier.cluster.wait;" ::: "memory");
}
__device__ __forceinline__ void wg_fence() { asm volatile("wgmma.fence.sync.aligned;" ::: "memory"); }
__device__ __forceinline__ void wg_commit() { asm volatile("wgmma.commit_group.sync.aligned;" ::: "memory"); }
template <int N> __device__ __forceinline__ void wg_wait() { asm volatile("wgmma.wait_group.sync.aligned %0;" :: "n"(N) : "memory"); }
template <int R> __device__ __forceinline__ void reg_alloc() { asm volatile("setmaxnreg.inc.sync.aligned.u32 %0;" :: "n"(R)); }
template <int R> __device__ __forceinline__ void reg_dealloc() { asm volatile("setmaxnreg.dec.sync.aligned.u32 %0;" :: "n"(R)); }
__device__ __forceinline__ void ldsm_x4(uint32_t addr, uint32_t& r0, uint32_t& r1, uint32_t& r2, uint32_t& r3) {
  asm volatile("ldmatrix.sync.aligned.m8n8.x4.shared.b16 {%0,%1,%2,%3}, [%4];" : "=r"(r0), "=r"(r1), "=r"(r2), "=r"(r3) : "r"(addr));
}
__device__ __forceinline__ void ldsm_x4_t(uint32_t addr, uint32_t& r0, uint32_t& r1, uint32_t& r2, uint32_t& r3) {
  asm volatile("ldmatrix.sync.aligned.m8n8.x4.trans.shared.b16 {%0,%1,%2,%3}, [%4];" : "=r"(r0), "=r"(r1), "=r"(r2), "=r"(r3) : "r"(addr));
}
__device__ __forceinline__ void stsm_x4(uint32_t addr, uint32_t r0, uint32_t r1, uint32_t r2, uint32_t r3) {
  asm volatile("stmatrix.sync.aligned.m8n8.x4.shared.b16 [%0], {%1,%2,%3,%4};" :: "r"(addr), "r"(r0), "r"(r1), "r"(r2), "r"(r3) : "memory");
}
__device__ __forceinline__ float2 lds_f2(uint32_t addr) { float2 v; asm volatile("ld.shared.v2.f32 {%0,%1}, [%2];" : "=f"(v.x), "=f"(v.y) : "r"(addr)); return v; }
__device__ __forceinline__ void sts32(uint32_t addr, uint32_t v) { asm volatile("st.shared.u32 [%0], %1;" :: "r"(addr), "r"(v) : "memory"); }
__device__ __forceinline__ void sts128(uint32_t addr, uint4 v) {
  asm volatile("st.shared.v4.u32 [%0], {%1,%2,%3,%4};" :: "r"(addr), "r"(v.x), "r"(v.y), "r"(v.z), "r"(v.w) : "memory");
}
__device__ __forceinline__ void mma16816(float (&d)[4], uint32_t a0, uint32_t a1, uint32_t a2, uint32_t a3, uint32_t b0, uint32_t b1) {
  asm("mma.sync.aligned.m16n8k16.row.col.f32.bf16.bf16.f32 {%0,%1,%2,%3}, {%4,%5,%6,%7}, {%8,%9}, {%0,%1,%2,%3};"
               : "+f"(d[0]), "+f"(d[1]), "+f"(d[2]), "+f"(d[3]) : "r"(a0), "r"(a1), "r"(a2), "r"(a3), "r"(b0), "r"(b1));
}
__device__ __forceinline__ uint32_t pack_bf16(float lo, float hi) {
  uint32_t r; asm("cvt.rn.bf16x2.f32 %0, %1, %2;" : "=r"(r) : "f"(hi), "f"(lo)); return r;
}
__device__ __forceinline__ float bf_lo(uint32_t v) { return __uint_as_float(v << 16); }
__device__ __forceinline__ float bf_hi(uint32_t v) { return __uint_as_float(v & 0xffff0000u); }
__device__ __forceinline__ uint32_t bmul2(uint32_t a, uint32_t b) { uint32_t r; asm("mul.rn.bf16x2 %0, %1, %2;" : "=r"(r) : "r"(a), "r"(b)); return r; }
__device__ __forceinline__ uint32_t badd2(uint32_t a, uint32_t b) { uint32_t r; asm("add.rn.bf16x2 %0, %1, %2;" : "=r"(r) : "r"(a), "r"(b)); return r; }
#define STAMP(idx) do {} while (0)
#define MSTAMP(idx) do {} while (0)
#define BSTAMP(idx, saddr) do {} while (0)

__device__ __forceinline__ uint32_t pack_f16(float lo, float hi) {
  uint32_t r; asm("cvt.rn.satfinite.f16x2.f32 %0, %1, %2;" : "=r"(r) : "f"(hi), "f"(lo)); return r;
}
__device__ __forceinline__ uint32_t hfma2(uint32_t a, uint32_t b, uint32_t c) { uint32_t r; asm("fma.rn.f16x2 %0, %1, %2, %3;" : "=r"(r) : "r"(a), "r"(b), "r"(c)); return r; }
__device__ __forceinline__ uint32_t gelu_pair_f16(uint32_t h) {
  const uint32_t c0 = 0x3e623e62u, c1 = 0x34913491u;
  uint32_t u, p, z, t, r, o;
  asm("mul.rn.f16x2 %0, %1, %1;" : "=r"(u) : "r"(h));
  asm("fma.rn.f16x2 %0, %1, %2, %3;" : "=r"(p) : "r"(u), "r"(c1), "r"(c0));
  asm("mul.rn.f16x2 %0, %1, %2;" : "=r"(z) : "r"(h), "r"(p));
  asm("tanh.approx.f16x2 %0, %1;" : "=r"(t) : "r"(z));
  asm("fma.rn.f16x2 %0, %1, %2, %1;" : "=r"(r) : "r"(h), "r"(t));
  float lo, hi;
  asm("{\n.reg .f16 a, b;\nmov.b32 {a, b}, %2;\ncvt.f32.f16 %0, a;\ncvt.f32.f16 %1, b;\n}" : "=f"(lo), "=f"(hi) : "r"(r));
  asm("cvt.rn.bf16x2.f32 %0, %1, %2;" : "=r"(o) : "f"(hi), "f"(lo));
  return o;
}
__device__ __forceinline__ float gelu_from_half(float h) {
  const float c0 = 2.f * 0.7978845608028654f, c1 = 8.f * 0.7978845608028654f * 0.044715f;
  float z = h * fmaf(h * h, c1, c0);
  float t; asm("tanh.approx.f32 %0, %1;" : "=f"(t) : "f"(z));
  return fmaf(h, t, h);
}
__device__ __forceinline__ void wgmma_ss_n128(float (&d)[64], uint64_t da, uint64_t db) {
  asm volatile(
    "{\n"
    "wgmma.mma_async.sync.aligned.m64n128k16.f32.bf16.bf16 "
    "{%0, %1, %2, %3, %4, %5, %6, %7, %8, %9, %10, %11, %12, %13, %14, %15, "
    "%16, %17, %18, %19, %20, %21, %22, %23, %24, %25, %26, %27, %28, %29, %30, %31, "
    "%32, %33, %34, %35, %36, %37, %38, %39, %40, %41, %42, %43, %44, %45, %46, %47, "
    "%48, %49, %50, %51, %52, %53, %54, %55, %56, %57, %58, %59, %60, %61, %62, %63}, "
    "%64, %65, 1, 1, 1, 0, 1;\n}\n"
    : "+f"(d[0]), "+f"(d[1]), "+f"(d[2]), "+f"(d[3]), "+f"(d[4]), "+f"(d[5]), "+f"(d[6]), "+f"(d[7]),
      "+f"(d[8]), "+f"(d[9]), "+f"(d[10]), "+f"(d[11]), "+f"(d[12]), "+f"(d[13]), "+f"(d[14]), "+f"(d[15]),
      "+f"(d[16]), "+f"(d[17]), "+f"(d[18]), "+f"(d[19]), "+f"(d[20]), "+f"(d[21]), "+f"(d[22]), "+f"(d[23]),
      "+f"(d[24]), "+f"(d[25]), "+f"(d[26]), "+f"(d[27]), "+f"(d[28]), "+f"(d[29]), "+f"(d[30]), "+f"(d[31]),
      "+f"(d[32]), "+f"(d[33]), "+f"(d[34]), "+f"(d[35]), "+f"(d[36]), "+f"(d[37]), "+f"(d[38]), "+f"(d[39]),
      "+f"(d[40]), "+f"(d[41]), "+f"(d[42]), "+f"(d[43]), "+f"(d[44]), "+f"(d[45]), "+f"(d[46]), "+f"(d[47]),
      "+f"(d[48]), "+f"(d[49]), "+f"(d[50]), "+f"(d[51]), "+f"(d[52]), "+f"(d[53]), "+f"(d[54]), "+f"(d[55]),
      "+f"(d[56]), "+f"(d[57]), "+f"(d[58]), "+f"(d[59]), "+f"(d[60]), "+f"(d[61]), "+f"(d[62]), "+f"(d[63])
    : "l"(da), "l"(db));
}
__device__ __forceinline__ void wgmma_ss_n192(float (&d)[96], uint64_t da, uint64_t db) {
  asm volatile(
    "{\n"
    "wgmma.mma_async.sync.aligned.m64n192k16.f32.bf16.bf16 "
    "{%0, %1, %2, %3, %4, %5, %6, %7, %8, %9, %10, %11, %12, %13, %14, %15, "
    "%16, %17, %18, %19, %20, %21, %22, %23, %24, %25, %26, %27, %28, %29, %30, %31, "
    "%32, %33, %34, %35, %36, %37, %38, %39, %40, %41, %42, %43, %44, %45, %46, %47, "
    "%48, %49, %50, %51, %52, %53, %54, %55, %56, %57, %58, %59, %60, %61, %62, %63, "
    "%64, %65, %66, %67, %68, %69, %70, %71, %72, %73, %74, %75, %76, %77, %78, %79, "
    "%80, %81, %82, %83, %84, %85, %86, %87, %88, %89, %90, %91, %92, %93, %94, %95}, "
    "%96, %97, 1, 1, 1, 0, 1;\n}\n"
    : "+f"(d[0]), "+f"(d[1]), "+f"(d[2]), "+f"(d[3]), "+f"(d[4]), "+f"(d[5]), "+f"(d[6]), "+f"(d[7]),
      "+f"(d[8]), "+f"(d[9]), "+f"(d[10]), "+f"(d[11]), "+f"(d[12]), "+f"(d[13]), "+f"(d[14]), "+f"(d[15]),
      "+f"(d[16]), "+f"(d[17]), "+f"(d[18]), "+f"(d[19]), "+f"(d[20]), "+f"(d[21]), "+f"(d[22]), "+f"(d[23]),
      "+f"(d[24]), "+f"(d[25]), "+f"(d[26]), "+f"(d[27]), "+f"(d[28]), "+f"(d[29]), "+f"(d[30]), "+f"(d[31]),
      "+f"(d[32]), "+f"(d[33]), "+f"(d[34]), "+f"(d[35]), "+f"(d[36]), "+f"(d[37]), "+f"(d[38]), "+f"(d[39]),
      "+f"(d[40]), "+f"(d[41]), "+f"(d[42]), "+f"(d[43]), "+f"(d[44]), "+f"(d[45]), "+f"(d[46]), "+f"(d[47]),
      "+f"(d[48]), "+f"(d[49]), "+f"(d[50]), "+f"(d[51]), "+f"(d[52]), "+f"(d[53]), "+f"(d[54]), "+f"(d[55]),
      "+f"(d[56]), "+f"(d[57]), "+f"(d[58]), "+f"(d[59]), "+f"(d[60]), "+f"(d[61]), "+f"(d[62]), "+f"(d[63]),
      "+f"(d[64]), "+f"(d[65]), "+f"(d[66]), "+f"(d[67]), "+f"(d[68]), "+f"(d[69]), "+f"(d[70]), "+f"(d[71]),
      "+f"(d[72]), "+f"(d[73]), "+f"(d[74]), "+f"(d[75]), "+f"(d[76]), "+f"(d[77]), "+f"(d[78]), "+f"(d[79]),
      "+f"(d[80]), "+f"(d[81]), "+f"(d[82]), "+f"(d[83]), "+f"(d[84]), "+f"(d[85]), "+f"(d[86]), "+f"(d[87]),
      "+f"(d[88]), "+f"(d[89]), "+f"(d[90]), "+f"(d[91]), "+f"(d[92]), "+f"(d[93]), "+f"(d[94]), "+f"(d[95])
    : "l"(da), "l"(db));
}
__device__ __forceinline__ void wgmma_ss_n256(float (&d)[128], uint64_t da, uint64_t db) {
  asm volatile(
    "{\n"
    "wgmma.mma_async.sync.aligned.m64n256k16.f32.bf16.bf16 "
    "{%0, %1, %2, %3, %4, %5, %6, %7, %8, %9, %10, %11, %12, %13, %14, %15, "
    "%16, %17, %18, %19, %20, %21, %22, %23, %24, %25, %26, %27, %28, %29, %30, %31, "
    "%32, %33, %34, %35, %36, %37, %38, %39, %40, %41, %42, %43, %44, %45, %46, %47, "
    "%48, %49, %50, %51, %52, %53, %54, %55, %56, %57, %58, %59, %60, %61, %62, %63, "
    "%64, %65, %66, %67, %68, %69, %70, %71, %72, %73, %74, %75, %76, %77, %78, %79, "
    "%80, %81, %82, %83, %84, %85, %86, %87, %88, %89, %90, %91, %92, %93, %94, %95, "
    "%96, %97, %98, %99, %100, %101, %102, %103, %104, %105, %106, %107, %108, %109, %110, %111, "
    "%112, %113, %114, %115, %116, %117, %118, %119, %120, %121, %122, %123, %124, %125, %126, %127}, "
    "%128, %129, 1, 1, 1, 0, 1;\n}\n"
    : "+f"(d[0]), "+f"(d[1]), "+f"(d[2]), "+f"(d[3]), "+f"(d[4]), "+f"(d[5]), "+f"(d[6]), "+f"(d[7]),
      "+f"(d[8]), "+f"(d[9]), "+f"(d[10]), "+f"(d[11]), "+f"(d[12]), "+f"(d[13]), "+f"(d[14]), "+f"(d[15]),
      "+f"(d[16]), "+f"(d[17]), "+f"(d[18]), "+f"(d[19]), "+f"(d[20]), "+f"(d[21]), "+f"(d[22]), "+f"(d[23]),
      "+f"(d[24]), "+f"(d[25]), "+f"(d[26]), "+f"(d[27]), "+f"(d[28]), "+f"(d[29]), "+f"(d[30]), "+f"(d[31]),
      "+f"(d[32]), "+f"(d[33]), "+f"(d[34]), "+f"(d[35]), "+f"(d[36]), "+f"(d[37]), "+f"(d[38]), "+f"(d[39]),
      "+f"(d[40]), "+f"(d[41]), "+f"(d[42]), "+f"(d[43]), "+f"(d[44]), "+f"(d[45]), "+f"(d[46]), "+f"(d[47]),
      "+f"(d[48]), "+f"(d[49]), "+f"(d[50]), "+f"(d[51]), "+f"(d[52]), "+f"(d[53]), "+f"(d[54]), "+f"(d[55]),
      "+f"(d[56]), "+f"(d[57]), "+f"(d[58]), "+f"(d[59]), "+f"(d[60]), "+f"(d[61]), "+f"(d[62]), "+f"(d[63]),
      "+f"(d[64]), "+f"(d[65]), "+f"(d[66]), "+f"(d[67]), "+f"(d[68]), "+f"(d[69]), "+f"(d[70]), "+f"(d[71]),
      "+f"(d[72]), "+f"(d[73]), "+f"(d[74]), "+f"(d[75]), "+f"(d[76]), "+f"(d[77]), "+f"(d[78]), "+f"(d[79]),
      "+f"(d[80]), "+f"(d[81]), "+f"(d[82]), "+f"(d[83]), "+f"(d[84]), "+f"(d[85]), "+f"(d[86]), "+f"(d[87]),
      "+f"(d[88]), "+f"(d[89]), "+f"(d[90]), "+f"(d[91]), "+f"(d[92]), "+f"(d[93]), "+f"(d[94]), "+f"(d[95]),
      "+f"(d[96]), "+f"(d[97]), "+f"(d[98]), "+f"(d[99]), "+f"(d[100]), "+f"(d[101]), "+f"(d[102]), "+f"(d[103]),
      "+f"(d[104]), "+f"(d[105]), "+f"(d[106]), "+f"(d[107]), "+f"(d[108]), "+f"(d[109]), "+f"(d[110]), "+f"(d[111]),
      "+f"(d[112]), "+f"(d[113]), "+f"(d[114]), "+f"(d[115]), "+f"(d[116]), "+f"(d[117]), "+f"(d[118]), "+f"(d[119]),
      "+f"(d[120]), "+f"(d[121]), "+f"(d[122]), "+f"(d[123]), "+f"(d[124]), "+f"(d[125]), "+f"(d[126]), "+f"(d[127])
    : "l"(da), "l"(db));
}
__device__ __forceinline__ void wgmma_ss_n128_p(float (&d)[64], uint64_t da, uint64_t db, uint32_t keep) {
  asm volatile(
    "{\n.reg .pred p;\nsetp.ne.b32 p, %66, 0;\n"
    "{\n"
    "wgmma.mma_async.sync.aligned.m64n128k16.f32.bf16.bf16 "
    "{%0, %1, %2, %3, %4, %5, %6, %7, %8, %9, %10, %11, %12, %13, %14, %15, "
    "%16, %17, %18, %19, %20, %21, %22, %23, %24, %25, %26, %27, %28, %29, %30, %31, "
    "%32, %33, %34, %35, %36, %37, %38, %39, %40, %41, %42, %43, %44, %45, %46, %47, "
    "%48, %49, %50, %51, %52, %53, %54, %55, %56, %57, %58, %59, %60, %61, %62, %63}, "
    "%64, %65, p, 1, 1, 0, 1;\n}\n}\n"
    : "+f"(d[0]), "+f"(d[1]), "+f"(d[2]), "+f"(d[3]), "+f"(d[4]), "+f"(d[5]), "+f"(d[6]), "+f"(d[7]),
      "+f"(d[8]), "+f"(d[9]), "+f"(d[10]), "+f"(d[11]), "+f"(d[12]), "+f"(d[13]), "+f"(d[14]), "+f"(d[15]),
      "+f"(d[16]), "+f"(d[17]), "+f"(d[18]), "+f"(d[19]), "+f"(d[20]), "+f"(d[21]), "+f"(d[22]), "+f"(d[23]),
      "+f"(d[24]), "+f"(d[25]), "+f"(d[26]), "+f"(d[27]), "+f"(d[28]), "+f"(d[29]), "+f"(d[30]), "+f"(d[31]),
      "+f"(d[32]), "+f"(d[33]), "+f"(d[34]), "+f"(d[35]), "+f"(d[36]), "+f"(d[37]), "+f"(d[38]), "+f"(d[39]),
      "+f"(d[40]), "+f"(d[41]), "+f"(d[42]), "+f"(d[43]), "+f"(d[44]), "+f"(d[45]), "+f"(d[46]), "+f"(d[47]),
      "+f"(d[48]), "+f"(d[49]), "+f"(d[50]), "+f"(d[51]), "+f"(d[52]), "+f"(d[53]), "+f"(d[54]), "+f"(d[55]),
      "+f"(d[56]), "+f"(d[57]), "+f"(d[58]), "+f"(d[59]), "+f"(d[60]), "+f"(d[61]), "+f"(d[62]), "+f"(d[63])
    : "l"(da), "l"(db), "r"(keep));
}
__device__ __forceinline__ void wgmma_ss_n256_first(float (&d)[128], uint64_t da, uint64_t db) {
  asm volatile(
    "{\n"
    "mov.b32 %0, 0; mov.b32 %1, 0; mov.b32 %2, 0; mov.b32 %3, 0; mov.b32 %4, 0; mov.b32 %5, 0; mov.b32 %6, 0; mov.b32 %7, 0;\n"
    "mov.b32 %8, 0; mov.b32 %9, 0; mov.b32 %10, 0; mov.b32 %11, 0; mov.b32 %12, 0; mov.b32 %13, 0; mov.b32 %14, 0; mov.b32 %15, 0;\n"
    "mov.b32 %16, 0; mov.b32 %17, 0; mov.b32 %18, 0; mov.b32 %19, 0; mov.b32 %20, 0; mov.b32 %21, 0; mov.b32 %22, 0; mov.b32 %23, 0;\n"
    "mov.b32 %24, 0; mov.b32 %25, 0; mov.b32 %26, 0; mov.b32 %27, 0; mov.b32 %28, 0; mov.b32 %29, 0; mov.b32 %30, 0; mov.b32 %31, 0;\n"
    "mov.b32 %32, 0; mov.b32 %33, 0; mov.b32 %34, 0; mov.b32 %35, 0; mov.b32 %36, 0; mov.b32 %37, 0; mov.b32 %38, 0; mov.b32 %39, 0;\n"
    "mov.b32 %40, 0; mov.b32 %41, 0; mov.b32 %42, 0; mov.b32 %43, 0; mov.b32 %44, 0; mov.b32 %45, 0; mov.b32 %46, 0; mov.b32 %47, 0;\n"
    "mov.b32 %48, 0; mov.b32 %49, 0; mov.b32 %50, 0; mov.b32 %51, 0; mov.b32 %52, 0; mov.b32 %53, 0; mov.b32 %54, 0; mov.b32 %55, 0;\n"
    "mov.b32 %56, 0; mov.b32 %57, 0; mov.b32 %58, 0; mov.b32 %59, 0; mov.b32 %60, 0; mov.b32 %61, 0; mov.b32 %62, 0; mov.b32 %63, 0;\n"
    "mov.b32 %64, 0; mov.b32 %65, 0; mov.b32 %66, 0; mov.b32 %67, 0; mov.b32 %68, 0; mov.b32 %69, 0; mov.b32 %70, 0; mov.b32 %71, 0;\n"
    "mov.b32 %72, 0; mov.b32 %73, 0; mov.b32 %74, 0; mov.b32 %75, 0; mov.b32 %76, 0; mov.b32 %77, 0; mov.b32 %78, 0; mov.b32 %79, 0;\n"
    "mov.b32 %80, 0; mov.b32 %81, 0; mov.b32 %82, 0; mov.b32 %83, 0; mov.b32 %84, 0; mov.b32 %85, 0; mov.b32 %86, 0; mov.b32 %87, 0;\n"
    "mov.b32 %88, 0; mov.b32 %89, 0; mov.b32 %90, 0; mov.b32 %91, 0; mov.b32 %92, 0; mov.b32 %93, 0; mov.b32 %94, 0; mov.b32 %95, 0;\n"
    "mov.b32 %96, 0; mov.b32 %97, 0; mov.b32 %98, 0; mov.b32 %99, 0; mov.b32 %100, 0; mov.b32 %101, 0; mov.b32 %102, 0; mov.b32 %103, 0;\n"
    "mov.b32 %104, 0; mov.b32 %105, 0; mov.b32 %106, 0; mov.b32 %107, 0; mov.b32 %108, 0; mov.b32 %109, 0; mov.b32 %110, 0; mov.b32 %111, 0;\n"
    "mov.b32 %112, 0; mov.b32 %113, 0; mov.b32 %114, 0; mov.b32 %115, 0; mov.b32 %116, 0; mov.b32 %117, 0; mov.b32 %118, 0; mov.b32 %119, 0;\n"
    "mov.b32 %120, 0; mov.b32 %121, 0; mov.b32 %122, 0; mov.b32 %123, 0; mov.b32 %124, 0; mov.b32 %125, 0; mov.b32 %126, 0; mov.b32 %127, 0;\n"
    "wgmma.mma_async.sync.aligned.m64n256k16.f32.bf16.bf16 "
    "{%0, %1, %2, %3, %4, %5, %6, %7, %8, %9, %10, %11, %12, %13, %14, %15, "
    "%16, %17, %18, %19, %20, %21, %22, %23, %24, %25, %26, %27, %28, %29, %30, %31, "
    "%32, %33, %34, %35, %36, %37, %38, %39, %40, %41, %42, %43, %44, %45, %46, %47, "
    "%48, %49, %50, %51, %52, %53, %54, %55, %56, %57, %58, %59, %60, %61, %62, %63, "
    "%64, %65, %66, %67, %68, %69, %70, %71, %72, %73, %74, %75, %76, %77, %78, %79, "
    "%80, %81, %82, %83, %84, %85, %86, %87, %88, %89, %90, %91, %92, %93, %94, %95, "
    "%96, %97, %98, %99, %100, %101, %102, %103, %104, %105, %106, %107, %108, %109, %110, %111, "
    "%112, %113, %114, %115, %116, %117, %118, %119, %120, %121, %122, %123, %124, %125, %126, %127}, "
    "%128, %129, 1, 1, 1, 0, 1;\n}\n"
    : "=f"(d[0]), "=f"(d[1]), "=f"(d[2]), "=f"(d[3]), "=f"(d[4]), "=f"(d[5]), "=f"(d[6]), "=f"(d[7]),
      "=f"(d[8]), "=f"(d[9]), "=f"(d[10]), "=f"(d[11]), "=f"(d[12]), "=f"(d[13]), "=f"(d[14]), "=f"(d[15]),
      "=f"(d[16]), "=f"(d[17]), "=f"(d[18]), "=f"(d[19]), "=f"(d[20]), "=f"(d[21]), "=f"(d[22]), "=f"(d[23]),
      "=f"(d[24]), "=f"(d[25]), "=f"(d[26]), "=f"(d[27]), "=f"(d[28]), "=f"(d[29]), "=f"(d[30]), "=f"(d[31]),
      "=f"(d[32]), "=f"(d[33]), "=f"(d[34]), "=f"(d[35]), "=f"(d[36]), "=f"(d[37]), "=f"(d[38]), "=f"(d[39]),
      "=f"(d[40]), "=f"(d[41]), "=f"(d[42]), "=f"(d[43]), "=f"(d[44]), "=f"(d[45]), "=f"(d[46]), "=f"(d[47]),
      "=f"(d[48]), "=f"(d[49]), "=f"(d[50]), "=f"(d[51]), "=f"(d[52]), "=f"(d[53]), "=f"(d[54]), "=f"(d[55]),
      "=f"(d[56]), "=f"(d[57]), "=f"(d[58]), "=f"(d[59]), "=f"(d[60]), "=f"(d[61]), "=f"(d[62]), "=f"(d[63]),
      "=f"(d[64]), "=f"(d[65]), "=f"(d[66]), "=f"(d[67]), "=f"(d[68]), "=f"(d[69]), "=f"(d[70]), "=f"(d[71]),
      "=f"(d[72]), "=f"(d[73]), "=f"(d[74]), "=f"(d[75]), "=f"(d[76]), "=f"(d[77]), "=f"(d[78]), "=f"(d[79]),
      "=f"(d[80]), "=f"(d[81]), "=f"(d[82]), "=f"(d[83]), "=f"(d[84]), "=f"(d[85]), "=f"(d[86]), "=f"(d[87]),
      "=f"(d[88]), "=f"(d[89]), "=f"(d[90]), "=f"(d[91]), "=f"(d[92]), "=f"(d[93]), "=f"(d[94]), "=f"(d[95]),
      "=f"(d[96]), "=f"(d[97]), "=f"(d[98]), "=f"(d[99]), "=f"(d[100]), "=f"(d[101]), "=f"(d[102]), "=f"(d[103]),
      "=f"(d[104]), "=f"(d[105]), "=f"(d[106]), "=f"(d[107]), "=f"(d[108]), "=f"(d[109]), "=f"(d[110]), "=f"(d[111]),
      "=f"(d[112]), "=f"(d[113]), "=f"(d[114]), "=f"(d[115]), "=f"(d[116]), "=f"(d[117]), "=f"(d[118]), "=f"(d[119]),
      "=f"(d[120]), "=f"(d[121]), "=f"(d[122]), "=f"(d[123]), "=f"(d[124]), "=f"(d[125]), "=f"(d[126]), "=f"(d[127])
    : "l"(da), "l"(db));
}

template <int N> struct Mma;
template <> struct Mma<128> {
  static __device__ __forceinline__ void ss(float (&d)[64], uint64_t a, uint64_t b) { wgmma_ss_n128(d, a, b); }
  static __device__ __forceinline__ void ss(float (&d)[64], uint64_t a, uint64_t b, uint32_t keep) { wgmma_ss_n128_p(d, a, b, keep); }
};
template <> struct Mma<192> {
  static __device__ __forceinline__ void ss(float (&d)[96], uint64_t a, uint64_t b) { wgmma_ss_n192(d, a, b); }
};
template <> struct Mma<256> {
  static __device__ __forceinline__ void ss(float (&d)[128], uint64_t a, uint64_t b) { wgmma_ss_n256(d, a, b); }
  static __device__ __forceinline__ void ss(float (&d)[128], uint64_t a, uint64_t b, uint32_t) { wgmma_ss_n256_first(d, a, b); }
};
template <int R> __device__ __forceinline__ void pin(float (&d)[R]) {
#pragma unroll
  for (int x = 0; x < R; x++) asm volatile("" : "+f"(d[x]));
}

__device__ __forceinline__ uint32_t ld_relaxed(const uint32_t* p) {
  uint32_t v; asm volatile("ld.relaxed.gpu.global.u32 %0, [%1];" : "=r"(v) : "l"(p) : "memory"); return v;
}
__device__ __forceinline__ void red_release(uint32_t* p) { asm volatile("red.release.gpu.global.add.u32 [%0], 1;" :: "l"(p) : "memory"); }
__device__ __forceinline__ uint32_t both_valid(uint32_t a, uint32_t b, uint32_t ep) {
  uint32_t r; asm("lop3.b32 %0, %1, %2, %3, 0x42;" : "=r"(r) : "r"(a), "r"(b), "r"(ep)); return r;
}
__device__ __forceinline__ uint32_t tagged(float v, uint32_t ep) { return (__float_as_uint(v) | 1u) ^ (ep & 1u); }
__device__ __forceinline__ void st_release(uint32_t* p, uint32_t v) { asm volatile("st.release.gpu.global.u32 [%0], %1;" :: "l"(p), "r"(v) : "memory"); }
__device__ __forceinline__ void stg32(void* p, uint32_t v) { asm volatile("st.global.u32 [%0], %1;" :: "l"(p), "r"(v) : "memory"); }
__device__ __forceinline__ float rsqrt_fast(float x) { float r; asm("rsqrt.approx.ftz.f32 %0, %1;" : "=f"(r) : "f"(x)); return r; }
__device__ __forceinline__ uint32_t gate_pair(uint32_t x, uint32_t y, uint32_t r, uint32_t nb) {
  uint32_t o;
  asm("{\n.reg .b16 l, h;\n.reg .b32 ll, hh, t;\nmov.b32 {l, h}, %3;\nmov.b32 ll, {l, l};\nmov.b32 hh, {h, h};\n"
      "fma.rn.bf16x2 t, %1, ll, %4;\nfma.rn.bf16x2 t, %1, hh, t;\nfma.rn.bf16x2 %0, t, %2, %1;\n}" : "=r"(o) : "r"(x), "r"(y), "r"(r), "r"(nb));
  return o;
}

constexpr int CV_KT_O = 4144;
constexpr int CV_KT_CH = 8336;
constexpr int CV_KH = 2064;
constexpr int CV_U_PLANE = 2240;
constexpr int CV_U_CH = 4496;
constexpr int CV_VQ = 8320, CV_Y_CH = 1040, CV_XROW = 2064;
constexpr int SM_BAR = 0;
constexpr int CV_K = 896;
constexpr int CV_X = CV_K + 128 + 32768;
constexpr int CV_ST0 = CV_X + 16 * CV_XROW;
constexpr int CV_KT = CV_ST0 + 8192;
constexpr int CV_QS = CV_KT + 8 * CV_KT_CH;
constexpr int CV_U = 142848;
constexpr int CV_V = CV_U + 8 * CV_U_CH;
constexpr int CV_ST1 = CV_V + 4 * CV_VQ;
constexpr int SM_ZERO = CV_ST1 + 8192, SM_ROLE = SM_ZERO + 4, SM_EPOCH = SM_ZERO + 8;
constexpr int CV_END = SM_ZERO + 16;
static_assert(CV_QS + 1024 <= CV_U && CV_X % 1024 == 0 && CV_V % 128 == 0, "layout");
constexpr int CV_BAR = SM_BAR + 8 * 84, BAR_REL = 25;
enum { CB_K0, CB_QA, CB_Q0, CB_Q1, CB_Q2, CB_Q3, CB_K1, CB_X0, CB_X1, CB_QC0, CB_QC1, CB_QS, CB_U1, CB_U2,
       CB_ST0, CB_ST1, CB_O1, CB_P1, CB_Y1, CB_Y2, CB_P2, CB_EARLY, CB_LATE, CB_YOUT, CB_STAT, CB_XFREE = CB_STAT + 2, CB_COUNT };
static_assert(CV_BAR + 8 * CB_COUNT <= CV_K, "layout");

__device__ __forceinline__ uint32_t lds32_nv(uint32_t addr) { uint32_t v; asm("ld.shared.u32 %0, [%1];" : "=r"(v) : "r"(addr)); return v; }
__device__ __forceinline__ void ldsm_x4_nv(uint32_t addr, uint32_t& r0, uint32_t& r1, uint32_t& r2, uint32_t& r3) {
  asm("ldmatrix.sync.aligned.m8n8.x4.shared.b16 {%0,%1,%2,%3}, [%4];" : "=r"(r0), "=r"(r1), "=r"(r2), "=r"(r3) : "r"(addr));
}
__device__ __forceinline__ void stsm_x4_t(uint32_t addr, uint32_t r0, uint32_t r1, uint32_t r2, uint32_t r3) {
  asm volatile("stmatrix.sync.aligned.m8n8.x4.trans.shared.b16 [%0], {%1,%2,%3,%4};" :: "r"(addr), "r"(r0), "r"(r1), "r"(r2), "r"(r3) : "memory");
}
__device__ __forceinline__ void bulk_load(uint32_t dst, const void* src, uint32_t bytes, uint32_t bar) {
  asm volatile("cp.async.bulk.shared::cluster.global.mbarrier::complete_tx::bytes [%0], [%1], %2, [%3];" :: "r"(dst), "l"(src), "r"(bytes), "r"(bar) : "memory");
}
__device__ __forceinline__ void mbar_wait_plain(uint32_t bar, uint32_t parity) {
#pragma unroll 1
  for (int spins = 0; spins < SPIN_LIMIT && !mbar_try(bar, parity); spins++) {}
}

__device__ __forceinline__ void shift_chunk(uint32_t src) {
  uint4 e;
  uint32_t nx;
  asm volatile("ld.shared.v4.u32 {%0,%1,%2,%3}, [%4];" : "=r"(e.x), "=r"(e.y), "=r"(e.z), "=r"(e.w) : "r"(src));
  asm volatile("ld.shared.u32 %0, [%1];" : "=r"(nx) : "r"(src + 16));
  sts128(src + CV_KT_O, make_uint4(__byte_perm(e.x, e.y, 0x5432), __byte_perm(e.y, e.z, 0x5432), __byte_perm(e.z, e.w, 0x5432), __byte_perm(e.w, nx, 0x5432)));
}
__device__ __forceinline__ void kv_block(uint32_t sm, int t0, const uint32_t (&wp)[4], int lane) {
  const int mi = lane >> 3, rev = 7 - (lane & 7);
  uint32_t vv[4], res[4];
  ldsm_x4(sm + CV_V + (t0 >> 9) * (CV_VQ - 8192) + (t0 + 8 * mi + rev) * 16, vv[0], vv[1], vv[2], vv[3]);
#pragma unroll
  for (int i = 0; i < 4; i++) {
    uint32_t k0, k1, k2, k3;
    ldsm_x4(sm + CV_K + (8 + t0 + 8 * i + rev - mi) * 16, k0, k1, k2, k3);
    res[i] = bmul2(badd2(badd2(badd2(bmul2(k3, wp[3]), bmul2(k2, wp[2])), bmul2(k1, wp[1])), bmul2(k0, wp[0])), vv[i]);
  }
  stsm_x4_t(sm + CV_U + (lane & 7) * CV_U_CH + (1 - (mi & 1)) * CV_U_PLANE + (8 + (t0 >> 4) + (mi >> 1)) * 16, res[0], res[1], res[2], res[3]);
}
template <int T0, int NT, int D0, int D1, int J0, int J1>
__device__ __forceinline__ void conv_phase(float (&acc)[16][4], uint32_t abase, uint32_t bbase, uint32_t zero) {
  abase += zero; bbase += zero;
#pragma unroll 1
  for (int dl = 0; dl < 8; dl++) {
    uint32_t bf[NT][2];
#pragma unroll
    for (int j = 0; j < NT; j += 2) ldsm_x4_nv(bbase + (T0 + j) * 128 - dl * 16, bf[j][0], bf[j][1], bf[j + 1][0], bf[j + 1][1]);
    const uint32_t ap = abase + dl * 32;
#pragma unroll
    for (int dh = D0; dh < D1; dh++) {
      const uint32_t a0 = lds32_nv(ap + dh * 256), a1 = lds32_nv(ap + dh * 256 - 16), a2 = lds32_nv(ap + dh * 256 + 16);
      const uint32_t a3 = a0 + zero;
#pragma unroll
      for (int j = 0; j < NT; j++)
        if (dh + T0 + j >= J0 && dh + T0 + j < J1) mma16816(acc[dh + T0 + j], a0, a1, a2, a3, bf[j][0], bf[j][1]);
    }
  }
}
__device__ __forceinline__ uint32_t hidden_zero(uint32_t addr) {
  uint32_t z; asm volatile("ld.volatile.shared.u32 %0, [%1];" : "=r"(z) : "r"(addr) : "memory"); return z;
}
template <int J0, int J1>
__device__ __forceinline__ void stage_y(const float (&acc)[16][4], uint32_t ys, uint32_t bar) {
#pragma unroll
  for (int j = J0; j < J1; j += 2)
    stsm_x4_t(ys + (j >> 2) * CV_VQ + (j & 3) * 128, pack_bf16(acc[j][0], acc[j][1]), pack_bf16(acc[j][2], acc[j][3]),
              pack_bf16(acc[j + 1][0], acc[j + 1][1]), pack_bf16(acc[j + 1][2], acc[j + 1][3]));
  if (J0) {
    __syncwarp();
    mbar_arrive_if(bar, (threadIdx.x & 31) == 0);
  }
}

constexpr int CV_JS = 8;
enum { M_K, M_V, M_Q, M_W1C, M_W3C, M_X3S, M_X3B, M_H, M_HS, M_X1, M_HID, M_W1, M_W2, M_W3A, M_W3B, M_W4, M_OUT, M_Y, M_COUNT };
struct alignas(64) Params {
  const bf16 *q, *shift_k, *ssm_k, *ssm_d, *w2;
  CUtensorMap m[M_COUNT];
};
__device__ __forceinline__ void prefetch_line(const void* p) { asm volatile("prefetch.global.L2 [%0];" :: "l"(p) : "memory"); }

__device__ __forceinline__ uint32_t tpc_id() { uint32_t smid; asm volatile("mov.u32 %0, %%smid;" : "=r"(smid)); return smid >> 1; }
__device__ __forceinline__ uint32_t pick_role(uint32_t t, int lane) {
  uint32_t gpc = t < 32 ? t & 7 : t < 60 ? 1 + (t - 32) % 7 : t < 62 ? t - 54 : 0;
  const uint32_t d = ld_relaxed(g_role + 12 + (lane >> 3)) - ld_relaxed(g_role + 4 + (lane & 7)) + 4096;
  const uint32_t match = __ballot_sync(0xffffffffu, d < 8192) & 0x3e3e3e3eu;
  const uint32_t nine = (match | match >> 8 | match >> 16 | match >> 24) & 0xff;
  if (t >= 62) gpc = max(__ffs((match >> (8 * t - 496)) & 0xff) - 1, 0);
  const uint32_t below = (1u << gpc) - 1, pos = (nine >> gpc) & 1 ? __popc(nine & below) : __popc(nine) + __popc(~nine & below & 0xfe);
  uint32_t cls = gpc == 0 ? 0 : min(pos, 7 - pos);
  if (pos > 3 && cls < __popc(nine) && t < 8) cls = 0;
  uint32_t role = 0;
  if (lane == 0) {
#pragma unroll 1
    for (uint32_t k = 0; k < 4; k++) {
      const uint32_t p = (cls + k) & 3, ticket = atomicAdd(&g_role[p], 1u);
      if (ticket < 16) { role = ticket * 4 + p; break; }
    }
  }
  return role;
}

__device__ __forceinline__ void load_k(const Params& pr, uint32_t sm, int x) {
  const uint32_t bar = sm + CV_BAR + 8 * (x ? CB_K1 : CB_K0), bytes = x ? 4096 - CV_KH : CV_KH;
  mbar_expect_tx(bar, 8 * bytes);
#pragma unroll 1
  for (int ch = 0; ch < 8; ch++)
    bulk_load(sm + CV_KT + ch * CV_KT_CH + 32 + x * CV_KH, reinterpret_cast<const char*>(pr.ssm_k) + (blockIdx.x * 8 + ch) * 4096 + x * CV_KH, bytes, bar);
}
__device__ __forceinline__ void load_kv(const Params& pr, uint32_t sm, int y, int barrier) {
  tma_2d(sm + CV_K + 128 + y * 4096, &pr.m[M_K], sm + CV_BAR + 8 * barrier, blockIdx.x * 8, y * 256);
  tma_2d(sm + CV_V + (y >> 1) * CV_VQ + (y & 1) * 4096, &pr.m[M_V], sm + CV_BAR + 8 * barrier, blockIdx.x * 8, y * 256);
}

__device__ __forceinline__ void conv_part(const Params& pr, uint32_t sm, int warp) {
  const int tid = threadIdx.x, lane = tid & 31;
  const int b = blockIdx.x, d0 = b * 8;
  const uint32_t kt = sm + CV_KT, ub = sm + CV_U, bar = sm + CV_BAR;
  const int g = lane >> 2, qd = lane & 3, mi = lane >> 3;
  if (warp == 8) {
    asm volatile("bar.arrive 1, 384;" ::: "memory");
    const uint32_t ep = ld_relaxed(&g_epoch);
    if (elect_one()) {
      load_k(pr, sm, 1);
#pragma unroll 1
      for (int y = 2; y < 8; y++) {
        if (y == 6) {
          mbar_expect_tx(bar + 8 * CB_X0, 32768);
#pragma unroll 1
          for (int r = 0; r < 16; r++) bulk_load(sm + CV_X + r * CV_XROW, pr.q + (size_t)(b * 16 + r) * DM, 2048, bar + 8 * CB_X0);
        }
        if (!(y & 1)) mbar_expect_tx(bar + 8 * (CB_Q0 + (y >> 1)), 16384);
        load_kv(pr, sm, y, CB_Q0 + (y >> 1));
      }
#pragma unroll 1
      for (int x = M_Q; x < M_COUNT; x++) asm volatile("prefetch.tensormap [%0];" :: "l"(&pr.m[x]) : "memory");
    }
    __syncwarp();
    const uint32_t role = b & 1 ? 0 : pick_role(tpc_id(), lane);
    if (lane == 0) {
      sts32(sm + SM_EPOCH, ep);
      sts32(sm + SM_ROLE, role);
      asm volatile("fence.release.sync_restrict::shared::cta.cluster;" ::: "memory");
    }
    __syncwarp();
    asm volatile("barrier.cluster.arrive.relaxed.aligned;" ::: "memory");
    auto load_q = [&](int x) {
      mbar_wait_plain(bar + 8 * (CB_U1 + x), 0);
      fence_async_smem();
      if (elect_one()) {
        mbar_expect_tx(bar + 8 * (CB_QC0 + x), 16384);
#pragma unroll 1
        for (int y = 4 * x; y < 4 * x + 4; y++) tma_2d(sm + CV_K + 128 + y * 4096, &pr.m[M_Q], bar + 8 * (CB_QC0 + x), d0, y * 256);
      }
    };
    const int npieces = b < 112 ? 5 : 1;
    const int xr = (mi >> 1) * 8 + (lane & 7);
    const uint32_t xa = sm + CV_X + xr * 64 + (((mi & 1) ^ ((xr >> 1) & 3)) << 4);
    float cs[8][4] = {};
    auto q_stats = [&]() {
      mbar_wait_plain(bar + 8 * CB_QS, 0);
      float sum = 0.f, sq = 0.f;
#pragma unroll
      for (int x = 0; x < 8; x++) { const float2 v = lds_f2(sm + CV_QS + x * 128 + (lane & 15) * 8); sum += v.x; sq += v.y; }
      const float mean = sum * (1.f / DM), rs = rsqrt_fast(fmaxf(fmaf(-mean, mean, sq * (1.f / DM)), 0.f) + LN_EPS);
      const uint32_t rh = pack_bf16(0.f, rs);
      if (lane < 16)
        asm volatile("st.relaxed.gpu.global.v2.b32 [%0], {%1,%2};" :: "l"(g_qstat + b * 16 + lane), "r"(tagged(__uint_as_float(pack_bf16(rs - bf_hi(rh), bf_hi(rh))), ep)),
                     "r"(pack_bf16(-mean * rs, -mean * rs)) : "memory");
      if (lane == 0) { STAMP(47); asm volatile("red.relaxed.gpu.global.add.u32 [%0], 1;" :: "l"(&g_qcnt) : "memory"); }
    };
#pragma unroll 1
    for (int pc = -3; pc < npieces; pc++) {
      if (pc == -2) q_stats();
      if (pc >= 0) {
        mbar_wait_plain(bar + 8 * (CB_X0 + ((pc + 1) & 1)), ((pc + 1) >> 1) & 1);
#pragma unroll 1
        for (int r = 0; r < 16; r += 4) {
#pragma unroll
          for (int x = 0; x < 8; x++) {
            uint32_t a0, a1, a2, a3;
            ldsm_x4_t((xa ^ ((x & 1) << 5)) + ((pc + 1) & 1) * 16384 + (r + (x >> 1)) * 1024, a0, a1, a2, a3);
            mma16816(cs[x], a0, a1, a2, a3, 0x3f803f80u, 0x3f803f80u);
          }
        }
        if (pc == 0 || pc == 4) {
          float t = 0.f;
#pragma unroll
          for (int x = 0; x < 8; x += 2) {
            t += qd & 2 ? (qd & 1 ? cs[x + 1][2] : cs[x + 1][0]) : (qd & 1 ? cs[x][2] : cs[x][0]);
            cs[x][0] = cs[x][2] = cs[x + 1][0] = cs[x + 1][2] = 0.f;
          }
          (pc ? g_cs3 + 32 * b : g_cs1[b & 3] + 32 * (b >> 2))[8 * qd + g] = t;
        }
        __syncwarp();
      }
      if (pc > -3 && pc + 2 < npieces && elect_one()) {
        const uint32_t bx = bar + 8 * (CB_X0 + ((pc + 1) & 1));
        mbar_expect_tx(bx, 16384);
        tma_2d(sm + CV_X + ((pc + 1) & 1) * 16384, &pr.m[pc == -2 ? M_W1C : M_W3C], bx, 32 * (pc == -2 ? b >> 2 : b), 256 * (pc == -2 ? b & 3 : pc + 1));
      }
      if (pc == -3 || pc == min(2, npieces - 1)) load_q(pc >= 0);
    }
#pragma unroll 1
    for (int x = 0; x < 4; x++) prefetch_line(reinterpret_cast<const char*>(pr.w2) + (b * 128 + x * 32 + lane) * 128);
    if (lane == 0) STAMP(52);
    return;
  }

  const uint32_t dpair = __ldg(reinterpret_cast<const uint32_t*>(pr.ssm_d + d0 + 2 * qd));
  const int wi = warp - (warp > 8), ti = 32 * wi + lane;
  {
    if (tid < 160) {
      const int x = tid - 128, y = x & 3;
      sts128(tid < 128 ? ub + (tid >> 4) * CV_U_CH + ((tid >> 3) & 1) * CV_U_PLANE + (tid & 7) * 16
                       : y == 3 ? sm + CV_K + (x >> 2) * 16 : kt + (x >> 2) * CV_KT_CH + (y == 2 ? 4128 : y * 16), make_uint4(0, 0, 0, 0));
    }
    uint32_t wp[4];
    {
      const uint4 a = ld_nc_u4(pr.shift_k + (d0 + 2 * qd) * 4);
      wp[0] = __byte_perm(a.x, a.z, 0x5410); wp[1] = __byte_perm(a.x, a.z, 0x7632);
      wp[2] = __byte_perm(a.y, a.w, 0x5410); wp[3] = __byte_perm(a.y, a.w, 0x7632);
    }
    const uint32_t kc = kt + (lane & 7) * CV_KT_CH;
    named_bar(1, 384);
#pragma unroll 1
    for (int x = 0; x < 2; x++) {
      mbar_wait_plain(bar + 8 * (x ? CB_K1 : CB_K0), 0);
#pragma unroll 1
      for (uint32_t a = kc + ((ti >> 3) + (x ? 130 - 32 : 0)) * 16; a < kc + (x ? 258 : 130) * 16; a += x ? 192 : 704) shift_chunk(a);
      __syncwarp();
      mbar_arrive_if(bar + 8 * CB_O1, x && lane == 0);
      if (tid == 0) BSTAMP(54, kt);
#pragma unroll 1
      for (int t0 = warp < 8 ? 32 * wi : 32 * wi + 256; t0 < (x ? SEQ : 512); t0 += x ? 96 : 256) {
        mbar_wait_plain(bar + 8 * (t0 < 256 ? CB_QA : CB_Q0 + (t0 >> 9)), 0);
        if (tid == 0) BSTAMP(56, kt);
        kv_block(sm, t0, wp, lane);
        constexpr int T1 = 128 * CV_JS + 32;
        __syncwarp();
        mbar_arrive_if(bar + 8 * (CB_U1 + (t0 >= T1)), t0 + 96 >= (t0 < T1 ? T1 : SEQ) && lane == 0);
      }
      if (x == 0) named_bar(4, 352);
      if (warp < 8) break;
    }
  }

  if (warp < 8) {
    const int o = 2 * qd - g;
    const uint32_t abase = kt + warp * CV_KT_CH + 32 + ((g & 1) ? CV_KT_O + (o - 1) * 2 : o * 2);
    const uint32_t bbase = ub + warp * CV_U_CH + (mi & 1) * CV_U_PLANE + (8 + (lane >> 4) * 8 + (lane & 7)) * 16;
    const uint32_t ys = sm + CV_V + warp * CV_Y_CH + (mi & 1) * 512 + ((lane >> 4) * 8 + (lane & 7)) * 16;
    auto q_sums = [&]() {
      mbar_wait_plain(bar + 8 * CB_X0, 0);
      float sum[4] = {0.f, 0.f, 0.f, 0.f}, lo[4] = {0.f, 0.f, 0.f, 0.f}, hi[4] = {0.f, 0.f, 0.f, 0.f};
#pragma unroll
      for (int x = 0; x < 8; x++) {
        uint32_t a0, a1, a2, a3;
        ldsm_x4(sm + CV_X + (lane & 15) * CV_XROW + warp * 256 + (lane >> 4) * 16 + x * 32, a0, a1, a2, a3);
        mma16816(sum, a0, a1, a2, a3, 0x3f803f80u, 0x3f803f80u);
        mma16816(lo, a0, a1, a2, a3, a0, a2);
        mma16816(hi, a0, a1, a2, a3, a1, a3);
      }
      if (qd == (g >> 1)) {
        asm volatile("st.shared.v2.f32 [%0], {%1,%2};" :: "r"(sm + CV_QS + warp * 128 + g * 8), "f"(sum[0]), "f"((g & 1) ? lo[1] : lo[0]) : "memory");
        asm volatile("st.shared.v2.f32 [%0], {%1,%2};" :: "r"(sm + CV_QS + warp * 128 + g * 8 + 64), "f"(sum[2]), "f"((g & 1) ? hi[3] : hi[2]) : "memory");
      }
      __syncwarp();
      mbar_arrive_if(bar + 8 * CB_QS, lane == 0);
    };
    if (tid == 0) STAMP(49);
    float acc[16][4];
#pragma unroll
    for (int j = 0; j < 16; j++) { acc[j][0] = acc[j][1] = acc[j][2] = acc[j][3] = 0.f; }
    conv_phase<0, 4, 0, 8, 0, 16>(acc, abase, bbase, hidden_zero(ub));
    stage_y<0, 4>(acc, ys, 0);
    if (tid == 0) STAMP(57);
    mbar_wait_plain(bar + 8 * CB_K1, 0);
    mbar_wait_plain(bar + 8 * CB_O1, 0);
    conv_phase<0, 4, 8, 16, 0, 16>(acc, abase, bbase, hidden_zero(ub));
    if (tid == 0) STAMP(58);
    q_sums();
    mbar_wait_plain(bar + 8 * CB_U1, 0);
    conv_phase<4, CV_JS - 4, 0, CV_JS - 4, 0, CV_JS>(acc, abase, bbase, hidden_zero(ub));
    stage_y<4, CV_JS>(acc, ys, bar + 8 * CB_Y1);
    if (tid == 0) STAMP(59);
    mbar_wait_plain(bar + 8 * CB_U2, 0);
    if (tid == 0) BSTAMP(55, kt);
    conv_phase<4, 12, 0, 12, CV_JS, 16>(acc, abase, bbase, hidden_zero(ub));
    stage_y<CV_JS, 16>(acc, ys, bar + 8 * CB_Y2);
    if (tid == 0) STAMP(50);
    if (tid == 32) STAMP(62);
  }
  {
    const int ch = lane & 7;
    const uint32_t ya = sm + CV_V + ch * CV_Y_CH + (mi & 1) * 512 + (mi >> 1) * 16;
    const uint32_t ua = ub + ch * CV_U_CH + (mi & 1) * CV_U_PLANE + (8 + (mi >> 1)) * 16;
    const uint32_t qa = sm + CV_K + 128 + (16 * (mi >> 1) + 15 - 8 * (mi & 1) - ch) * 16;
    char* xo = reinterpret_cast<char*>(g_x3[0]) + (size_t)b * CB_BYTES + (15 - g) * 16 + qd * 4;
    const uint32_t yo = sm + CV_K + 128 + ((7 - g) * 4 + qd) * 8;
    int budget = SPIN_LIMIT;
    uint32_t ep = 0;
    if (warp > 9) {
      if (tid == 320) STAMP(53);
      ep = ld_relaxed(&g_epoch);
#pragma unroll 1
      while (ld_relaxed(&g_qcnt) - 128 * ep < 128 && --budget > 0) __nanosleep(100);
      if (tid == 320) STAMP(43);
    }
#pragma unroll 1
    for (int part = warp < 8; part < 2; part++) {
      if (warp == 9 && part) break;
      if (warp > 9) {
        uint4 v[8];
#pragma unroll 1
        do {
          uint32_t ok = 1;
#pragma unroll
          for (int y = 0; y < 8; y++) {
            asm volatile("ld.relaxed.gpu.global.v4.u32 {%0,%1,%2,%3}, [%4];" : "=r"(v[y].x), "=r"(v[y].y), "=r"(v[y].z), "=r"(v[y].w)
                         : "l"(g_qstat + 1024 * part + 2 * (tid & 63) + 128 * y) : "memory");
            ok &= both_valid(v[y].x, v[y].z, ep);
          }
          if (__all_sync(0xffffffffu, ok)) break;
        } while (--budget > 0);
#pragma unroll
        for (int y = 0; y < 8; y++) sts128(sm + (part ? CV_ST1 : CV_ST0) + (tid & 63) * 16 + 1024 * y, make_uint4(v[y].x | 1u, v[y].y, v[y].z | 1u, v[y].w));
        __syncwarp();
        mbar_arrive_if(bar + 8 * (CB_ST0 + part), lane == 0);
      }
      mbar_wait_plain(bar + 8 * (CB_ST0 + part), 0);
      mbar_wait_plain(bar + 8 * (CB_QC0 + part), 0);
      if (tid == 288) STAMP(63);
      mbar_wait_plain(bar + 8 * (CB_Y1 + part), 0);
      const uint32_t sa = sm + (part ? CV_ST1 - 8192 : CV_ST0) + (15 - g) * 8;
#pragma unroll 1
      for (int u = part ? 4 * CV_JS + warp - 2 * (warp > 8) : warp - 9; u < (part ? 64 : 4 * CV_JS); u += part ? 10 : 3) {
        uint32_t y[4], uu[4], qq[4];
        ldsm_x4_t(ya + ((u >> 4) * (CV_VQ - 512) + u * 32), y[0], y[1], y[2], y[3]);
        ldsm_x4_t(ua + u * 32, uu[0], uu[1], uu[2], uu[3]);
        ldsm_x4(qa + u * 512, qq[0], qq[1], qq[2], qq[3]);
#pragma unroll
        for (int i = 0; i < 4; i++) {
          const int off = 16 * (i >> 1) - 8 * (i & 1);
          const float2 s = lds_f2(sa + (u * 256 + off * 8));
          y[i] = badd2(y[i], bmul2(uu[i], dpair));
          stg32(xo + (uint32_t)u * 512 + off * 16, gate_pair(qq[i], y[i], __float_as_uint(s.x), __float_as_uint(s.y)));
        }
        asm volatile("st.shared.v2.u32 [%0], {%1,%2};" :: "r"(yo + u * 512), "r"(y[1]), "r"(y[0]) : "memory");
        asm volatile("st.shared.v2.u32 [%0], {%1,%2};" :: "r"(yo + u * 512 + 256), "r"(y[3]), "r"(y[2]) : "memory");
      }
      __syncwarp();
      mbar_arrive_if(bar + 8 * (part ? CB_P2 : CB_P1), lane == 0);
    }
  }
  if (warp == 9) {
    mbar_wait_plain(bar + 8 * CB_P1, 0);
    if (elect_one()) {
      STAMP(61);
      red_release(&g_xcnt[b >> 3]);
      fence_async_smem();
      bulk_store(reinterpret_cast<char*>(g_y) + (size_t)b * CB_BYTES, sm + CV_K + 128, 16384);
      bulk_commit();
      bulk_wait_all();
      mbar_arrive(bar + 8 * CB_YOUT);
    }
  }
  if (tid == 0) STAMP(51);
}

constexpr int NA = 5, A_SLOT = 68 * 128;
constexpr int SM_B = 1024;
constexpr int SM_A = SM_B + 98304;
constexpr int SM_X = SM_A + 2 * NA * A_SLOT;
constexpr int SM_CS1 = CV_END;
constexpr int SM_CS3 = SM_CS1 + 512;
static_assert(SM_X % 1024 == 0 && SM_X + 32768 <= SM_CS1 && SM_B + 2 * 16384 == CV_X && SM_A + NA * A_SLOT == CV_U, "layout");
constexpr int BAR_FULLA = 0, BAR_FULLB = 16, BAR_TURN = 24, BAR_OWN = 26;
constexpr int BAR_EMPTYA = 28, BAR_EMPTYB = BAR_EMPTYA + 18, BAR_CS = BAR_EMPTYB + 9;
constexpr int BAR_PUB = 56;
constexpr int BAR_END = 84;
constexpr int SM_RS = SM_CS3 + 1792;
constexpr int RS_G1 = 2 * 68 * 8;
constexpr int MEGA_SMEM = SM_RS + 2 * RS_G1;
static_assert(MEGA_SMEM <= 232448, "shared memory");
#define LEAD 4
#define LEAD3 2

template <int N> struct BGeo;
template <> struct BGeo<128> { static constexpr int SLOTS = 6, BYTES = 16384; };
template <> struct BGeo<256> { static constexpr int SLOTS = 3, BYTES = 32768; };
template <> struct BGeo<192> { static constexpr int SLOTS = 4, BYTES = 24576; };
__host__ __device__ constexpr int first_slot(int s) { return s == 0 || s == 2 ? 2 : 0; }
__device__ __forceinline__ bool starts_local(int l, int s) { return s == 2 || s == 1 - l; }
__device__ __forceinline__ int token_shift(int j) { return ((j >> 1) & 1 ? 1 : -1) * (1 + (j >> 2)); }

struct Ctx {
  uint32_t sm;
  uint32_t bar;
  int i, j, r;
  int bid;
  uint32_t ep;
};

struct Pipe {
  uint32_t ko, kp;
  uint32_t po;
  uint32_t a0, a1, ar;
  uint32_t b;
  uint32_t keep;
  uint32_t sh, wide;
  uint64_t ak;
  uint32_t turn;
  int budget;
  uint32_t rel;
  bool signals;
  __device__ __forceinline__ void release() const {
    asm volatile("{\n.reg .pred p;\nsetp.ne.b32 p, %1, 0;\n@p mbarrier.arrive.shared::cluster.b64 _, [%0];\n}" :: "r"(rel + po), "r"((uint32_t)signals) : "memory");
  }
  __device__ __forceinline__ void drain() { wg_wait<0>(); release(); po = 64; }
};
__device__ __forceinline__ uint32_t desc_a(const Ctx& c, int off) { return ((c.sm & 0x3FFFFu) >> 4) + 0x400000u + (off >> 4); }
__device__ __forceinline__ uint32_t desc_b(const Ctx& c, int off) { return ((c.sm & 0x3FFFFu) >> 4) + 0x2000000u + ((SM_B + off) >> 4); }

template <int N, bool PRED, bool SHIFT = false, class Extra>
__device__ __forceinline__ void gemm_step(float (&acc)[N / 2], const Ctx& c, int wg, Pipe& p, Extra&& extra) {
  using G = BGeo<N>;
  const uint32_t fa = c.bar + 8 * BAR_FULLA + 64 * wg + p.ko, fb = c.bar + 8 * BAR_FULLB + p.ko;
#pragma unroll 1
  while (true) {
    uint32_t ready;
    asm volatile("{\n.reg .pred p, q;\nmbarrier.try_wait.parity.shared::cta.b64 p, [%1], %3;\nmbarrier.try_wait.parity.shared::cta.b64 q, [%2], %3;\n"
                 "and.pred p, p, q;\nselp.b32 %0, 1, 0, p;\n}" : "=r"(ready) : "r"(fa), "r"(fb), "r"(p.kp) : "memory");
    if (ready || --p.budget <= 0) break;
  }
  wg_fence();
  uint64_t da = (8ull << 32) | (SHIFT ? p.a0 + (p.sh & 3) + p.wide : p.a0), db = (0x40000040ull << 32) | p.b;
  if constexpr (SHIFT) p.sh >>= 2;
  if constexpr (PRED) { Mma<N>::ss(acc, da, db, p.keep); p.keep = 1; } else Mma<N>::ss(acc, da, db);
#pragma unroll
  for (int kk = 1; kk < 4; kk++) {
    asm volatile("add.s64 %0, %0, %2;\nadd.s64 %1, %1, 128;" : "+l"(da), "+l"(db) : "l"(SHIFT ? p.ak : (uint64_t)128));
    Mma<N>::ss(acc, da, db);
  }
  wg_commit();
  extra();
  wg_wait<1>();
  p.release();
  p.po = p.ko;
  p.ko = (p.ko + 8) & 63;
  p.kp ^= p.ko == 0;
  p.a0 = p.a1; p.a1 = p.ar;
  p.ar = p.ar == desc_a(c, SM_A + (NA - 1) * A_SLOT) + wg * NA * (A_SLOT >> 4) ? p.ar - (NA - 1) * (A_SLOT >> 4) : p.ar + (A_SLOT >> 4);
  p.b = p.b == desc_b(c, (G::SLOTS - 1) * G::BYTES) ? desc_b(c, 0) : p.b + (G::BYTES >> 4);
}
template <int N>
__device__ __forceinline__ void gemm_begin(const Ctx& c, int wg, int wq, Pipe& p, int s, bool local) {
  if (local) {
    fence_async_smem();
    named_bar(2 + wg, 128);
    mbar_arrive_if(c.bar + 8 * BAR_FULLA + 64 * wg + 8 * (threadIdx.x & 1), (threadIdx.x & 126) == 96);
    if (wq < 2) {
      mbar_wait(c.bar + 8 * (BAR_EMPTYA + 9 * wg + 8 - NA + wq), p.kp ^ 1, p.budget);
      if (elect_one()) {
        const uint32_t peer = mapa(c.sm, c.r ^ 1), bar = peer + SM_BAR + 8 * (BAR_FULLA + 8 * wg + 2 + wq);
        mbar_expect_tx_cluster(bar, 8192);
        bulk_copy_cluster(peer + (((wq ? p.a1 : p.a0) - desc_a(c, 0)) << 4), c.sm + SM_X + (2 * wg + wq) * 8192, 8192, bar);
      }
      __syncwarp();
    }
  }
  asm volatile("{\n.reg .pred p;\nsetp.ne.b32 p, %3, 0;\nselp.b32 %2, %0, %2, p;\nselp.b32 %0, %4, %0, p;\nselp.b32 %1, %5, %1, p;\n}"
               : "+r"(p.a0), "+r"(p.a1), "+r"(p.ar) : "r"((uint32_t)local), "r"(desc_a(c, SM_X) + wg * 1024), "r"(desc_a(c, SM_X + 8192) + wg * 1024));
  p.b = desc_b(c, first_slot(s) * BGeo<N>::BYTES);
}
template <class Hook>
__device__ __forceinline__ void yield_turn(const Ctx& c, int wg, Pipe& p, Hook&& hook) {
  if (wg == 1) p.drain();
  hook();
  if (wg == 1) mbar_wait(c.bar + 8 * BAR_TURN, p.turn, p.budget);
  p.turn ^= 1;
}
__device__ __forceinline__ void pass_turn(const Ctx& c, bool now) { mbar_arrive_if(c.bar + 8 * BAR_TURN, now && threadIdx.x == 96); }
struct Nop { __device__ __forceinline__ void operator()() const {} };
template <int N, bool PRED, bool SHIFT = false, class Hook>
__device__ __forceinline__ void gemm_steps(float (&acc)[N / 2], const Ctx& c, int wg, Pipe& p, int count, Hook&& hook) {
  constexpr int lead = N == 128 ? LEAD : LEAD3;
  int m = count - lead;
#pragma unroll 1
  do { gemm_step<N, PRED, SHIFT>(acc, c, wg, p, Nop()); } while (--m > 0);
  yield_turn(c, wg, p, hook);
#pragma unroll 1
  for (int n = lead - 1; n >= 0; n--) {
    gemm_step<N, false, SHIFT>(acc, c, wg, p, Nop());
    pass_turn(c, n == 1);
  }
}

__device__ __forceinline__ void put_stat(float2* gdst, float s, float q, bool cond, uint32_t ep) {
  const float m = s * (1.f / 128), v = fmaxf(fmaf(-m, s, q), 0.f);
  asm volatile("{\n.reg .pred p;\nsetp.ne.b32 p, %3, 0;\n@p st.relaxed.gpu.global.v2.b32 [%0], {%1,%2};\n}"
               :: "l"(gdst), "r"(__float_as_uint(m)), "r"(tagged(v, ep)), "r"((uint32_t)cond) : "memory");
}
__device__ __forceinline__ void put_partial(const float (&v)[64], float2* gdst, uint32_t ep) {
  float s[4] = {v[0], v[1], v[2], v[3]}, q[4] = {v[0] * v[0], v[1] * v[1], v[2] * v[2], v[3] * v[3]};
#pragma unroll
  for (int x = 4; x < 64; x++) { s[x & 3] += v[x]; q[x & 3] = fmaf(v[x], v[x], q[x & 3]); }
  const bool odd = threadIdx.x & 1;
  const float s0 = s[0] + s[1], s1 = s[2] + s[3], q0 = q[0] + q[1], q1 = q[2] + q[3];
  float ss = (odd ? s1 : s0) + __shfl_xor_sync(0xffffffffu, odd ? s0 : s1, 1);
  float qq = (odd ? q1 : q0) + __shfl_xor_sync(0xffffffffu, odd ? q0 : q1, 1);
  ss += __shfl_xor_sync(0xffffffffu, ss, 2);
  qq += __shfl_xor_sync(0xffffffffu, qq, 2);
  put_stat(gdst + (odd ? 8 : 0), ss, qq, !(threadIdx.x & 2), ep);
}
__device__ __forceinline__ void poll_stats(const float2* src, int& budget, float2& s0, float2& s1) {
  float2 p[4];
  __nanosleep(250);
#pragma unroll 1
  while (true) {
#pragma unroll
    for (int x = 0; x < 4; x++)
      asm volatile("ld.relaxed.gpu.global.v2.f32 {%0,%1}, [%2];" : "=f"(p[x].x), "=f"(p[x].y) : "l"(src + (x >> 1) * 8 + (x & 1) * SEQ) : "memory");
    const uint32_t ok = both_valid(__float_as_uint(p[0].y), __float_as_uint(p[1].y), 0) & both_valid(__float_as_uint(p[2].y), __float_as_uint(p[3].y), 0);
    if (__all_sync(0xffffffffu, ok & 1) || --budget <= 0) break;
  }
#pragma unroll
  for (int h = 0; h < 2; h++) {
    const float2 a = p[2 * h], b = p[2 * h + 1];
    float m = a.x + b.x;
    m += __shfl_xor_sync(0xffffffffu, m, 1);
    m += __shfl_xor_sync(0xffffffffu, m, 2);
    m *= 0.125f;
    const float ea = a.x - m, eb = b.x - m;
    float t = fmaf(fmaf(ea, ea, eb * eb), 128.f, a.y + b.y);
    t += __shfl_xor_sync(0xffffffffu, t, 1);
    t += __shfl_xor_sync(0xffffffffu, t, 2);
    (h ? s1 : s0) = make_float2(m, rsqrt_fast(fmaf(t, 1.f / DM, LN_EPS)));
  }
}

__device__ __forceinline__ void emit_panel(const uint32_t* v, char* gp, uint32_t pub) {
#pragma unroll
  for (int t = 0; t < 8; t++) { stg32(gp + t * CB_BYTES, v[2 * t]); stg32(gp + t * CB_BYTES + 128, v[2 * t + 1]); }
  __syncwarp();
  mbar_arrive_if(pub, (threadIdx.x & 31) == 0);
}
template <int NT>
__device__ __forceinline__ void stage_tiles(const uint32_t* v, uint32_t sp) {
#pragma unroll
  for (int t = 0; t < NT; t += 2) stsm_x4(sp + t * 1024, v[2 * t], v[2 * t + 1], v[2 * t + 2], v[2 * t + 3]);
}

__device__ __forceinline__ float late_zero(uint32_t addr) {
  float z; asm volatile("ld.volatile.shared.f32 %0, [%1];" : "=f"(z) : "r"(addr) : "memory"); return z;
}

template <int NT>
__device__ __forceinline__ void fold_tiles(uint32_t* v, const float* acc, const float2* cs_ptr, float2 st0, float2 st1) {
  const float n0 = -st0.x * st0.y, n1 = -st1.x * st1.y;
#pragma unroll
  for (int tile = 0; tile < NT; tile++) {
    const float2 cs = cs_ptr[tile * 4];
    float a = fmaf(acc[4 * tile + 0], st0.y, n0 * cs.x), b = fmaf(acc[4 * tile + 1], st0.y, n0 * cs.y);
    float cc = fmaf(acc[4 * tile + 2], st1.y, n1 * cs.x), d = fmaf(acc[4 * tile + 3], st1.y, n1 * cs.y);
    v[2 * tile] = pack_bf16(gelu_from_half(a), gelu_from_half(b));
    v[2 * tile + 1] = pack_bf16(gelu_from_half(cc), gelu_from_half(d));
  }
}

__device__ __forceinline__ void move_reg(uint32_t& d, uint32_t s) { asm volatile("mov.b32 %0, %1;" : "=r"(d) : "r"(s)); }
__device__ __forceinline__ void move_reg(float& d, float s) { asm volatile("mov.f32 %0, %1;" : "=f"(d) : "f"(s)); }
template <int CH, int LO, int HI, class T, int NR>
__device__ __forceinline__ void pick_group(T (&held)[NR], int idx) {
  if constexpr (HI - LO == 1) {
#pragma unroll
    for (int x = 0; x < CH; x++) move_reg(held[x], held[CH * LO + x]);
  } else {
    constexpr int MID = (LO + HI) / 2;
    if (idx < MID) pick_group<CH, LO, MID>(held, idx); else pick_group<CH, MID, HI>(held, idx);
  }
}
template <int CH>
__device__ __forceinline__ void gelu_chunk(const uint32_t* t, char* gp) {
#pragma unroll
  for (int x = 0; x < CH; x++) stg32(gp + (x >> 1) * CB_BYTES + (x & 1) * 128, gelu_pair_f16(t[x]));
}

#define REG_CONS 216
#define REG_PROD 72
__global__ void __cluster_dims__(2, 1, 1) __launch_bounds__(384, 1)
fused_kernel(const __grid_constant__ Params maps) {
  extern __shared__ __align__(1024) char smem[];
  const int tid = threadIdx.x, lane = tid & 31;
  const int warp = __shfl_sync(0xffffffffu, tid >> 5, 0), wg = warp >> 2;
  if (tid == 0) STAMP(48);
  const uint32_t sm0 = opaque(smem_u32(smem));
  if (elect_one()) {
    if (warp == 8) {
#pragma unroll
      for (int x = 0; x < CB_Q1; x++) mbar_init(sm0 + CV_BAR + 8 * x, 1);
      asm volatile("fence.mbarrier_init.release.cluster;" ::: "memory");
      load_k(maps, sm0, 0);
#pragma unroll
      for (int y = 0; y < 2; y++) {
        mbar_expect_tx(sm0 + CV_BAR + 8 * (CB_QA + y), 8192);
        load_kv(maps, sm0, y, CB_QA + y);
      }
#pragma unroll
      for (int x = CB_Q1; x < CB_ST0; x++) mbar_init(sm0 + CV_BAR + 8 * x, x < CB_QS ? 1 : x == CB_QS ? 8 : 3);
    } else if (warp == 9) {
#pragma unroll
      for (int x = CB_ST0; x < CB_COUNT; x++) mbar_init(sm0 + CV_BAR + 8 * x, x < CB_O1 ? 2 : x < CB_Y1 ? 3 : x < CB_P2 ? 8 : x == CB_P2 ? 10 : x == CB_YOUT ? 5 : x < CB_STAT ? 2 : 1);
    } else if (warp < 2) {
      asm volatile("prefetch.tensormap [%0];" :: "l"(&maps.m[M_K + warp]) : "memory");
    }
#pragma unroll
    for (int x = 0; x < 7; x++) mbar_init(sm0 + SM_BAR + 56 * warp + 8 * x, 1 << wg);
    asm volatile("fence.mbarrier_init.release.cluster;" ::: "memory");
    if (warp == 11) {
      sts32(sm0 + SM_ZERO, 0);
      const uint32_t t = tpc_id();
      if (t < 8 || (t >= 62 && t < 66)) asm volatile("{\n.reg .b32 c;\nmov.u32 c, %%clock;\nst.relaxed.gpu.global.u32 [%0], c;\n}" :: "l"(g_role + (t < 8 ? t + 4 : t - 50)) : "memory");
    }
  }
  static_assert(BAR_END == 84, "start-up work of 12 warps");
  __syncwarp();
  if (warp != 8) asm volatile("barrier.cluster.arrive.relaxed.aligned;" ::: "memory");
  conv_part(maps, sm0, warp);
  __syncwarp();
  asm volatile("barrier.cluster.wait.acquire.aligned;" ::: "memory");
  Ctx c;
  c.sm = sm0;
  c.bar = c.sm + SM_BAR;
  c.r = blockIdx.x & 1;
  {
    uint32_t role;
    asm volatile("ld.shared::cluster.u32 %0, [%1];" : "=r"(role) : "r"(mapa(sm0 + SM_ROLE, 0)) : "memory");
    role = __shfl_sync(0xffffffffu, role, 0);
    c.i = role >> 2; c.j = (role & 3) * 2 + c.r;
    c.bid = c.i * 8 + c.j;
    asm volatile("ld.shared.u32 %0, [%1];" : "=r"(c.ep) : "r"(c.sm + SM_EPOCH) : "memory");
  }

  if (tid == 0) MSTAMP(45);
  if (wg == 2) {
    reg_dealloc<REG_PROD>();
    int budget = SPIN_LIMIT;
    if (warp == 8) {
      const int hh = 16 * c.r + c.i;
      const uint32_t full0 = c.bar + 8 * (BAR_FULLA + c.r * 8), empty0 = c.bar + 8 * (BAR_EMPTYA + c.r * 9), full_peer = mapa(full0, c.r ^ 1);
      const uint32_t ring0 = c.sm + SM_A + c.r * NA * A_SLOT;
      const int nb = hh + (lane & 8 ? (lane & 2) - 1 : 0);
      const uint32_t* lf = g_flag + ((nb >= 0 && nb < 32 ? nb : hh) * 8 + (lane & 7)) * FS;
      const uint32_t* xf = g_xcnt + (hh + ((c.j >> 1) & 1) >= 16 ? 16 : 0) + (lane & 15);
      const uint32_t cb = c.sm + CV_BAR;
      if (lane == 0) mbar_arrive(cb + 8 * CB_XFREE);
      mbar_wait(cb + 8 * CB_Y2, 0, budget);
      if (lane == 0) STAMP(60);
      mbar_wait(cb + 8 * CB_P1, 0, budget);
      fence_async_smem();
      if (lane < 2) mbar_arrive_cluster(mapa(cb + 8 * CB_EARLY, lane));
      int seen = ld_relaxed(xf) - 8 * c.ep;
      mbar_wait(cb + 8 * (CB_EARLY + c.r), 0, budget);
      fence_async_global();
      if (lane == 0) MSTAMP(46);
      uint32_t slot = ring0;
      int k = 0;
#pragma unroll 1
      for (int ph = 0; ph < 10; ph++) {
        const int l = ph >= 5, s = ph - 5 * l;
        const CUtensorMap* m = &maps.m[s == 0 ? M_X3S + l : s == 1 ? M_H + l : s == 4 ? M_HID : M_X1];
        const uint32_t bytes = s == l ? A_SLOT : 8192;
        const bool local = starts_local(l, s);
        const int np = ph == 0 ? 1 : s == 4 ? 7 : 2, cnt = ph == 0 ? 16 : local ? 6 : 8, e0 = ph == 0 ? 2 * (c.j & 6) : (c.j & 6) + (local ? 2 : 0);
        const int need0 = ph == 0 ? 8 : 13 * l + (s == 0 ? 1 : s == 1 ? 3 : s == 4 ? 7 : 5);
        const uint32_t up = ph == 0 ? (c.j & 2 ? 0u : 0xffffu) : ph == 6 ? 0x33u : 0u;
        const uint32_t* fp = ph == 0 ? xf : lf;
        const uint32_t base = ph == 0 ? 8 * c.ep : 32 * c.ep;
        const bool polls = lane < (s == l ? 16 : 8);
        if (ph == 1) seen = 0;
        if (local) {
          k += 4;
          slot += slot >= ring0 + (NA - 2) * A_SLOT ? (2 - NA) * A_SLOT : 2 * A_SLOT;
        }
#pragma unroll 1
        for (int p = 0; p < np; p++) {
          uint32_t ready = __ballot_sync(0xffffffffu, seen >= need0 + p);
          if (ph == 6) ready &= ready >> 8;
#pragma unroll 1
          for (int x = 0; x < cnt; x++) {
            const int e = (e0 + x) & (ph == 0 ? 15 : 7);
            const uint32_t off = 8 * (k & 7);
            mbar_wait(empty0 + 8 * ((k - NA) & 7), ((k - NA) >> 3) & 1, budget);
            if (elect_one()) {
              mbar_expect_tx(full0 + off, bytes);
              mbar_expect_tx_cluster(full_peer + off, bytes);
            }
            if (!((ready >> e) & 1)) {
#pragma unroll 1
              do {
                if (polls) seen = ld_relaxed(fp) - base;
                ready = __ballot_sync(0xffffffffu, seen >= need0 + p);
                if (ph == 6) ready &= ready >> 8;
              } while (!((ready >> e) & 1) && --budget > 0);
              fence_async_global();
            }
            if (elect_one()) tma_2d_mc(slot, m, full0 + off, 128 * hh - 8 * ((up >> e) & 1), (np * e + p) * 8, (uint16_t)3);
            slot += slot == ring0 + (NA - 1) * A_SLOT ? (1 - NA) * A_SLOT : A_SLOT;
            k++;
          }
        }
      }
    } else if (warp == 9) {
      const uint32_t e8 = __funnelshift_r(0x76543210u, 0x76543210u, 4 * (c.j & 6));
      int k = 0;
#pragma unroll 1
      for (int ph = 0; ph < 10; ph++) {
        const int l = ph >= 5, s = ph - 5 * l;
        const uint32_t bytes = s == 2 ? 32768 : s == 3 ? 24576 : 16384, slots = s == 2 ? 3 : s == 3 ? 4 : 6;
        uint32_t dist = s == 2 ? 0x33333345u : s == 3 ? 0x44444333u : s == 4 ? 0x66655544u : 0x66666666u;
        const CUtensorMap* m = &maps.m[M_W1 + s];
        const int np = s == 4 ? 7 : 2;
        const int panel0 = s == 2 ? 7 * c.j : s == 3 ? 7 * c.j + 4 : 2 * c.j;
        const bool local = starts_local(l, s), direct = local || ph == 0;
        uint32_t slot = c.sm + SM_B + first_slot(s) * bytes;
#pragma unroll 1
        for (int o = 0; o < np; o++) {
          uint32_t tab = e8;
          if (local) tab = o ? (e8 >> 24 << 1) | ((e8 << 1) & 0xffffff00u) | 0x11111100u : (0x3210u ^ (c.j * 0x2222u)) | (e8 >> 8 << 17);
          if (ph == 0) tab = (c.j & 2 ? 0xba987654u : 0x76543210u) ^ (((c.j >> 2) ^ o) * 0x88888888u);
          const int mul = direct ? 64 : 64 * np, add = direct ? 0 : 64 * o;
#pragma unroll 1
          for (uint32_t bar = c.bar + 8 * BAR_FULLB; bar < c.bar + 8 * BAR_FULLB + 64; bar += 8) {
            const int last = k - (dist & 15), row = (tab & 15) * mul + add;
            if (last < 0) {
              mbar_wait(c.sm + CV_BAR + 8 * (k < 2 ? CB_XFREE : k < 5 ? CB_EARLY : CB_YOUT), 0, budget);
              fence_async_smem();
            }
            mbar_wait(c.bar + 8 * (BAR_EMPTYB + (last & 7)), (last >> 3) & 1, budget);
            if (elect_one()) {
              mbar_expect_tx(bar, bytes);
              tma_3d(slot, m, bar, 0, row, panel0);
            }
            slot += bytes;
            if (slot == c.sm + SM_B + 98304) slot = c.sm + SM_B;
            dist = __funnelshift_r(dist, slots, 4);
            tab >>= 4;
            k++;
          }
        }
      }
    } else {
      const int w = warp - 10;
      const int row0 = 64 * (16 * w + c.i);
      mbar_wait(c.sm + CV_BAR + 8 * CB_P2, 0, budget);
      if (w == 0) {
        fence_async_smem();
        if (lane < 2) mbar_arrive_cluster(mapa(c.sm + CV_BAR + 8 * CB_LATE, lane));
      } else if (elect_one()) {
        red_release(&g_xcnt[16 + (blockIdx.x >> 3)]);
        mbar_arrive(c.bar + 8 * BAR_REL);
        MSTAMP(44);
      }
      __syncwarp();
      uint32_t* my_flag = g_flag + ((16 * w + c.i) * 8 + c.j) * FS;
#pragma unroll 1
      for (int pc = 1; pc < 26; pc++) {
        const int l = pc >= 13, u = pc - 13 * l;
        if (pc > 1) {
          if (pc == 8) { reinterpret_cast<uint4*>(&g_part[2][c.j][row0])[lane] = make_uint4(0, 0, 0, 0); __syncwarp(); }
          mbar_wait(c.bar + 8 * (BAR_PUB + 13 * w + u), u < 2 ? 0 : l, budget);
          st_release(my_flag, 32 * c.ep + pc + 1);
        }
        float2* part = &g_part[3 * l + (u == 5)][0][0];
#pragma unroll 1
        for (uint32_t jobs = pc == 1 ? 0x453u : u == 5 ? 0x421u : u == 1 ? 4u : 0u; jobs; jobs >>= 4) {
          const int job = jobs & 15;
          if (job < 3) {
            const int r = 32 * (job - 1) + lane;
            float s0 = 0.f, s1 = 0.f, q0 = 0.f, q1 = 0.f;
#pragma unroll 2
            for (int x = 0; x < 16; x++) {
              uint32_t v[4];
              asm volatile("ld.shared.v4.u32 {%0,%1,%2,%3}, [%4];" : "=r"(v[0]), "=r"(v[1]), "=r"(v[2]), "=r"(v[3])
                           : "r"(c.sm + SM_X + w * 16384 + x * 1024 + r * 16) : "memory");
#pragma unroll
              for (int y = 0; y < 4; y++) {
                const float a = bf_lo(v[y]), b = bf_hi(v[y]);
                s0 += a; s1 += b; q0 = fmaf(a, a, q0); q1 = fmaf(b, b, q1);
              }
            }
            put_stat(part + c.j * SEQ + row0 + r, s0 + s1, q0 + q1, true, c.ep);
          } else if (job == 3) {
            if (w == 1) {
              mbar_wait(c.sm + CV_BAR + 8 * CB_YOUT, 0, budget);
              mbar_wait(c.sm + CV_BAR + 8 * CB_EARLY, 0, budget);
              if (lane == 0) red_release(&g_xcnt[32 + (blockIdx.x >> 3)]);
              __syncwarp();
            }
            uint32_t xseen;
#pragma unroll 1
            do {
              asm volatile("ld.acquire.gpu.global.u32 %0, [%1];" : "=r"(xseen) : "l"(g_xcnt + 32 + (lane & 15)) : "memory");
            } while (!__all_sync(0xffffffffu, (int)(xseen - 8 * c.ep) >= 8) && --budget > 0);
            if (w == 0) {
              float4 s = make_float4(0.f, 0.f, 0.f, 0.f);
#pragma unroll
              for (int x = 0; x < 4; x++) {
                const float4 v = __ldcg(reinterpret_cast<const float4*>(&g_cs1[x][c.j * 128]) + lane);
                s.x += v.x; s.y += v.y; s.z += v.z; s.w += v.w;
              }
              reinterpret_cast<float4*>(smem + SM_CS1)[lane] = s;
            } else {
#pragma unroll
              for (int x = 0; x < 4; x++) {
                const int y = min(32 * x + lane, 111);
                const float4 v = __ldcg(reinterpret_cast<const float4*>(g_cs3 + c.j * 448) + y);
                if (x < 2) {
                  uint32_t* d = reinterpret_cast<uint32_t*>(smem + SM_CS3) + (y >> 2) * 8 + (y & 1) * 4 + ((y >> 1) & 1);
                  d[0] = pack_f16(v.x, v.y); d[2] = pack_f16(v.z, v.w);
                } else {
                  reinterpret_cast<float4*>(smem + SM_CS3)[y] = v;
                }
              }
            }
            __syncwarp();
            if (lane == 0) mbar_arrive(c.bar + 8 * BAR_CS);
            if (c.bid == 0 && w == 0 && lane <= 16) *(lane < 16 ? g_role + lane : &g_epoch) = lane < 12 ? 0 : lane < 16 ? 0x80000000u : c.ep + 1;
          } else {
            const int r = job == 4 ? 2 * lane : token_shift(c.j) > 0 ? 64 : -2;
            const float2* src = part + min(max(row0 + r, 0), SEQ - 2);
            float4 v[8];
#pragma unroll 1
            do {
              uint32_t ok = 1;
#pragma unroll
              for (int x = 0; x < 8; x++) {
                asm volatile("ld.relaxed.gpu.global.v4.f32 {%0,%1,%2,%3}, [%4];" : "=f"(v[x].x), "=f"(v[x].y), "=f"(v[x].z), "=f"(v[x].w) : "l"(src + x * SEQ) : "memory");
                ok &= both_valid(__float_as_uint(v[x].y), __float_as_uint(v[x].w), c.ep);
              }
              if (__all_sync(0xffffffffu, ok)) break;
            } while (--budget > 0);
            float ma = 0.f, mb = 0.f, ta = 0.f, tb = 0.f;
#pragma unroll
            for (int x = 0; x < 8; x++) { ma += v[x].x; mb += v[x].z; }
            ma *= 0.125f; mb *= 0.125f;
#pragma unroll
            for (int x = 0; x < 8; x++) {
              const float ea = v[x].x - ma, eb = v[x].z - mb;
              ta += fmaf(128.f * ea, ea, __uint_as_float(__float_as_uint(v[x].y) | 1u));
              tb += fmaf(128.f * eb, eb, __uint_as_float(__float_as_uint(v[x].w) | 1u));
            }
            ta *= 1.f / DM; tb *= 1.f / DM;
            const float ra = rsqrt_fast(ta + LN_EPS), rb = rsqrt_fast(tb + LN_EPS);
            *reinterpret_cast<float4*>(smem + SM_RS + (68 * w + 2 + r) * 8) = make_float4(ma, ra, mb, rb);
            const float in = (uint32_t)(row0 + r) < SEQ ? 0.5f : 0.f;
            *reinterpret_cast<float4*>(smem + SM_RS + RS_G1 + (68 * w + 2 + r) * 8) =
                make_float4(ma, in * ra * rsqrt_fast(fmaf(ta * ra, ra, LN_EPS)), mb, in * rb * rsqrt_fast(fmaf(tb * rb, rb, LN_EPS)));
            __syncwarp();
            if (job == 4 && lane == 0) mbar_arrive(c.sm + CV_BAR + 8 * (CB_STAT + w));
          }
        }
        if (pc == 6) {
          if (elect_one()) {
            const uint32_t bar = c.bar + 8 * (BAR_OWN + w);
            fence_async_global();
            fence_async_smem();
            mbar_expect_tx(bar, 16384);
            tma_2d(c.sm + SM_X + w * 16384, &maps.m[M_Y], bar, 2 * row0, 16 * c.j);
            tma_2d(c.sm + SM_X + w * 16384 + 8192, &maps.m[M_Y], bar, 2 * row0, 16 * c.j + 8);
          }
          __syncwarp();
        }
      }
    }
    cluster_exit_barrier();
  } else {
    reg_alloc<REG_CONS>();
#define WSTAMP(idx) do {} while (0)
    const int t = tid & 127, g = lane >> 2, qd = lane & 3;
    const int wrow = 64 * (16 * wg + c.i) + (t >> 5) * 16, row = wrow + g;
    const uint32_t frag = row * 16 + qd * 4 + c.j * 16 * CB_BYTES;
    const uint32_t stage = c.sm + SM_X + wg * 16384 + (lane >> 4) * 1024 + ((t >> 5) * 16 + (lane & 15)) * 16;
    const uint32_t pub = c.bar + 8 * (BAR_PUB + 13 * wg);
    const uint32_t rstat = c.sm + SM_RS + (68 * wg + 2 + (t >> 5) * 16 + g) * 8;
    Pipe p;
    p.ko = 0; p.kp = 0; p.po = 64; p.turn = 0; p.budget = SPIN_LIMIT;
    p.a0 = desc_a(c, SM_A) + wg * NA * (A_SLOT >> 4); p.a1 = p.a0 + (A_SLOT >> 4); p.ar = p.a1 + (A_SLOT >> 4);
    p.signals = t == 0 || t == 32 || t == 64;
    p.rel = mapa(c.bar + 8 * (t == 64 ? BAR_EMPTYB : BAR_EMPTYA + wg * 9), t == 32 ? c.r ^ 1 : c.r);
    auto fence_sched = [&]() { mbar_wait(c.bar + 8 * BAR_CS, 0, p.budget); };
    uint32_t x3[32];
    float acc[64];
#pragma unroll
    for (int x = 0; x < 64; x++) acc[x] = 0.f;
    pin(acc);
    const uint32_t own = opaque(c.sm + SM_A + (wg * NA + 2 * c.r) * A_SLOT + (lane >> 4) * 1088 + ((c.j & 2 ? 0 : 4) + (t >> 5) * 16 + (lane & 15)) * 16);
    WSTAMP(0);
    if (wg == 1) {
      mbar_wait(c.bar + 8 * BAR_REL, 0, p.budget);
#pragma unroll 2
      for (int x = 0; x < 8; x++)
        reinterpret_cast<uint4*>(g_y)[blockIdx.x * 2048 + 1024 + x * 128 + t] = reinterpret_cast<const uint4*>(smem + CV_K + 128 + 16384)[x * 128 + t];
      __syncwarp();
      mbar_arrive_if(c.sm + CV_BAR + 8 * CB_YOUT, lane == 0);
    }
    {
      mbar_wait(c.bar + 8 * (BAR_FULLA + 8 * wg + 2 * c.r), 0, p.budget);
      mbar_wait(c.bar + 8 * (BAR_FULLA + 8 * wg + 2 * c.r + 1), 0, p.budget);
#pragma unroll
      for (int x = 0; x < 32; x += 4) ldsm_x4(own + x * 544, x3[x], x3[x + 1], x3[x + 2], x3[x + 3]);
    }
    const uint32_t sh_g1 = opaque((token_shift(c.j) & 3) * 0x55555555u), sh_g2 = opaque(__funnelshift_r(0xaa5faa5fu, 0xaa5faa5fu, 2 * (c.j & 6)));
    const uint64_t ak0 = 128 + ((uint64_t)__shfl_sync(0xffffffffu, hidden_zero(c.sm + SM_ZERO), 0) << 32);
#pragma unroll 1
    for (int ph = 0; ph < 6; ph++) {
      const int l = ph >= 3, s = ph - 3 * l;
      p.keep = s;
      p.wide = s == l ? 4 << 16 : 0;
      p.ak = ak0 + (s == l ? 8 : 0);
      p.sh = s == l ? (l ? sh_g2 : sh_g1) : 0;
      if (s < 2) {
        gemm_begin<128>(c, wg, warp & 3, p, s, s != l);
        if (s == 0) {
          float sum[2][4] = {}, lo[2][4] = {}, hi[2][4] = {};
#pragma unroll
          for (int x = 0; x < 32; x += 4) {
            mma16816(sum[x >> 4], x3[x], x3[x + 1], x3[x + 2], x3[x + 3], 0x3f803f80u, 0x3f803f80u);
            mma16816(lo[x >> 4], x3[x], x3[x + 1], x3[x + 2], x3[x + 3], x3[x], x3[x + 2]);
            mma16816(hi[x >> 4], x3[x], x3[x + 1], x3[x + 2], x3[x + 3], x3[x + 1], x3[x + 3]);
          }
          put_stat(&g_part[3 * l][c.j][row], sum[0][0] + sum[1][0], (g & 1) ? lo[0][1] + lo[1][1] : lo[0][0] + lo[1][0], qd == (g >> 1), c.ep);
          put_stat(&g_part[3 * l][c.j][row + 8], sum[0][2] + sum[1][2], (g & 1) ? hi[0][3] + hi[1][3] : hi[0][2] + hi[1][2], qd == (g >> 1), c.ep);
          WSTAMP(1 + 16 * l);
        }
      } else {
        char* hp = reinterpret_cast<char*>(g_hid) + frag + c.j * 40 * CB_BYTES;
        uint32_t held[64];
        float acc3[128];
        gemm_step<256, true>(acc3, c, wg, p, Nop());
        float2 s0 = make_float2(0.f, 0.f), s1 = s0;
        gemm_steps<256, false>(acc3, c, wg, p, 15, [&]() {
          mbar_wait(c.sm + CV_BAR + 8 * (CB_STAT + wg), 1, p.budget);
          s0 = lds_f2(rstat); s1 = lds_f2(rstat + 64);
          s0.y *= 0.5f; s1.y *= 0.5f;
        });
        p.drain();
        WSTAMP(6 + 16 * l);
#pragma unroll
        for (int x = 0; x < 64; x++) held[x] = pack_f16(acc3[2 * x] * ((x & 1) ? s1.y : s0.y), acc3[2 * x + 1] * ((x & 1) ? s1.y : s0.y));
        const uint32_t n0 = pack_f16(-s0.x * s0.y, -s0.x * s0.y), n1 = pack_f16(-s1.x * s1.y, -s1.x * s1.y);
        float accb[96];
#pragma unroll
        for (int x = 0; x < 24; x++) {
          const float2 cs = (reinterpret_cast<const float2*>(smem + SM_CS3 + 1024) + qd)[4 * x];
          accb[4 * x] = -s0.x * cs.x; accb[4 * x + 1] = -s0.x * cs.y; accb[4 * x + 2] = -s1.x * cs.x; accb[4 * x + 3] = -s1.x * cs.y;
        }
        pin(accb);
        WSTAMP(7 + 16 * l);
        gemm_begin<192>(c, wg, warp & 3, p, 3, false);
#pragma unroll 1
        for (int pn = 0; pn < 4; pn++) {
#pragma unroll
          for (int u = 0; u < 4; u++)
            gemm_step<192, false>(accb, c, wg, p, [&]() {
              const uint2 cs = reinterpret_cast<const uint2*>(smem + SM_CS3)[16 * pn + 4 * u + qd];
              const uint32_t h[4] = {hfma2(cs.x, n0, held[4 * u]), hfma2(cs.x, n1, held[4 * u + 1]), hfma2(cs.y, n0, held[4 * u + 2]), hfma2(cs.y, n1, held[4 * u + 3])};
              gelu_chunk<4>(h, hp + 2 * u * CB_BYTES);
            });
          hp += 8 * CB_BYTES;
          __syncwarp();
          mbar_arrive_if(pub + 8 * (6 + pn), lane == 0);
          if (pn < 3) pick_group<16, 1, 4>(held, pn + 1);
        }
        WSTAMP(8 + 16 * l);
#pragma unroll
        for (int x = 0; x < 32; x++) { acc[2 * x] = bf_lo(x3[x]); acc[2 * x + 1] = bf_hi(x3[x]); }
        pin(acc);
        WSTAMP(9 + 16 * l);
        gemm_begin<128>(c, wg, warp & 3, p, 4, false);
        gemm_step<128, false>(acc, c, wg, p, Nop());
        pin(accb);
#pragma unroll 1
        for (int hpn = 0; hpn < 6; hpn++) {
#pragma unroll
          for (int u = 0; u < 4; u++)
            gemm_step<128, false>(acc, c, wg, p, [&]() {
              const uint32_t h[2] = {pack_f16(accb[4 * u] * s0.y, accb[4 * u + 1] * s0.y), pack_f16(accb[4 * u + 2] * s1.y, accb[4 * u + 3] * s1.y)};
              gelu_chunk<2>(h, hp + u * CB_BYTES);
            });
          hp += 4 * CB_BYTES;
          __syncwarp();
          mbar_arrive_if(pub + 8 * (10 + (hpn >> 1)), (hpn & 1) && lane == 0);
          if (hpn < 5) pick_group<16, 1, 6>(accb, hpn + 1);
        }
        WSTAMP(12 + 16 * l);
      }
      gemm_steps<128, true, true>(acc, c, wg, p, s == 2 ? 31 : 16, Nop());
      const uint32_t z = hidden_zero(c.sm + SM_ZERO), stg = stage + z;
      char* gp = reinterpret_cast<char*>(s == 0 ? g_h : s == 1 ? g_x1 : g_x3[1]) + (frag + z);
      float2 s0, s1;
      if (s == 0) {
        mbar_wait(c.sm + CV_BAR + 8 * (CB_STAT + wg), 0, p.budget);
        const uint32_t ra = rstat + RS_G1 + (l == 0 ? 8 * token_shift(c.j) : 0);
        s0 = lds_f2(ra); s1 = lds_f2(ra + 64);
        fence_sched();
        p.drain();
        WSTAMP(2 + 16 * l);
#pragma unroll
        for (int pn = 0; pn < 2; pn++) {
          uint32_t v[16];
          if (pn == 0) {
            fold_tiles<4>(v, acc, reinterpret_cast<const float2*>(smem + SM_CS1) + qd, s0, s1);
#pragma unroll
            for (int x = 0; x < 8; x++) stg32(gp + (x >> 1) * CB_BYTES + (x & 1) * 128, v[x]);
            fence_sched();
            fold_tiles<4>(v + 8, acc + 16, reinterpret_cast<const float2*>(smem + SM_CS1) + qd + 16, s0, s1);
#pragma unroll
            for (int x = 8; x < 16; x++) stg32(gp + (x >> 1) * CB_BYTES + (x & 1) * 128, v[x]);
            __syncwarp();
            mbar_arrive_if(pub + 8 * 2, lane == 0);
          } else {
            fold_tiles<8>(v, acc + 32, reinterpret_cast<const float2*>(smem + SM_CS1) + qd + 32, s0, s1);
            emit_panel(v, gp + 8 * CB_BYTES, pub + 8 * 3);
          }
          if (l == 0) stage_tiles<8>(v, stg + pn * 8192);
        }
        s0 = lds_f2(rstat); s1 = lds_f2(rstat + 64);
        const float nb0 = -s0.x * s0.y, nb1 = -s1.x * s1.y;
#pragma unroll
        for (int x = 0; x < 32; x++) {
          acc[2 * x] = fmaf(bf_lo(x3[x]), (x & 1) ? s1.y : s0.y, (x & 1) ? nb1 : nb0);
          acc[2 * x + 1] = fmaf(bf_hi(x3[x]), (x & 1) ? s1.y : s0.y, (x & 1) ? nb1 : nb0);
        }
        WSTAMP(3 + 16 * l);
      } else if (s == 1) {
        fence_sched();
        p.drain();
        WSTAMP(4 + 16 * l);
        uint32_t v[32];
#pragma unroll
        for (int x = 0; x < 32; x++) v[x] = pack_bf16(acc[2 * x], acc[2 * x + 1]);
        emit_panel(v, gp, pub + 8 * 4);
        stage_tiles<16>(v, stg);
        gemm_begin<256>(c, wg, warp & 3, p, 2, true);
        emit_panel(v + 16, gp + 8 * CB_BYTES, pub + 8 * 5);
#pragma unroll
        for (int x = 0; x < 32; x++) x3[x] = badd2(x3[x], v[x]);
        WSTAMP(5 + 16 * l);
      } else if (l == 0) {
        float2* mine = &g_part[2][c.j][row + z];
        const float2* sp = &g_part[2][2 * qd][row + z];
        fence_sched();
        p.drain();
        WSTAMP(10);
        put_partial(acc, mine, 0);
        WSTAMP(11);
        uint32_t yv[32];
        mbar_wait(c.bar + 8 * (BAR_OWN + wg), 0, p.budget);
#pragma unroll
        for (int x = 0; x < 16; x++)
          asm volatile("ld.shared.v2.u32 {%0,%1}, [%2];" : "=r"(yv[2 * x]), "=r"(yv[2 * x + 1]) : "r"(c.sm + SM_X + wg * 16384 + x * 1024 + t * 8) : "memory");
#pragma unroll
        for (int x = 0; x < 32; x++) asm volatile("cvt.rn.bf16x2.f32 %0, %1, %2;" : "=r"(x3[x]) : "f"(acc[2 * x + 1]), "f"(acc[2 * x]));
        fence_sched();
        poll_stats(sp, p.budget, s0, s1);
        WSTAMP(13);
        float nb0 = -s0.x * s0.y, nb1 = -s1.x * s1.y;
#pragma unroll
        for (int pn = 0; pn < 2; pn++) {
          if (pn == 1) { const float z = late_zero(c.sm + SM_ZERO); nb0 += z; nb1 += z; }
#pragma unroll
          for (int x = 16 * pn; x < 16 * pn + 16; x++) {
            const float r = (x & 1) ? s1.y : s0.y, nb = (x & 1) ? nb1 : nb0;
            asm("fma.rn.bf16x2 %0, %1, %2, %0;" : "+r"(x3[x]) : "r"(pack_bf16(fmaf(acc[2 * x], r, nb), fmaf(acc[2 * x + 1], r, nb))), "r"(yv[x]));
          }
          if (pn == 1) stage_tiles<16>(x3, stg);
          emit_panel(x3 + 16 * pn, gp + pn * 8 * CB_BYTES, pub + 8 * pn);
        }
      } else {
        const uint32_t ob = c.sm + SM_X + warp * 4096, oa = ob + (lane & 15) * 128 + (((lane >> 4) ^ (lane & 7)) << 4) + z;
        fence_sched();
        p.drain();
        WSTAMP(26);
#pragma unroll
        for (int pn = 0; pn < 2; pn++) {
#pragma unroll
          for (int x = 0; x < 8; x += 2) {
            const float* a = acc + 32 * pn + 4 * x;
            stsm_x4((oa ^ (x << 4)) + pn * 2048, pack_bf16(a[0], a[1]), pack_bf16(a[2], a[3]), pack_bf16(a[4], a[5]), pack_bf16(a[6], a[7]));
          }
          fence_async_smem();
          __syncwarp();
          if (elect_one()) {
            tma_store_2d(&maps.m[M_OUT], ob + pn * 2048, c.j * 128 + 64 * pn, 64 * (16 * wg + c.i) + 16 * (warp & 3));
            if (pn == 1) {
              bulk_commit();
              asm volatile("cp.async.bulk.wait_group.read 0;" ::: "memory");
            }
          }
        }
        __syncwarp();
      }
    }
    WSTAMP(27);
    cluster_exit_barrier();
    WSTAMP(30);
  }
}

typedef CUresult (*EncodeFn)(CUtensorMap*, CUtensorMapDataType, cuuint32_t, void*, const cuuint64_t*, const cuuint64_t*, const cuuint32_t*,
                             const cuuint32_t*, CUtensorMapInterleave, CUtensorMapSwizzle, CUtensorMapL2promotion, CUtensorMapFloatOOBfill);

void encode(EncodeFn fn, CUtensorMap* m, CUtensorMapDataType type, const void* ptr, int rank, const cuuint64_t* dims, const cuuint64_t* strides,
            const cuuint32_t* box, CUtensorMapSwizzle swizzle, CUtensorMapL2promotion promo = CU_TENSOR_MAP_L2_PROMOTION_L2_128B) {
  const cuuint32_t es[3] = {1, 1, 1};
  fn(m, type, rank, const_cast<void*>(ptr), dims, strides, box, es, CU_TENSOR_MAP_INTERLEAVE_NONE, swizzle, promo, CU_TENSOR_MAP_FLOAT_OOB_FILL_NONE);
}
void map_act(EncodeFn fn, CUtensorMap* m, const void* ptr, int cols, int rows = 64) {
  const cuuint64_t dims[2] = {(cuuint64_t)SEQ * 2, (cuuint64_t)cols / 8}, st[1] = {(cuuint64_t)CB_BYTES};
  const cuuint32_t box[2] = {(cuuint32_t)rows * 2, 8};
  encode(fn, m, CU_TENSOR_MAP_DATA_TYPE_UINT64, ptr, 2, dims, st, box, CU_TENSOR_MAP_SWIZZLE_NONE);
}
void map_rows(EncodeFn fn, CUtensorMap* m, const void* ptr, int rows, int cols, int box_rows, int box_cols, CUtensorMapSwizzle swizzle,
              CUtensorMapL2promotion promo) {
  const cuuint64_t dims[2] = {(cuuint64_t)cols, (cuuint64_t)rows}, st[1] = {(cuuint64_t)cols * 2};
  const cuuint32_t box[2] = {(cuuint32_t)box_cols, (cuuint32_t)box_rows};
  encode(fn, m, CU_TENSOR_MAP_DATA_TYPE_BFLOAT16, ptr, 2, dims, st, box, swizzle, promo);
}
void map_w(EncodeFn fn, CUtensorMap* m, const void* ptr, int rows, int cols, int panels) {
  const cuuint64_t dims[3] = {64, (cuuint64_t)rows, (cuuint64_t)cols / 64}, st[2] = {(cuuint64_t)cols * 2, 128};
  const cuuint32_t box[3] = {64, 64, (cuuint32_t)panels};
  encode(fn, m, CU_TENSOR_MAP_DATA_TYPE_BFLOAT16, ptr, 3, dims, st, box, CU_TENSOR_MAP_SWIZZLE_128B);
}

}

extern "C" void kernel_launch(void* const* d_in, const int* in_sizes, int n_in, void* d_out, int out_size) {
  (void)in_sizes; (void)n_in; (void)out_size;
  const bf16* q = (const bf16*)d_in[0];
  const bf16* k = (const bf16*)d_in[1];
  const bf16* v = (const bf16*)d_in[2];
  const bf16* shift_k = (const bf16*)d_in[3];
  const bf16* ssm_k = (const bf16*)d_in[4];
  const bf16* ssm_d = (const bf16*)d_in[5];
  const bf16* w1 = (const bf16*)d_in[7];
  const bf16* w2 = (const bf16*)d_in[8];
  const bf16* w3 = (const bf16*)d_in[9];
  const bf16* w4 = (const bf16*)d_in[10];

  static EncodeFn fn = nullptr;
  static void *p_x3, *p_h, *p_x1, *p_hid, *p_y;
  if (!fn) {
    void* p = nullptr;
    cudaDriverEntryPointQueryResult qr;
    cudaGetDriverEntryPoint("cuTensorMapEncodeTiled", &p, cudaEnableDefault, &qr);
    fn = (EncodeFn)p;
    cudaGetSymbolAddress(&p_x3, g_x3);
    cudaGetSymbolAddress(&p_h, g_h);
    cudaGetSymbolAddress(&p_x1, g_x1);
    cudaGetSymbolAddress(&p_hid, g_hid);
    cudaGetSymbolAddress(&p_y, g_y);
    cudaFuncSetAttribute(fused_kernel, cudaFuncAttributeMaxDynamicSharedMemorySize, MEGA_SMEM);
  }
  Params maps;
  map_act(fn, &maps.m[M_X3B], (const bf16*)p_x3 + SEQ * DM, DM);
  map_act(fn, &maps.m[M_X3S], p_x3, DM, 68);
  map_act(fn, &maps.m[M_H], p_h, DM);
  map_act(fn, &maps.m[M_HS], p_h, DM, 68);
  map_act(fn, &maps.m[M_X1], p_x1, DM);
  map_act(fn, &maps.m[M_HID], p_hid, FF);
  map_act(fn, &maps.m[M_Y], p_y, DM);
  map_rows(fn, &maps.m[M_OUT], d_out, SEQ, DM, 16, 64, CU_TENSOR_MAP_SWIZZLE_128B, CU_TENSOR_MAP_L2_PROMOTION_L2_128B);
  map_w(fn, &maps.m[M_W1], w1, DM, DM, 2);
  map_w(fn, &maps.m[M_W2], w2, DM, DM, 2);
  map_w(fn, &maps.m[M_W3A], w3, DM, FF, 4);
  map_w(fn, &maps.m[M_W3B], w3, DM, FF, 3);
  map_w(fn, &maps.m[M_W4], w4, FF, DM, 2);

  map_rows(fn, &maps.m[M_K], k, SEQ, DM, 256, 8, CU_TENSOR_MAP_SWIZZLE_NONE, CU_TENSOR_MAP_L2_PROMOTION_L2_128B);
  map_rows(fn, &maps.m[M_V], v, SEQ, DM, 256, 8, CU_TENSOR_MAP_SWIZZLE_NONE, CU_TENSOR_MAP_L2_PROMOTION_L2_128B);
  map_rows(fn, &maps.m[M_Q], q, SEQ, DM, 256, 8, CU_TENSOR_MAP_SWIZZLE_NONE, CU_TENSOR_MAP_L2_PROMOTION_L2_128B);
  map_rows(fn, &maps.m[M_W1C], w1, DM, DM, 256, 32, CU_TENSOR_MAP_SWIZZLE_64B, CU_TENSOR_MAP_L2_PROMOTION_L2_128B);
  map_rows(fn, &maps.m[M_W3C], w3, DM, FF, 256, 32, CU_TENSOR_MAP_SWIZZLE_64B, CU_TENSOR_MAP_L2_PROMOTION_L2_128B);
  maps.q = q; maps.shift_k = shift_k; maps.ssm_k = ssm_k; maps.ssm_d = ssm_d; maps.w2 = w2;
  fused_kernel<<<128, 384, MEGA_SMEM, cudaStreamPerThread>>>(maps);
}
```
